```python
import torch

def _softmax(x, axis=-1):
    return torch.softmax(x, dim=axis)
def _gelu(x):
    return torch.nn.functional.gelu(x, approximate="tanh")
def _silu(x):
    return torch.nn.functional.silu(x)
def _sigmoid(x):
    return torch.sigmoid(x)
def _layernorm(x, axis=-1, eps=1e-5):
    m = x.mean(dim=axis, keepdim=True)
    v = x.var(dim=axis, keepdim=True, unbiased=False)
    return (x - m) / torch.sqrt(v + eps)
def _scatter_add(tgt, idx, src, axis=0):
    return tgt.clone().index_add_(axis, idx, src)
def _segment_sum(src, seg, n):
    out = torch.zeros((n,) + src.shape[1:], dtype=src.dtype)
    return out.index_add_(0, seg, src)
def _pad(x, pw):
    flat = tuple(v for pair in reversed(pw) for v in pair)
    return torch.nn.functional.pad(x, flat)

kernel_name = 'recurrent_scan__linear_attn_block__dense_activation_gelu__prompt'

def setup_inputs():

    _w = (lambda a: (lambda t: t.to(torch.bfloat16) if t.is_floating_point() else t)(torch.as_tensor(a)))
    def _A_setup():
        B, S, D = 1, 2048, 576
        return {
            "x": _w((lambda *s: torch.randn(*s, dtype=torch.bfloat16) * 0.05)(B, S, D)),
            "wqkv": _w((lambda *s: torch.randn(*s, dtype=torch.bfloat16) * 0.2)(D, 3 * D)),
            "wo": _w((lambda *s: torch.randn(*s, dtype=torch.bfloat16) * 0.2)(D, D)),
        }
    _A_in = _A_setup()

    def _B_setup():
        B, S, D, F = 1, 2048, 576, 4608
        return {
            "x": _w((lambda *s: torch.randn(*s, dtype=torch.bfloat16) * 0.05)(B, S, D)),
            "w1": _w((lambda *s: torch.randn(*s, dtype=torch.bfloat16) * 0.4)(D, F) * (D ** -0.5)),
            "b1": _w((lambda *s: torch.randn(*s, dtype=torch.bfloat16) * 12.8)(F) * 0.01),
            "w2": _w((lambda *s: torch.randn(*s, dtype=torch.bfloat16) * 0.2)(F, D) * (F ** -0.5)),
            "b2": _w((lambda *s: torch.randn(*s, dtype=torch.bfloat16) * 1.6)(D) * 0.01),
        }
    _B_in = _B_setup()

    return {
        "A_x": _A_in["x"],
        "A_wqkv": _A_in["wqkv"],
        "A_wo": _A_in["wo"],
        "B_x": _B_in["x"],
        "B_w1": _B_in["w1"],
        "B_b1": _B_in["b1"],
        "B_w2": _B_in["w2"],
        "B_b2": _B_in["b2"],
    }

def reference(A_x, A_wqkv, A_wo, B_x, B_w1, B_b1, B_w2, B_b2):
    def _A_ref(x, wqkv, wo):
        B, S, D = x.shape
        H = 32; Dh = D // H
        qkv = (lambda x, *d: x.permute(*d))((x @ wqkv).reshape(B, S, 3, H, Dh), 2, 0, 3, 1, 4)
        q, k, v = qkv[0], qkv[1], qkv[2]
        phi = lambda t: torch.where(t > 0, t + 1, torch.exp(t)) + 1e-6
        pq, pk = phi(q), phi(k)
        kv = torch.einsum("bhsd,bhse->bhde", pk, v)
        z = torch.einsum("bhsd->bhd", pk)
        num = torch.einsum("bhqd,bhde->bhqe", pq, kv)
        den = torch.einsum("bhqd,bhd->bhq", pq, z)[..., None] + 1e-6
        o = num / den
        return (lambda x, *d: x.permute(*d))(o, 0, 2, 1, 3).reshape(B, S, D) @ wo

    def _B_ref(x, w1, b1, w2, b2):
        h = torch.einsum("bsd,df->bsf", x, w1) + b1
        h = _gelu(h)
        return torch.einsum("bsf,fd->bsd", h, w2) + b2

    x = A_x
    xn = _layernorm(x, axis=-1)
    s = _A_ref(xn, A_wqkv, A_wo)
    g = _silu(_B_ref(xn, B_w1, B_b1, B_w2, B_b2))
    return x + s * g
```

```cpp
#include <cuda_runtime.h>
#include <cuda.h>
#include <cuda_bf16.h>
#include <stdint.h>

namespace {

constexpr int S_ = 2048, D_ = 576, F_ = 4608, Q3_ = 1728;
constexpr int NSTAGE = 5, STAGE_BYTES = 16384;
constexpr int SM_A = 0, SM_B = 147456, SM_BIAS = SM_B + NSTAGE * STAGE_BYTES, SM_BAR = SM_BIAS + 2304;
constexpr int SMEM_BYTES = SM_BAR + 128;
constexpr int NTHREADS = 384;
constexpr int NCTAS = 132;

__device__ __nv_bfloat16 g_qkv[S_ * Q3_];
__device__ __align__(1024) __nv_bfloat16 g_o[S_ * D_];
__device__ float4 g_kvp4[32 * 16 * 3 * 32];
__device__ float2 g_kvp2[32 * 16 * 3 * 32];
__device__ uint32_t g_kvt[32 * 9 * 32];
__device__ uint4 g_part[16 * 8 * 9 * 36 * 32];
__device__ uint32_t g_f_qkv[16 * 8];
__device__ uint32_t g_f_kvp[32];
__device__ uint32_t g_f_kvt[32];
__device__ uint32_t g_f_o[16];
__device__ uint32_t g_f_part[16 * 8 * 16];
__device__ uint32_t g_epoch[NCTAS];

__device__ __forceinline__ uint32_t smem_u32(const void* p) { return (uint32_t)__cvta_generic_to_shared(p); }
__device__ __forceinline__ void mbar_init(uint32_t a, int c) { asm volatile("mbarrier.init.shared::cta.b64 [%0], %1;" ::"r"(a), "r"(c)); }
__device__ __forceinline__ void mbar_expect(uint32_t a, uint32_t b) { asm volatile("mbarrier.arrive.expect_tx.shared::cta.b64 _, [%0], %1;" ::"r"(a), "r"(b) : "memory"); }
__device__ __forceinline__ void mbar_arrive(uint32_t a) { asm volatile("mbarrier.arrive.shared::cta.b64 _, [%0];" ::"r"(a) : "memory"); }
__device__ __forceinline__ void mbar_arrive_cl(uint32_t a) { asm volatile("mbarrier.arrive.shared::cluster.b64 _, [%0];" ::"r"(a) : "memory"); }
__device__ __forceinline__ uint32_t mapa(uint32_t a, uint32_t cta) { uint32_t r; asm volatile("mapa.shared::cluster.u32 %0, %1, %2;" : "=r"(r) : "r"(a), "r"(cta)); return r; }
__device__ __forceinline__ void mbar_wait(uint32_t a, uint32_t ph) {
  uint32_t ok; int it = 0;
  do {
    asm volatile("{.reg .pred p; mbarrier.try_wait.parity.shared::cta.b64 p, [%1], %2; selp.u32 %0,1,0,p;}" : "=r"(ok) : "r"(a), "r"(ph) : "memory");
  } while (!ok && ++it < (1 << 18));
}
__device__ __forceinline__ void tma2d(uint32_t dst, const CUtensorMap* m, int c0, int c1, uint32_t bar) {
  asm volatile("cp.async.bulk.tensor.2d.shared::cluster.global.mbarrier::complete_tx::bytes [%0], [%1, {%3,%4}], [%2];" ::"r"(dst), "l"(m), "r"(bar), "r"(c0), "r"(c1) : "memory");
}
__device__ __forceinline__ void tma2d_mc(uint32_t dst, const CUtensorMap* m, int c0, int c1, uint32_t bar) {
  asm volatile("cp.async.bulk.tensor.2d.shared::cluster.global.mbarrier::complete_tx::bytes.multicast::cluster [%0], [%1, {%3,%4}], [%2], %5;" ::"r"(dst), "l"(m), "r"(bar), "r"(c0), "r"(c1), "h"((uint16_t)3) : "memory");
}
__device__ __forceinline__ void cluster_arrive() { asm volatile("barrier.cluster.arrive.release.aligned;" ::: "memory"); }
__device__ __forceinline__ void cluster_wait() { asm volatile("barrier.cluster.wait.acquire.aligned;" ::: "memory"); }
__device__ __forceinline__ void wg_fence() { asm volatile("wgmma.fence.sync.aligned;" ::: "memory"); }
__device__ __forceinline__ void wg_commit() { asm volatile("wgmma.commit_group.sync.aligned;" ::: "memory"); }
template <int n> __device__ __forceinline__ void wg_wait() { asm volatile("wgmma.wait_group.sync.aligned %0;" ::"n"(n) : "memory"); }
__device__ __forceinline__ uint32_t ld_acquire(const uint32_t* p) { uint32_t v; asm volatile("ld.acquire.gpu.global.u32 %0, [%1];" : "=r"(v) : "l"(p) : "memory"); return v; }
__device__ __forceinline__ void flag_wait(const uint32_t* p, uint32_t target) {
  int it = 0;
  while ((int)(ld_acquire(p) - target) < 0 && ++it < (1 << 21)) __nanosleep(40);
}
__device__ __forceinline__ void flag_signal_warp(uint32_t* p) {
  __syncwarp();
  if ((threadIdx.x & 31) == 0) asm volatile("red.release.gpu.global.add.u32 [%0], 1;" ::"l"(p) : "memory");
}
__device__ __forceinline__ uint32_t pack_bf16(float lo, float hi) { uint32_t r; asm("cvt.rn.bf16x2.f32 %0, %1, %2;" : "=r"(r) : "f"(hi), "f"(lo)); return r; }
__device__ __forceinline__ float bf_lo(uint32_t v) { return __uint_as_float(v << 16); }
__device__ __forceinline__ float bf_hi(uint32_t v) { return __uint_as_float(v & 0xffff0000u); }
__device__ __forceinline__ float tanh_fast(float x) { float r; asm("tanh.approx.f32 %0, %1;" : "=f"(r) : "f"(x)); return r; }
__device__ __forceinline__ uint32_t movmat(uint32_t a) { uint32_t d; asm volatile("movmatrix.sync.aligned.m8n8.trans.b16 %0, %1;" : "=r"(d) : "r"(a)); return d; }
__device__ __forceinline__ void mma16816(float* c, uint32_t a0, uint32_t a1, uint32_t a2, uint32_t a3, uint32_t b0, uint32_t b1) {
  asm volatile("mma.sync.aligned.m16n8k16.row.col.f32.bf16.bf16.f32 {%0,%1,%2,%3}, {%4,%5,%6,%7}, {%8,%9}, {%0,%1,%2,%3};"
               : "+f"(c[0]), "+f"(c[1]), "+f"(c[2]), "+f"(c[3]) : "r"(a0), "r"(a1), "r"(a2), "r"(a3), "r"(b0), "r"(b1));
}
__device__ __forceinline__ uint32_t ldcg32(const void* p) { uint32_t v; asm volatile("ld.global.cg.u32 %0, [%1];" : "=r"(v) : "l"(p) : "memory"); return v; }
__device__ __forceinline__ uint4 ldcg128(const void* p) { uint4 v; asm volatile("ld.global.cg.v4.u32 {%0,%1,%2,%3}, [%4];" : "=r"(v.x), "=r"(v.y), "=r"(v.z), "=r"(v.w) : "l"(p) : "memory"); return v; }
__device__ __forceinline__ uint2 ldcg64(const void* p) { uint2 v; asm volatile("ld.global.cg.v2.u32 {%0,%1}, [%2];" : "=r"(v.x), "=r"(v.y) : "l"(p) : "memory"); return v; }

template <int N> __device__ __forceinline__ void wgmma_ss(float* d, uint64_t da, uint64_t db, int sc);
template <int N> __device__ __forceinline__ void wgmma_rs(float* d, const uint32_t* a, uint64_t db, int sc);
template <> __device__ __forceinline__ void wgmma_ss<128>(float* d, uint64_t da, uint64_t db, int sc) {
  asm volatile("{.reg .pred p; setp.ne.b32 p, %66, 0; wgmma.mma_async.sync.aligned.m64n128k16.f32.bf16.bf16 {%0, %1, %2, %3, %4, %5, %6, %7, %8, %9, %10, %11, %12, %13, %14, %15, %16, %17, %18, %19, %20, %21, %22, %23, %24, %25, %26, %27, %28, %29, %30, %31, %32, %33, %34, %35, %36, %37, %38, %39, %40, %41, %42, %43, %44, %45, %46, %47, %48, %49, %50, %51, %52, %53, %54, %55, %56, %57, %58, %59, %60, %61, %62, %63}, %64, %65, p, 1, 1, 0, 1;}"
   : "+f"(d[0]), "+f"(d[1]), "+f"(d[2]), "+f"(d[3]), "+f"(d[4]), "+f"(d[5]), "+f"(d[6]), "+f"(d[7]), "+f"(d[8]), "+f"(d[9]), "+f"(d[10]), "+f"(d[11]), "+f"(d[12]), "+f"(d[13]), "+f"(d[14]), "+f"(d[15]), "+f"(d[16]), "+f"(d[17]), "+f"(d[18]), "+f"(d[19]), "+f"(d[20]), "+f"(d[21]), "+f"(d[22]), "+f"(d[23]), "+f"(d[24]), "+f"(d[25]), "+f"(d[26]), "+f"(d[27]), "+f"(d[28]), "+f"(d[29]), "+f"(d[30]), "+f"(d[31]), "+f"(d[32]), "+f"(d[33]), "+f"(d[34]), "+f"(d[35]), "+f"(d[36]), "+f"(d[37]), "+f"(d[38]), "+f"(d[39]), "+f"(d[40]), "+f"(d[41]), "+f"(d[42]), "+f"(d[43]), "+f"(d[44]), "+f"(d[45]), "+f"(d[46]), "+f"(d[47]), "+f"(d[48]), "+f"(d[49]), "+f"(d[50]), "+f"(d[51]), "+f"(d[52]), "+f"(d[53]), "+f"(d[54]), "+f"(d[55]), "+f"(d[56]), "+f"(d[57]), "+f"(d[58]), "+f"(d[59]), "+f"(d[60]), "+f"(d[61]), "+f"(d[62]), "+f"(d[63]) : "l"(da), "l"(db), "r"(sc));
}
template <> __device__ __forceinline__ void wgmma_ss<160>(float* d, uint64_t da, uint64_t db, int sc) {
  asm volatile("{.reg .pred p; setp.ne.b32 p, %82, 0; wgmma.mma_async.sync.aligned.m64n160k16.f32.bf16.bf16 {%0, %1, %2, %3, %4, %5, %6, %7, %8, %9, %10, %11, %12, %13, %14, %15, %16, %17, %18, %19, %20, %21, %22, %23, %24, %25, %26, %27, %28, %29, %30, %31, %32, %33, %34, %35, %36, %37, %38, %39, %40, %41, %42, %43, %44, %45, %46, %47, %48, %49, %50, %51, %52, %53, %54, %55, %56, %57, %58, %59, %60, %61, %62, %63, %64, %65, %66, %67, %68, %69, %70, %71, %72, %73, %74, %75, %76, %77, %78, %79}, %80, %81, p, 1, 1, 0, 1;}"
   : "+f"(d[0]), "+f"(d[1]), "+f"(d[2]), "+f"(d[3]), "+f"(d[4]), "+f"(d[5]), "+f"(d[6]), "+f"(d[7]), "+f"(d[8]), "+f"(d[9]), "+f"(d[10]), "+f"(d[11]), "+f"(d[12]), "+f"(d[13]), "+f"(d[14]), "+f"(d[15]), "+f"(d[16]), "+f"(d[17]), "+f"(d[18]), "+f"(d[19]), "+f"(d[20]), "+f"(d[21]), "+f"(d[22]), "+f"(d[23]), "+f"(d[24]), "+f"(d[25]), "+f"(d[26]), "+f"(d[27]), "+f"(d[28]), "+f"(d[29]), "+f"(d[30]), "+f"(d[31]), "+f"(d[32]), "+f"(d[33]), "+f"(d[34]), "+f"(d[35]), "+f"(d[36]), "+f"(d[37]), "+f"(d[38]), "+f"(d[39]), "+f"(d[40]), "+f"(d[41]), "+f"(d[42]), "+f"(d[43]), "+f"(d[44]), "+f"(d[45]), "+f"(d[46]), "+f"(d[47]), "+f"(d[48]), "+f"(d[49]), "+f"(d[50]), "+f"(d[51]), "+f"(d[52]), "+f"(d[53]), "+f"(d[54]), "+f"(d[55]), "+f"(d[56]), "+f"(d[57]), "+f"(d[58]), "+f"(d[59]), "+f"(d[60]), "+f"(d[61]), "+f"(d[62]), "+f"(d[63]), "+f"(d[64]), "+f"(d[65]), "+f"(d[66]), "+f"(d[67]), "+f"(d[68]), "+f"(d[69]), "+f"(d[70]), "+f"(d[71]), "+f"(d[72]), "+f"(d[73]), "+f"(d[74]), "+f"(d[75]), "+f"(d[76]), "+f"(d[77]), "+f"(d[78]), "+f"(d[79]) : "l"(da), "l"(db), "r"(sc));
}
template <> __device__ __forceinline__ void wgmma_ss<192>(float* d, uint64_t da, uint64_t db, int sc) {
  asm volatile("{.reg .pred p; setp.ne.b32 p, %98, 0; wgmma.mma_async.sync.aligned.m64n192k16.f32.bf16.bf16 {%0, %1, %2, %3, %4, %5, %6, %7, %8, %9, %10, %11, %12, %13, %14, %15, %16, %17, %18, %19, %20, %21, %22, %23, %24, %25, %26, %27, %28, %29, %30, %31, %32, %33, %34, %35, %36, %37, %38, %39, %40, %41, %42, %43, %44, %45, %46, %47, %48, %49, %50, %51, %52, %53, %54, %55, %56, %57, %58, %59, %60, %61, %62, %63, %64, %65, %66, %67, %68, %69, %70, %71, %72, %73, %74, %75, %76, %77, %78, %79, %80, %81, %82, %83, %84, %85, %86, %87, %88, %89, %90, %91, %92, %93, %94, %95}, %96, %97, p, 1, 1, 0, 1;}"
   : "+f"(d[0]), "+f"(d[1]), "+f"(d[2]), "+f"(d[3]), "+f"(d[4]), "+f"(d[5]), "+f"(d[6]), "+f"(d[7]), "+f"(d[8]), "+f"(d[9]), "+f"(d[10]), "+f"(d[11]), "+f"(d[12]), "+f"(d[13]), "+f"(d[14]), "+f"(d[15]), "+f"(d[16]), "+f"(d[17]), "+f"(d[18]), "+f"(d[19]), "+f"(d[20]), "+f"(d[21]), "+f"(d[22]), "+f"(d[23]), "+f"(d[24]), "+f"(d[25]), "+f"(d[26]), "+f"(d[27]), "+f"(d[28]), "+f"(d[29]), "+f"(d[30]), "+f"(d[31]), "+f"(d[32]), "+f"(d[33]), "+f"(d[34]), "+f"(d[35]), "+f"(d[36]), "+f"(d[37]), "+f"(d[38]), "+f"(d[39]), "+f"(d[40]), "+f"(d[41]), "+f"(d[42]), "+f"(d[43]), "+f"(d[44]), "+f"(d[45]), "+f"(d[46]), "+f"(d[47]), "+f"(d[48]), "+f"(d[49]), "+f"(d[50]), "+f"(d[51]), "+f"(d[52]), "+f"(d[53]), "+f"(d[54]), "+f"(d[55]), "+f"(d[56]), "+f"(d[57]), "+f"(d[58]), "+f"(d[59]), "+f"(d[60]), "+f"(d[61]), "+f"(d[62]), "+f"(d[63]), "+f"(d[64]), "+f"(d[65]), "+f"(d[66]), "+f"(d[67]), "+f"(d[68]), "+f"(d[69]), "+f"(d[70]), "+f"(d[71]), "+f"(d[72]), "+f"(d[73]), "+f"(d[74]), "+f"(d[75]), "+f"(d[76]), "+f"(d[77]), "+f"(d[78]), "+f"(d[79]), "+f"(d[80]), "+f"(d[81]), "+f"(d[82]), "+f"(d[83]), "+f"(d[84]), "+f"(d[85]), "+f"(d[86]), "+f"(d[87]), "+f"(d[88]), "+f"(d[89]), "+f"(d[90]), "+f"(d[91]), "+f"(d[92]), "+f"(d[93]), "+f"(d[94]), "+f"(d[95]) : "l"(da), "l"(db), "r"(sc));
}
template <> __device__ __forceinline__ void wgmma_rs<64>(float* d, const uint32_t* a, uint64_t db, int sc) {
  asm volatile("{.reg .pred p; setp.ne.b32 p, %37, 0; wgmma.mma_async.sync.aligned.m64n64k16.f32.bf16.bf16 {%0, %1, %2, %3, %4, %5, %6, %7, %8, %9, %10, %11, %12, %13, %14, %15, %16, %17, %18, %19, %20, %21, %22, %23, %24, %25, %26, %27, %28, %29, %30, %31}, {%32,%33,%34,%35}, %36, p, 1, 1, 1;}"
   : "+f"(d[0]), "+f"(d[1]), "+f"(d[2]), "+f"(d[3]), "+f"(d[4]), "+f"(d[5]), "+f"(d[6]), "+f"(d[7]), "+f"(d[8]), "+f"(d[9]), "+f"(d[10]), "+f"(d[11]), "+f"(d[12]), "+f"(d[13]), "+f"(d[14]), "+f"(d[15]), "+f"(d[16]), "+f"(d[17]), "+f"(d[18]), "+f"(d[19]), "+f"(d[20]), "+f"(d[21]), "+f"(d[22]), "+f"(d[23]), "+f"(d[24]), "+f"(d[25]), "+f"(d[26]), "+f"(d[27]), "+f"(d[28]), "+f"(d[29]), "+f"(d[30]), "+f"(d[31]) : "r"(a[0]), "r"(a[1]), "r"(a[2]), "r"(a[3]), "l"(db), "r"(sc));
}
template <> __device__ __forceinline__ void wgmma_rs<128>(float* d, const uint32_t* a, uint64_t db, int sc) {
  asm volatile("{.reg .pred p; setp.ne.b32 p, %69, 0; wgmma.mma_async.sync.aligned.m64n128k16.f32.bf16.bf16 {%0, %1, %2, %3, %4, %5, %6, %7, %8, %9, %10, %11, %12, %13, %14, %15, %16, %17, %18, %19, %20, %21, %22, %23, %24, %25, %26, %27, %28, %29, %30, %31, %32, %33, %34, %35, %36, %37, %38, %39, %40, %41, %42, %43, %44, %45, %46, %47, %48, %49, %50, %51, %52, %53, %54, %55, %56, %57, %58, %59, %60, %61, %62, %63}, {%64,%65,%66,%67}, %68, p, 1, 1, 1;}"
   : "+f"(d[0]), "+f"(d[1]), "+f"(d[2]), "+f"(d[3]), "+f"(d[4]), "+f"(d[5]), "+f"(d[6]), "+f"(d[7]), "+f"(d[8]), "+f"(d[9]), "+f"(d[10]), "+f"(d[11]), "+f"(d[12]), "+f"(d[13]), "+f"(d[14]), "+f"(d[15]), "+f"(d[16]), "+f"(d[17]), "+f"(d[18]), "+f"(d[19]), "+f"(d[20]), "+f"(d[21]), "+f"(d[22]), "+f"(d[23]), "+f"(d[24]), "+f"(d[25]), "+f"(d[26]), "+f"(d[27]), "+f"(d[28]), "+f"(d[29]), "+f"(d[30]), "+f"(d[31]), "+f"(d[32]), "+f"(d[33]), "+f"(d[34]), "+f"(d[35]), "+f"(d[36]), "+f"(d[37]), "+f"(d[38]), "+f"(d[39]), "+f"(d[40]), "+f"(d[41]), "+f"(d[42]), "+f"(d[43]), "+f"(d[44]), "+f"(d[45]), "+f"(d[46]), "+f"(d[47]), "+f"(d[48]), "+f"(d[49]), "+f"(d[50]), "+f"(d[51]), "+f"(d[52]), "+f"(d[53]), "+f"(d[54]), "+f"(d[55]), "+f"(d[56]), "+f"(d[57]), "+f"(d[58]), "+f"(d[59]), "+f"(d[60]), "+f"(d[61]), "+f"(d[62]), "+f"(d[63]) : "r"(a[0]), "r"(a[1]), "r"(a[2]), "r"(a[3]), "l"(db), "r"(sc));
}


__device__ __forceinline__ uint64_t mkdesc(uint32_t addr, uint32_t lbo, uint32_t sbo) {
  return (uint64_t)((addr & 0x3FFFF) >> 4) | ((uint64_t)(lbo >> 4) << 16) | ((uint64_t)(sbo >> 4) << 32) | (1ull << 62);
}
template <int n> __device__ __forceinline__ void fence_regs(float (&a)[n]) {
#pragma unroll
  for (int i = 0; i < n; i++) asm volatile("" : "+f"(a[i])::"memory");
}

struct Ctx {
  uint32_t full;
  uint32_t emb;
  bool sig;
  uint32_t stage, phase, prev;
  bool has_prev;
  uint32_t sb;
  uint64_t descA;
  __device__ __forceinline__ void release_prev() { if (sig && has_prev) mbar_arrive_cl(emb + 8 * prev); }
  __device__ __forceinline__ void adv() { prev = stage; has_prev = true; if (++stage == NSTAGE) { stage = 0; phase ^= 1; } }
};

template <int N, int KS, class Epi>
__device__ __forceinline__ void tile_ss(float (&acc)[N / 2], Ctx& c, Epi epi) {
  constexpr int NSTG = 36 / KS;
  constexpr int LBO = KS * 2048;
#pragma unroll
  for (int s = 0; s < NSTG; s++) {
    mbar_wait(c.full + 8 * c.stage, c.phase);
    wg_fence();
    uint64_t db = mkdesc(c.sb + c.stage * STAGE_BYTES, LBO, 1024);
#pragma unroll
    for (int kk = 0; kk < KS; kk++) {
      const int kg = s * KS + kk;
      wgmma_ss<N>(acc, c.descA + (uint64_t)(((kg >> 2) * 16384 + (kg & 3) * 32) >> 4), db + kk * 128, kg != 0);
    }
    wg_commit();
    wg_wait<1>();
    c.release_prev();
    epi(s);
    c.adv();
  }
}
template <int N, int KS, class Epi>
__device__ __forceinline__ void tile_rs(float (&acc)[N / 2], uint32_t (&h)[144], Ctx& c, Epi epi) {
  constexpr int NSTG = (36 + KS - 1) / KS;
#pragma unroll
  for (int s = 0; s < NSTG; s++) {
    mbar_wait(c.full + 8 * c.stage, c.phase);
    wg_fence();
    uint64_t db = mkdesc(c.sb + c.stage * STAGE_BYTES, 8192, 1024);
#pragma unroll
    for (int kk = 0; kk < KS; kk++) {
      const int kg = s * KS + kk;
      if (kg < 36) wgmma_rs<N>(acc, &h[4 * kg], db + kk * 128, kg != 0);
    }
    wg_commit();
    wg_wait<1>();
    c.release_prev();
    epi(s);
    c.adv();
  }
}
__device__ __forceinline__ void drain(Ctx& c) { wg_wait<0>(); c.release_prev(); c.has_prev = false; }

__device__ __forceinline__ float gelu2(float x) {
  float u = x * fmaf(x * x, 0.0356774081f, 0.7978845608f);
  return fmaf(x, tanh_fast(u), x);
}
__device__ __forceinline__ void gelu_group(const float* a, uint32_t* h, const float* bias  ) {
  float2 b0 = *reinterpret_cast<const float2*>(bias);
  float2 b1 = *reinterpret_cast<const float2*>(bias + 8);
  h[0] = pack_bf16(gelu2(a[0] + b0.x), gelu2(a[1] + b0.y));
  h[1] = pack_bf16(gelu2(a[2] + b0.x), gelu2(a[3] + b0.y));
  h[2] = pack_bf16(gelu2(a[4] + b1.x), gelu2(a[5] + b1.y));
  h[3] = pack_bf16(gelu2(a[6] + b1.x), gelu2(a[7] + b1.y));
}
__device__ __forceinline__ float phi(float t) { return (t > 0.f ? t + 1.f : __expf(t)) + 1e-6f; }
__device__ __forceinline__ void qkv_group(const float* a, __nv_bfloat16* p  , bool do_phi) {
  float v[8];
#pragma unroll
  for (int i = 0; i < 8; i++) v[i] = do_phi ? phi(a[i]) : a[i];
  *reinterpret_cast<uint32_t*>(p) = pack_bf16(v[0], v[1]);
  *reinterpret_cast<uint32_t*>(p + 8 * Q3_) = pack_bf16(v[2], v[3]);
  *reinterpret_cast<uint32_t*>(p + 8) = pack_bf16(v[4], v[5]);
  *reinterpret_cast<uint32_t*>(p + 8 * Q3_ + 8) = pack_bf16(v[6], v[7]);
}
__device__ __forceinline__ void part_group(const float* a, uint4* p) {
  *p = make_uint4(pack_bf16(a[0], a[1]), pack_bf16(a[2], a[3]), pack_bf16(a[4], a[5]), pack_bf16(a[6], a[7]));
}
__device__ __forceinline__ float silu(float y) { return __fdividef(y, 1.f + __expf(-y)); }

struct Params {
  CUtensorMap tm_wqkv, tm_w1, tm_w2, tm_wo, tm_o;
  const __nv_bfloat16 *x, *b1, *b2, *wqkv, *w1, *w2, *wo;
  __nv_bfloat16* out;
};

__global__ void __launch_bounds__(NTHREADS, 1) fused_kernel(const __grid_constant__ Params P) {
  extern __shared__ __align__(1024) uint8_t smem[];
  const uint32_t sbase = smem_u32(smem);
  const int tid = threadIdx.x, warp = tid >> 5, lane = tid & 31;
  const int g = lane >> 2, t = lane & 3;
  const uint32_t ep = g_epoch[blockIdx.x] + 1;

  if (blockIdx.x >= 128) {
    const int a = blockIdx.x - 128;
    if (warp < 8) {
      const int head = a * 8 + warp;
      if (lane == 0) flag_wait(&g_f_kvp[head], 16 * ep);
      __syncwarp();
      float s4[3][4], s2[3][2];
#pragma unroll
      for (int j = 0; j < 3; j++) { s4[j][0] = s4[j][1] = s4[j][2] = s4[j][3] = 0.f; s2[j][0] = s2[j][1] = 0.f; }
#pragma unroll 4
      for (int m = 0; m < 16; m++) {
#pragma unroll
        for (int j = 0; j < 3; j++) {
          uint4 v = ldcg128(&g_kvp4[((head * 16 + m) * 3 + j) * 32 + lane]);
          uint2 w = ldcg64(&g_kvp2[((head * 16 + m) * 3 + j) * 32 + lane]);
          s4[j][0] += __uint_as_float(v.x); s4[j][1] += __uint_as_float(v.y); s4[j][2] += __uint_as_float(v.z); s4[j][3] += __uint_as_float(v.w);
          s2[j][0] += __uint_as_float(w.x); s2[j][1] += __uint_as_float(w.y);
        }
      }
#pragma unroll
      for (int j = 0; j < 3; j++) {
        g_kvt[(head * 9 + 0 + j) * 32 + lane] = pack_bf16(s4[j][0], s4[j][1]);
        g_kvt[(head * 9 + 3 + j) * 32 + lane] = pack_bf16(s4[j][2], s4[j][3]);
        g_kvt[(head * 9 + 6 + j) * 32 + lane] = pack_bf16(s2[j][0], s2[j][1]);
      }
      flag_signal_warp(&g_f_kvt[head]);
    } else if (lane == 0) {
      const int id = a * 4 + (warp - 8);
      constexpr uint32_t CH = 9216 * 2;
      const char* w1 = (const char*)P.w1; const char* w2 = (const char*)P.w2; const char* wo = (const char*)P.wo;
      for (int i = id; i < 288; i += 16) asm volatile("cp.async.bulk.prefetch.L2.global [%0], %1;" ::"l"(w1 + (size_t)i * CH), "r"(CH) : "memory");
      for (int i = id; i < 288; i += 16) asm volatile("cp.async.bulk.prefetch.L2.global [%0], %1;" ::"l"(w2 + (size_t)i * CH), "r"(CH) : "memory");
      for (int i = id; i < 36; i += 16) asm volatile("cp.async.bulk.prefetch.L2.global [%0], %1;" ::"l"(wo + (size_t)i * CH), "r"(CH) : "memory");
    }
    __syncthreads();
    if (tid == 0) g_epoch[blockIdx.x] = ep;
    return;
  }

  const int cl = blockIdx.x >> 1, rank = blockIdx.x & 1;
  const int f = cl & 7, m = (cl >> 3) * 2 + rank;
  const bool srole = f >= 6;
  const uint32_t bar_full = sbase + SM_BAR, bar_empty = bar_full + 8 * NSTAGE, bar_xfree = bar_empty + 8 * NSTAGE, bar_ofull = bar_xfree + 8;

  if (tid == 0) {
    for (int i = 0; i < NSTAGE; i++) { mbar_init(bar_full + 8 * i, 1); mbar_init(bar_empty + 8 * i, 4); }
    mbar_init(bar_xfree, 2); mbar_init(bar_ofull, 1);
    asm volatile("fence.mbarrier_init.release.cluster;" ::: "memory");
  }
  __syncwarp();
  cluster_arrive();

  if (warp >= 8) {
    asm volatile("setmaxnreg.dec.sync.aligned.u32 56;");
    cluster_wait();
    if (warp == 8) {
      if (lane == 0) {
        uint32_t stage = 0, phase = 1;
        const uint32_t sb = sbase + SM_B;
        auto k64 = [&](const CUtensorMap* map, int col, int row0) {
          for (int kb = 0; kb < 9; kb++) {
            mbar_wait(bar_empty + 8 * stage, phase);
            mbar_expect(bar_full + 8 * stage, 16384);
            uint32_t dst = sb + stage * STAGE_BYTES + rank * 4096;
            tma2d_mc(dst, map, col, row0 + kb * 64 + rank * 32, bar_full + 8 * stage);
            tma2d_mc(dst + 8192, map, col + 64, row0 + kb * 64 + rank * 32, bar_full + 8 * stage);
            if (++stage == NSTAGE) { stage = 0; phase ^= 1; }
          }
        };
        auto k32 = [&](const CUtensorMap* map, int col, int row0) {
          for (int st = 0; st < 18; st++) {
            mbar_wait(bar_empty + 8 * stage, phase);
            mbar_expect(bar_full + 8 * stage, 12288);
            uint32_t dst = sb + stage * STAGE_BYTES;
            if (((st ^ rank) & 1) == 0) {
              tma2d_mc(dst, map, col, row0 + st * 32, bar_full + 8 * stage);
              tma2d_mc(dst + 8192, map, col + 128, row0 + st * 32, bar_full + 8 * stage);
            } else {
              tma2d_mc(dst + 4096, map, col + 64, row0 + st * 32, bar_full + 8 * stage);
            }
            if (++stage == NSTAGE) { stage = 0; phase ^= 1; }
          }
        };
        if (!srole) { k32(&P.tm_wqkv, 288 * f, 0); k64(&P.tm_wqkv, 288 * f + 160, 0); }
        k32(&P.tm_w1, 576 * f, 0);
        for (int i = 0; i < 3; i++) k64(&P.tm_w1, 576 * f + 192 + 128 * i, 0);
        for (int st = 0; st < 5; st++) {
          mbar_wait(bar_empty + 8 * stage, phase);
          mbar_expect(bar_full + 8 * stage, st < 4 ? 16384 : 8192);
          uint32_t dst = sb + stage * STAGE_BYTES + rank * 4096;
          tma2d_mc(dst, &P.tm_w2, 0, 576 * f + st * 128 + rank * 32, bar_full + 8 * stage);
          if (st < 4) tma2d_mc(dst + 8192, &P.tm_w2, 0, 576 * f + st * 128 + 64 + rank * 32, bar_full + 8 * stage);
          if (++stage == NSTAGE) { stage = 0; phase ^= 1; }
        }
        for (int i = 0; i < 4; i++) k64(&P.tm_w2, 64 + 128 * i, 576 * f);
        if (srole) { k32(&P.tm_wo, 288 * (f - 6), 0); k64(&P.tm_wo, 288 * (f - 6) + 160, 0); }
      }
      __syncwarp();
    } else {
      const int aw = warp - 9;
      const int hi = f >> 2;
      const __nv_bfloat16* qrow = g_qkv + (size_t)(m * 128 + g) * Q3_ + 2 * t;
      if (aw < 2) {
        if (lane == 0) { flag_wait(&g_f_qkv[m * 8 + 2 + hi], 16 * ep); flag_wait(&g_f_qkv[m * 8 + 4 + hi], 16 * ep); }
        __syncwarp();
#pragma unroll 1
        for (int hh = 0; hh < 2; hh++) {
          const int head = 4 * f + 2 * aw + hh;
          float c0[3][4], c1[3][4];
#pragma unroll
          for (int j = 0; j < 3; j++) { c0[j][0] = c0[j][1] = c0[j][2] = c0[j][3] = 0.f; c1[j][0] = c1[j][1] = c1[j][2] = c1[j][3] = 0.f; }
#pragma unroll 2
          for (int ks = 0; ks < 8; ks++) {
            const __nv_bfloat16* pk = qrow + (size_t)ks * 16 * Q3_ + 576 + head * 18;
            const __nv_bfloat16* pv = pk + 576;
            uint32_t kf[3][2], vf[3][2];
#pragma unroll
            for (int r = 0; r < 2; r++) {
              kf[0][r] = ldcg32(pk + r * 8 * Q3_); kf[1][r] = ldcg32(pk + r * 8 * Q3_ + 8);
              kf[2][r] = (t == 0) ? ldcg32(pk + r * 8 * Q3_ + 16) : 0u;
              vf[0][r] = ldcg32(pv + r * 8 * Q3_); vf[1][r] = ldcg32(pv + r * 8 * Q3_ + 8);
              vf[2][r] = (t == 0) ? ldcg32(pv + r * 8 * Q3_ + 16) : (t == 1 ? 0x00003f80u : 0u);
            }
#pragma unroll
            for (int j = 0; j < 3; j++) { kf[j][0] = movmat(kf[j][0]); kf[j][1] = movmat(kf[j][1]); vf[j][0] = movmat(vf[j][0]); vf[j][1] = movmat(vf[j][1]); }
#pragma unroll
            for (int j = 0; j < 3; j++) {
              mma16816(c0[j], vf[0][0], vf[1][0], vf[0][1], vf[1][1], kf[j][0], kf[j][1]);
              mma16816(c1[j], vf[2][0], 0u, vf[2][1], 0u, kf[j][0], kf[j][1]);
            }
          }
#pragma unroll
          for (int j = 0; j < 3; j++) {
            g_kvp4[((head * 16 + m) * 3 + j) * 32 + lane] = make_float4(c0[j][0], c0[j][1], c0[j][2], c0[j][3]);
            g_kvp2[((head * 16 + m) * 3 + j) * 32 + lane] = make_float2(c1[j][0], c1[j][1]);
          }
          flag_signal_warp(&g_f_kvp[head]);
        }
      }
      if (lane == 0) flag_wait(&g_f_qkv[m * 8 + hi], 16 * ep);
      if (lane < 4) flag_wait(&g_f_kvt[4 * f + lane], ep);
      __syncwarp();
#pragma unroll 1
      for (int hh = 0; hh < 4; hh++) {
        const int head = 4 * f + hh;
        uint32_t bf[9];
#pragma unroll
        for (int i = 0; i < 9; i++) bf[i] = ldcg32(&g_kvt[(head * 9 + i) * 32 + lane]);
#pragma unroll 1
        for (int rb = (aw + hh) % 3; rb < 8; rb += 3) {
          const __nv_bfloat16* pq = qrow + (size_t)rb * 16 * Q3_ + head * 18;
          uint32_t a0 = ldcg32(pq), a1 = ldcg32(pq + 8 * Q3_), a2 = ldcg32(pq + 8), a3 = ldcg32(pq + 8 * Q3_ + 8);
          uint32_t a4 = (t == 0) ? ldcg32(pq + 16) : 0u, a5 = (t == 0) ? ldcg32(pq + 8 * Q3_ + 16) : 0u;
          float c[3][4];
#pragma unroll
          for (int e = 0; e < 3; e++) {
            c[e][0] = c[e][1] = c[e][2] = c[e][3] = 0.f;
            mma16816(c[e], a0, a1, a2, a3, bf[e * 3 + 0], bf[e * 3 + 1]);
            mma16816(c[e], a4, a5, 0u, 0u, bf[e * 3 + 2], 0u);
          }
          float d0 = __shfl_sync(0xffffffffu, c[2][0], (lane & ~3) | 1) + 1e-6f;
          float d1 = __shfl_sync(0xffffffffu, c[2][2], (lane & ~3) | 1) + 1e-6f;
          float r0 = 1.f / d0, r1 = 1.f / d1;
          __nv_bfloat16* po = g_o + (size_t)(m * 128 + rb * 16 + g) * D_ + head * 18 + 2 * t;
          *reinterpret_cast<uint32_t*>(po) = pack_bf16(c[0][0] * r0, c[0][1] * r0);
          *reinterpret_cast<uint32_t*>(po + 8) = pack_bf16(c[1][0] * r0, c[1][1] * r0);
          *reinterpret_cast<uint32_t*>(po + 8 * D_) = pack_bf16(c[0][2] * r1, c[0][3] * r1);
          *reinterpret_cast<uint32_t*>(po + 8 * D_ + 8) = pack_bf16(c[1][2] * r1, c[1][3] * r1);
          if (t == 0) {
            *reinterpret_cast<uint32_t*>(po + 16) = pack_bf16(c[2][0] * r0, c[2][1] * r0);
            *reinterpret_cast<uint32_t*>(po + 8 * D_ + 16) = pack_bf16(c[2][2] * r1, c[2][3] * r1);
          }
        }
      }
      asm volatile("fence.proxy.async.global;" ::: "memory");
      flag_signal_warp(&g_f_o[m]);
      if (srole && aw == 2) {
        if (lane == 0) {
          mbar_wait(bar_xfree, 0);
          flag_wait(&g_f_o[m], 24 * ep);
          asm volatile("fence.proxy.async.global;" ::: "memory");
          mbar_expect(bar_ofull, 147456);
          for (int kb = 0; kb < 9; kb++) tma2d(sbase + SM_A + kb * 16384, &P.tm_o, kb * 64, m * 128, bar_ofull);
        }
        __syncwarp();
      }
    }
    cluster_arrive();
    cluster_wait();
  } else {
    asm volatile("setmaxnreg.inc.sync.aligned.u32 224;");
    const int wg = warp >> 2;
    float* sbias = reinterpret_cast<float*>(smem + SM_BIAS);
    {
      const int rs = lane >> 3, j = lane & 7;
      uint4 xv[4][9];
#pragma unroll
      for (int it = 0; it < 4; it++) {
        const uint4* src = reinterpret_cast<const uint4*>(P.x + (size_t)(m * 128 + warp * 16 + it * 4 + rs) * D_) + j;
#pragma unroll
        for (int kb = 0; kb < 9; kb++) xv[it][kb] = __ldg(src + kb * 8);
      }
      for (int i = tid; i < 576; i += 256) sbias[i] = __bfloat162float(P.b1[576 * f + i]);
#pragma unroll
      for (int it = 0; it < 4; it++) {
        float sum = 0.f;
#pragma unroll
        for (int kb = 0; kb < 9; kb++) {
          const uint32_t* w = reinterpret_cast<const uint32_t*>(&xv[it][kb]);
#pragma unroll
          for (int q = 0; q < 4; q++) sum += bf_lo(w[q]) + bf_hi(w[q]);
        }
        sum += __shfl_xor_sync(0xffffffffu, sum, 1); sum += __shfl_xor_sync(0xffffffffu, sum, 2); sum += __shfl_xor_sync(0xffffffffu, sum, 4);
        const float mean = sum * (1.f / 576.f);
        float sq = 0.f;
#pragma unroll
        for (int kb = 0; kb < 9; kb++) {
          const uint32_t* w = reinterpret_cast<const uint32_t*>(&xv[it][kb]);
#pragma unroll
          for (int q = 0; q < 4; q++) { float a = bf_lo(w[q]) - mean, b = bf_hi(w[q]) - mean; sq = fmaf(a, a, sq); sq = fmaf(b, b, sq); }
        }
        sq += __shfl_xor_sync(0xffffffffu, sq, 1); sq += __shfl_xor_sync(0xffffffffu, sq, 2); sq += __shfl_xor_sync(0xffffffffu, sq, 4);
        const float rstd = rsqrtf(sq * (1.f / 576.f) + 1e-5f);
        const float nb = -mean * rstd;
        const int row = warp * 16 + it * 4 + rs;
        uint8_t* dst = smem + SM_A + row * 128 + ((j ^ (row & 7)) << 4);
#pragma unroll
        for (int kb = 0; kb < 9; kb++) {
          const uint32_t* w = reinterpret_cast<const uint32_t*>(&xv[it][kb]);
          uint4 o;
          o.x = pack_bf16(fmaf(bf_lo(w[0]), rstd, nb), fmaf(bf_hi(w[0]), rstd, nb));
          o.y = pack_bf16(fmaf(bf_lo(w[1]), rstd, nb), fmaf(bf_hi(w[1]), rstd, nb));
          o.z = pack_bf16(fmaf(bf_lo(w[2]), rstd, nb), fmaf(bf_hi(w[2]), rstd, nb));
          o.w = pack_bf16(fmaf(bf_lo(w[3]), rstd, nb), fmaf(bf_hi(w[3]), rstd, nb));
          *reinterpret_cast<uint4*>(dst + kb * 16384) = o;
        }
      }
      asm volatile("fence.proxy.async.shared::cta;" ::: "memory");
    }
    cluster_wait();
    asm volatile("bar.sync 1, 256;" ::: "memory");

    Ctx c;
    c.full = bar_full;
    c.sig = (lane == 0) && ((warp & 3) < 2);
    c.emb = mapa(bar_empty, (warp & 3) == 0 ? rank : (rank ^ 1));
    c.stage = 0; c.phase = 0; c.prev = 0; c.has_prev = false;
    c.sb = sbase + SM_B;
    c.descA = mkdesc(sbase + SM_A + wg * 8192, 16, 1024);

    uint32_t h[144];
    const float* bias_t = sbias + 2 * t;
    uint4* part = g_part + (size_t)(((m * 8 + warp) * 9 + f) * 36) * 32 + lane;
    uint32_t* fpart = g_f_part + (m * 8 + warp) * 16;
    {
      float accB[64];
      __nv_bfloat16* qp = g_qkv + (size_t)(m * 128 + warp * 16 + g) * Q3_ + 288 * f + 2 * t;
      const bool do_phi = f < 4;
      if (!srole) {
        float accA[80];
        tile_ss<160, 2>(accA, c, [&](int) {});
        tile_ss<128, 4>(accB, c, [&](int s) {
          if (s == 0) fence_regs(accA);
#pragma unroll
          for (int q = 0; q < 10; q++) if (q * 8 / 10 == s) qkv_group(&accA[8 * q], qp + 16 * q, do_phi);
          if (s == 8) flag_signal_warp(&g_f_qkv[m * 8 + f]);
        });
      }
      float t0[96];
      tile_ss<192, 2>(t0, c, [&](int s) {
        if (!srole) {
          if (s == 0) fence_regs(accB);
#pragma unroll
          for (int q = 0; q < 8; q++) if (q == s) qkv_group(&accB[8 * q], qp + 160 + 16 * q, do_phi);
          if (s == 10) flag_signal_warp(&g_f_qkv[m * 8 + f]);
        }
      });
      float t1[64];
      tile_ss<128, 4>(t1, c, [&](int s) {
        if (s == 0) fence_regs(t0);
#pragma unroll
        for (int q = 0; q < 12; q++) if (q * 9 / 12 == s) gelu_group(&t0[8 * q], &h[4 * q], bias_t + 16 * q);
      });
      float t2[64];
      tile_ss<128, 4>(t2, c, [&](int s) {
        if (s == 0) fence_regs(t1);
#pragma unroll
        for (int q = 0; q < 8; q++) if (q == s) gelu_group(&t1[8 * q], &h[4 * (12 + q)], bias_t + 16 * (12 + q));
      });
      float t3[64];
      tile_ss<128, 4>(t3, c, [&](int s) {
        if (s == 0) fence_regs(t2);
#pragma unroll
        for (int q = 0; q < 8; q++) if (q == s) gelu_group(&t2[8 * q], &h[4 * (20 + q)], bias_t + 16 * (20 + q));
      });
      float y0[32];
      tile_rs<64, 8>(y0, h, c, [&](int s) {
        if (s == 0) { fence_regs(t3); if (lane == 0 && (warp & 3) == 0) mbar_arrive(bar_xfree); }
#pragma unroll
        for (int q = 0; q < 8; q++) if (q / 2 == s) gelu_group(&t3[8 * q], &h[4 * (28 + q)], bias_t + 16 * (28 + q));
      });
      drain(c);
      fence_regs(y0);
#pragma unroll
      for (int q = 0; q < 4; q++) part_group(&y0[8 * q], part + q * 32);
    }
#pragma unroll 1
    for (int ch = 1; ch <= 4; ch++) {
      float y[64];
      tile_rs<128, 4>(y, h, c, [&](int s) { if (s == 2) flag_signal_warp(fpart + ch - 1); });
      drain(c);
      fence_regs(y);
#pragma unroll
      for (int q = 0; q < 8; q++) part_group(&y[8 * q], part + (4 + (ch - 1) * 8 + q) * 32);
    }
    flag_signal_warp(fpart + 4);
    if (srole) {
      uint4* sp = g_part + (size_t)(((m * 8 + warp) * 9 + 8) * 36 + (f - 6) * 18) * 32 + lane;
      mbar_wait(bar_ofull, 0);
      float sa[80];
      tile_ss<160, 2>(sa, c, [&](int) {});
      float sb2[64];
      tile_ss<128, 4>(sb2, c, [&](int s) {
        if (s == 0) {
          fence_regs(sa);
#pragma unroll
          for (int q = 0; q < 10; q++) part_group(&sa[8 * q], sp + q * 32);
        }
        if (s == 3) flag_signal_warp(fpart + 5 + (f - 6) * 2);
      });
      drain(c);
      fence_regs(sb2);
#pragma unroll
      for (int q = 0; q < 8; q++) part_group(&sb2[8 * q], sp + (10 + q) * 32);
      flag_signal_warp(fpart + 6 + (f - 6) * 2);
    }
    {
      const uint32_t* fo = g_f_part + (m * 8 + f) * 16;
      if (lane < 9) flag_wait(fo + lane, (lane < 5 ? 8u : 1u) * ep);
      __syncwarp();
      const uint4* src = g_part + (size_t)((m * 8 + f) * 9 * 36) * 32 + lane;
      const size_t r0 = (size_t)(m * 128 + f * 16 + g) * D_;
#pragma unroll 1
      for (int v = warp; v < 36; v += 8) {
        uint4 p[9];
#pragma unroll
        for (int i = 0; i < 9; i++) p[i] = ldcg128(src + (i * 36 + v) * 32);
        const int col = 16 * v + 2 * t;
        uint32_t xx[4], bb[2];
        xx[0] = __ldg(reinterpret_cast<const uint32_t*>(P.x + r0 + col));
        xx[1] = __ldg(reinterpret_cast<const uint32_t*>(P.x + r0 + 8 * D_ + col));
        xx[2] = __ldg(reinterpret_cast<const uint32_t*>(P.x + r0 + col + 8));
        xx[3] = __ldg(reinterpret_cast<const uint32_t*>(P.x + r0 + 8 * D_ + col + 8));
        bb[0] = __ldg(reinterpret_cast<const uint32_t*>(P.b2 + col));
        bb[1] = __ldg(reinterpret_cast<const uint32_t*>(P.b2 + col + 8));
        uint32_t res[4];
#pragma unroll
        for (int q = 0; q < 4; q++) {
          float lo = 0.f, hi2 = 0.f;
#pragma unroll
          for (int i = 0; i < 8; i++) { uint32_t w = reinterpret_cast<const uint32_t*>(&p[i])[q]; lo += bf_lo(w); hi2 += bf_hi(w); }
          uint32_t sw = reinterpret_cast<const uint32_t*>(&p[8])[q];
          float ylo = fmaf(lo, 0.5f, bf_lo(bb[q >> 1])), yhi = fmaf(hi2, 0.5f, bf_hi(bb[q >> 1]));
          res[q] = pack_bf16(fmaf(bf_lo(sw), silu(ylo), bf_lo(xx[q])), fmaf(bf_hi(sw), silu(yhi), bf_hi(xx[q])));
        }
        *reinterpret_cast<uint32_t*>(P.out + r0 + col) = res[0];
        *reinterpret_cast<uint32_t*>(P.out + r0 + 8 * D_ + col) = res[1];
        *reinterpret_cast<uint32_t*>(P.out + r0 + col + 8) = res[2];
        *reinterpret_cast<uint32_t*>(P.out + r0 + 8 * D_ + col + 8) = res[3];
      }
    }
    cluster_arrive();
    cluster_wait();
    if (tid == 0) g_epoch[blockIdx.x] = ep;
  }
}

typedef CUresult (*EncFn)(CUtensorMap*, CUtensorMapDataType, cuuint32_t, void*, const cuuint64_t*, const cuuint64_t*, const cuuint32_t*, const cuuint32_t*,
                          CUtensorMapInterleave, CUtensorMapSwizzle, CUtensorMapL2promotion, CUtensorMapFloatOOBfill);

void make_map(EncFn enc, CUtensorMap* tm, const void* ptr, int rows, int cols, int box_rows) {
  cuuint64_t gd[2] = {(cuuint64_t)cols, (cuuint64_t)rows};
  cuuint64_t gs[1] = {(cuuint64_t)cols * 2};
  cuuint32_t bx[2] = {64, (cuuint32_t)box_rows};
  cuuint32_t es[2] = {1, 1};
  enc(tm, CU_TENSOR_MAP_DATA_TYPE_BFLOAT16, 2, const_cast<void*>(ptr), gd, gs, bx, es, CU_TENSOR_MAP_INTERLEAVE_NONE, CU_TENSOR_MAP_SWIZZLE_128B,
      CU_TENSOR_MAP_L2_PROMOTION_L2_256B, CU_TENSOR_MAP_FLOAT_OOB_FILL_NONE);
}

}

extern "C" void kernel_launch(void* const* d_in, const int* in_sizes, int n_in, void* d_out, int out_size) {
  (void)in_sizes; (void)n_in; (void)out_size;
  static EncFn enc = nullptr;
  static void* o_ptr = nullptr;
  if (!enc) {
    void* fn = nullptr; cudaDriverEntryPointQueryResult q;
    cudaGetDriverEntryPoint("cuTensorMapEncodeTiled", &fn, cudaEnableDefault, &q);
    enc = (EncFn)fn;
    cudaFuncSetAttribute(fused_kernel, cudaFuncAttributeMaxDynamicSharedMemorySize, SMEM_BYTES);
    cudaGetSymbolAddress(&o_ptr, g_o);
  }
  Params P;
  P.x = (const __nv_bfloat16*)d_in[0];
  P.wqkv = (const __nv_bfloat16*)d_in[1];
  P.wo = (const __nv_bfloat16*)d_in[2];
  P.w1 = (const __nv_bfloat16*)d_in[4];
  P.b1 = (const __nv_bfloat16*)d_in[5];
  P.w2 = (const __nv_bfloat16*)d_in[6];
  P.b2 = (const __nv_bfloat16*)d_in[7];
  P.out = (__nv_bfloat16*)d_out;
  make_map(enc, &P.tm_wqkv, P.wqkv, D_, Q3_, 32);
  make_map(enc, &P.tm_w1, P.w1, D_, F_, 32);
  make_map(enc, &P.tm_w2, P.w2, F_, D_, 32);
  make_map(enc, &P.tm_wo, P.wo, D_, D_, 32);
  make_map(enc, &P.tm_o, o_ptr, S_, D_, 128);
  cudaLaunchConfig_t cfg = {};
  cfg.gridDim = dim3(NCTAS); cfg.blockDim = dim3(NTHREADS); cfg.dynamicSmemBytes = SMEM_BYTES; cfg.stream = cudaStreamPerThread;
  cudaLaunchAttribute at[1];
  at[0].id = cudaLaunchAttributeClusterDimension; at[0].val.clusterDim.x = 2; at[0].val.clusterDim.y = 1; at[0].val.clusterDim.z = 1;
  cfg.attrs = at; cfg.numAttrs = 1;
  cudaLaunchKernelEx(&cfg, fused_kernel, P);
}
```

```cpp
#include <cuda_runtime.h>
#include <cuda.h>
#include <cuda_bf16.h>
#include <stdint.h>

namespace {

constexpr int S_ = 2048, D_ = 576, F_ = 4608, Q3_ = 1728;
constexpr int NSTAGE = 6, STAGE_BYTES = 12288;
constexpr int SM_A = 0, SM_B = 147456, SM_BIAS = SM_B + NSTAGE * STAGE_BYTES, SM_BAR = SM_BIAS + 2304;
constexpr int SMEM_BYTES = SM_BAR + 256;
constexpr int NTHREADS = 384;
constexpr int NCTAS = 132;

__device__ __nv_bfloat16 g_qkv[S_ * Q3_];
__device__ __align__(1024) __nv_bfloat16 g_o[S_ * D_];
__device__ float4 g_kvp4[32 * 16 * 3 * 32];
__device__ float2 g_kvp2[32 * 16 * 3 * 32];
__device__ uint32_t g_kvt[32 * 9 * 32];
__device__ uint4 g_part[16 * 8 * 9 * 36 * 32];
__device__ uint4 g_hsp[128 * 12 * 256];
__device__ uint32_t g_f_qkv[16 * 8];
__device__ uint32_t g_f_kvp[32];
__device__ uint32_t g_f_kvt[32];
__device__ uint32_t g_f_o[16];
__device__ uint32_t g_f_part[16 * 8 * 16];
__device__ uint32_t g_epoch[NCTAS];

__device__ __forceinline__ uint32_t smem_u32(const void* p) { return (uint32_t)__cvta_generic_to_shared(p); }
__device__ __forceinline__ void mbar_init(uint32_t a, int c) { asm volatile("mbarrier.init.shared::cta.b64 [%0], %1;" ::"r"(a), "r"(c)); }
__device__ __forceinline__ void mbar_expect(uint32_t a, uint32_t b) { asm volatile("mbarrier.arrive.expect_tx.shared::cta.b64 _, [%0], %1;" ::"r"(a), "r"(b) : "memory"); }
__device__ __forceinline__ void mbar_arrive(uint32_t a) { asm volatile("mbarrier.arrive.shared::cta.b64 _, [%0];" ::"r"(a) : "memory"); }
__device__ __forceinline__ void mbar_arrive_cl(uint32_t a) { asm volatile("mbarrier.arrive.shared::cluster.b64 _, [%0];" ::"r"(a) : "memory"); }
__device__ __forceinline__ uint32_t mapa(uint32_t a, uint32_t cta) { uint32_t r; asm volatile("mapa.shared::cluster.u32 %0, %1, %2;" : "=r"(r) : "r"(a), "r"(cta)); return r; }
__device__ __forceinline__ void mbar_wait(uint32_t a, uint32_t ph) {
  uint32_t ok; int it = 0;
  do {
    asm volatile("{.reg .pred p; mbarrier.try_wait.parity.shared::cta.b64 p, [%1], %2; selp.u32 %0,1,0,p;}" : "=r"(ok) : "r"(a), "r"(ph) : "memory");
  } while (!ok && ++it < (1 << 18));
}
__device__ __forceinline__ void tma2d(uint32_t dst, const CUtensorMap* m, int c0, int c1, uint32_t bar) {
  asm volatile("cp.async.bulk.tensor.2d.shared::cluster.global.mbarrier::complete_tx::bytes [%0], [%1, {%3,%4}], [%2];" ::"r"(dst), "l"(m), "r"(bar), "r"(c0), "r"(c1) : "memory");
}
__device__ __forceinline__ void tma2d_mc(uint32_t dst, const CUtensorMap* m, int c0, int c1, uint32_t bar) {
  asm volatile("cp.async.bulk.tensor.2d.shared::cluster.global.mbarrier::complete_tx::bytes.multicast::cluster [%0], [%1, {%3,%4}], [%2], %5;" ::"r"(dst), "l"(m), "r"(bar), "r"(c0), "r"(c1), "h"((uint16_t)3) : "memory");
}
__device__ __forceinline__ void cluster_arrive() { asm volatile("barrier.cluster.arrive.release.aligned;" ::: "memory"); }
__device__ __forceinline__ void cluster_wait() { asm volatile("barrier.cluster.wait.acquire.aligned;" ::: "memory"); }
__device__ __forceinline__ void wg_fence() { asm volatile("wgmma.fence.sync.aligned;" ::: "memory"); }
__device__ __forceinline__ void wg_commit() { asm volatile("wgmma.commit_group.sync.aligned;" ::: "memory"); }
template <int n> __device__ __forceinline__ void wg_wait() { asm volatile("wgmma.wait_group.sync.aligned %0;" ::"n"(n) : "memory"); }
__device__ __forceinline__ uint32_t ld_acquire(const uint32_t* p) { uint32_t v; asm volatile("ld.acquire.gpu.global.u32 %0, [%1];" : "=r"(v) : "l"(p) : "memory"); return v; }
__device__ __forceinline__ void flag_wait(const uint32_t* p, uint32_t target) {
  int it = 0;
  while ((int)(ld_acquire(p) - target) < 0 && ++it < (1 << 21)) __nanosleep(40);
}
__device__ __forceinline__ void flag_signal_warp(uint32_t* p) {
  __syncwarp();
  if ((threadIdx.x & 31) == 0) asm volatile("red.release.gpu.global.add.u32 [%0], 1;" ::"l"(p) : "memory");
}
__device__ __forceinline__ uint32_t pack_bf16(float lo, float hi) { uint32_t r; asm("cvt.rn.bf16x2.f32 %0, %1, %2;" : "=r"(r) : "f"(hi), "f"(lo)); return r; }
__device__ __forceinline__ float bf_lo(uint32_t v) { return __uint_as_float(v << 16); }
__device__ __forceinline__ float bf_hi(uint32_t v) { return __uint_as_float(v & 0xffff0000u); }
__device__ __forceinline__ float tanh_fast(float x) { float r; asm("tanh.approx.f32 %0, %1;" : "=f"(r) : "f"(x)); return r; }
__device__ __forceinline__ uint32_t movmat(uint32_t a) { uint32_t d; asm volatile("movmatrix.sync.aligned.m8n8.trans.b16 %0, %1;" : "=r"(d) : "r"(a)); return d; }
__device__ __forceinline__ void mma16816(float* c, uint32_t a0, uint32_t a1, uint32_t a2, uint32_t a3, uint32_t b0, uint32_t b1) {
  asm volatile("mma.sync.aligned.m16n8k16.row.col.f32.bf16.bf16.f32 {%0,%1,%2,%3}, {%4,%5,%6,%7}, {%8,%9}, {%0,%1,%2,%3};"
               : "+f"(c[0]), "+f"(c[1]), "+f"(c[2]), "+f"(c[3]) : "r"(a0), "r"(a1), "r"(a2), "r"(a3), "r"(b0), "r"(b1));
}
__device__ __forceinline__ uint32_t ldcg32(const void* p) { uint32_t v; asm volatile("ld.global.cg.u32 %0, [%1];" : "=r"(v) : "l"(p) : "memory"); return v; }
__device__ __forceinline__ uint4 ldcg128(const void* p) { uint4 v; asm volatile("ld.global.cg.v4.u32 {%0,%1,%2,%3}, [%4];" : "=r"(v.x), "=r"(v.y), "=r"(v.z), "=r"(v.w) : "l"(p) : "memory"); return v; }
__device__ __forceinline__ uint2 ldcg64(const void* p) { uint2 v; asm volatile("ld.global.cg.v2.u32 {%0,%1}, [%2];" : "=r"(v.x), "=r"(v.y) : "l"(p) : "memory"); return v; }

template <int N> __device__ __forceinline__ void wgmma_ss(float* d, uint64_t da, uint64_t db, int sc);
template <int N> __device__ __forceinline__ void wgmma_rs(float* d, const uint32_t* a, uint64_t db, int sc);
template <> __device__ __forceinline__ void wgmma_ss<128>(float* d, uint64_t da, uint64_t db, int sc) {
  asm volatile("{.reg .pred p; setp.ne.b32 p, %66, 0; wgmma.mma_async.sync.aligned.m64n128k16.f32.bf16.bf16 {%0, %1, %2, %3, %4, %5, %6, %7, %8, %9, %10, %11, %12, %13, %14, %15, %16, %17, %18, %19, %20, %21, %22, %23, %24, %25, %26, %27, %28, %29, %30, %31, %32, %33, %34, %35, %36, %37, %38, %39, %40, %41, %42, %43, %44, %45, %46, %47, %48, %49, %50, %51, %52, %53, %54, %55, %56, %57, %58, %59, %60, %61, %62, %63}, %64, %65, p, 1, 1, 0, 1;}"
   : "+f"(d[0]), "+f"(d[1]), "+f"(d[2]), "+f"(d[3]), "+f"(d[4]), "+f"(d[5]), "+f"(d[6]), "+f"(d[7]), "+f"(d[8]), "+f"(d[9]), "+f"(d[10]), "+f"(d[11]), "+f"(d[12]), "+f"(d[13]), "+f"(d[14]), "+f"(d[15]), "+f"(d[16]), "+f"(d[17]), "+f"(d[18]), "+f"(d[19]), "+f"(d[20]), "+f"(d[21]), "+f"(d[22]), "+f"(d[23]), "+f"(d[24]), "+f"(d[25]), "+f"(d[26]), "+f"(d[27]), "+f"(d[28]), "+f"(d[29]), "+f"(d[30]), "+f"(d[31]), "+f"(d[32]), "+f"(d[33]), "+f"(d[34]), "+f"(d[35]), "+f"(d[36]), "+f"(d[37]), "+f"(d[38]), "+f"(d[39]), "+f"(d[40]), "+f"(d[41]), "+f"(d[42]), "+f"(d[43]), "+f"(d[44]), "+f"(d[45]), "+f"(d[46]), "+f"(d[47]), "+f"(d[48]), "+f"(d[49]), "+f"(d[50]), "+f"(d[51]), "+f"(d[52]), "+f"(d[53]), "+f"(d[54]), "+f"(d[55]), "+f"(d[56]), "+f"(d[57]), "+f"(d[58]), "+f"(d[59]), "+f"(d[60]), "+f"(d[61]), "+f"(d[62]), "+f"(d[63]) : "l"(da), "l"(db), "r"(sc));
}
template <> __device__ __forceinline__ void wgmma_ss<160>(float* d, uint64_t da, uint64_t db, int sc) {
  asm volatile("{.reg .pred p; setp.ne.b32 p, %82, 0; wgmma.mma_async.sync.aligned.m64n160k16.f32.bf16.bf16 {%0, %1, %2, %3, %4, %5, %6, %7, %8, %9, %10, %11, %12, %13, %14, %15, %16, %17, %18, %19, %20, %21, %22, %23, %24, %25, %26, %27, %28, %29, %30, %31, %32, %33, %34, %35, %36, %37, %38, %39, %40, %41, %42, %43, %44, %45, %46, %47, %48, %49, %50, %51, %52, %53, %54, %55, %56, %57, %58, %59, %60, %61, %62, %63, %64, %65, %66, %67, %68, %69, %70, %71, %72, %73, %74, %75, %76, %77, %78, %79}, %80, %81, p, 1, 1, 0, 1;}"
   : "+f"(d[0]), "+f"(d[1]), "+f"(d[2]), "+f"(d[3]), "+f"(d[4]), "+f"(d[5]), "+f"(d[6]), "+f"(d[7]), "+f"(d[8]), "+f"(d[9]), "+f"(d[10]), "+f"(d[11]), "+f"(d[12]), "+f"(d[13]), "+f"(d[14]), "+f"(d[15]), "+f"(d[16]), "+f"(d[17]), "+f"(d[18]), "+f"(d[19]), "+f"(d[20]), "+f"(d[21]), "+f"(d[22]), "+f"(d[23]), "+f"(d[24]), "+f"(d[25]), "+f"(d[26]), "+f"(d[27]), "+f"(d[28]), "+f"(d[29]), "+f"(d[30]), "+f"(d[31]), "+f"(d[32]), "+f"(d[33]), "+f"(d[34]), "+f"(d[35]), "+f"(d[36]), "+f"(d[37]), "+f"(d[38]), "+f"(d[39]), "+f"(d[40]), "+f"(d[41]), "+f"(d[42]), "+f"(d[43]), "+f"(d[44]), "+f"(d[45]), "+f"(d[46]), "+f"(d[47]), "+f"(d[48]), "+f"(d[49]), "+f"(d[50]), "+f"(d[51]), "+f"(d[52]), "+f"(d[53]), "+f"(d[54]), "+f"(d[55]), "+f"(d[56]), "+f"(d[57]), "+f"(d[58]), "+f"(d[59]), "+f"(d[60]), "+f"(d[61]), "+f"(d[62]), "+f"(d[63]), "+f"(d[64]), "+f"(d[65]), "+f"(d[66]), "+f"(d[67]), "+f"(d[68]), "+f"(d[69]), "+f"(d[70]), "+f"(d[71]), "+f"(d[72]), "+f"(d[73]), "+f"(d[74]), "+f"(d[75]), "+f"(d[76]), "+f"(d[77]), "+f"(d[78]), "+f"(d[79]) : "l"(da), "l"(db), "r"(sc));
}
template <> __device__ __forceinline__ void wgmma_ss<192>(float* d, uint64_t da, uint64_t db, int sc) {
  asm volatile("{.reg .pred p; setp.ne.b32 p, %98, 0; wgmma.mma_async.sync.aligned.m64n192k16.f32.bf16.bf16 {%0, %1, %2, %3, %4, %5, %6, %7, %8, %9, %10, %11, %12, %13, %14, %15, %16, %17, %18, %19, %20, %21, %22, %23, %24, %25, %26, %27, %28, %29, %30, %31, %32, %33, %34, %35, %36, %37, %38, %39, %40, %41, %42, %43, %44, %45, %46, %47, %48, %49, %50, %51, %52, %53, %54, %55, %56, %57, %58, %59, %60, %61, %62, %63, %64, %65, %66, %67, %68, %69, %70, %71, %72, %73, %74, %75, %76, %77, %78, %79, %80, %81, %82, %83, %84, %85, %86, %87, %88, %89, %90, %91, %92, %93, %94, %95}, %96, %97, p, 1, 1, 0, 1;}"
   : "+f"(d[0]), "+f"(d[1]), "+f"(d[2]), "+f"(d[3]), "+f"(d[4]), "+f"(d[5]), "+f"(d[6]), "+f"(d[7]), "+f"(d[8]), "+f"(d[9]), "+f"(d[10]), "+f"(d[11]), "+f"(d[12]), "+f"(d[13]), "+f"(d[14]), "+f"(d[15]), "+f"(d[16]), "+f"(d[17]), "+f"(d[18]), "+f"(d[19]), "+f"(d[20]), "+f"(d[21]), "+f"(d[22]), "+f"(d[23]), "+f"(d[24]), "+f"(d[25]), "+f"(d[26]), "+f"(d[27]), "+f"(d[28]), "+f"(d[29]), "+f"(d[30]), "+f"(d[31]), "+f"(d[32]), "+f"(d[33]), "+f"(d[34]), "+f"(d[35]), "+f"(d[36]), "+f"(d[37]), "+f"(d[38]), "+f"(d[39]), "+f"(d[40]), "+f"(d[41]), "+f"(d[42]), "+f"(d[43]), "+f"(d[44]), "+f"(d[45]), "+f"(d[46]), "+f"(d[47]), "+f"(d[48]), "+f"(d[49]), "+f"(d[50]), "+f"(d[51]), "+f"(d[52]), "+f"(d[53]), "+f"(d[54]), "+f"(d[55]), "+f"(d[56]), "+f"(d[57]), "+f"(d[58]), "+f"(d[59]), "+f"(d[60]), "+f"(d[61]), "+f"(d[62]), "+f"(d[63]), "+f"(d[64]), "+f"(d[65]), "+f"(d[66]), "+f"(d[67]), "+f"(d[68]), "+f"(d[69]), "+f"(d[70]), "+f"(d[71]), "+f"(d[72]), "+f"(d[73]), "+f"(d[74]), "+f"(d[75]), "+f"(d[76]), "+f"(d[77]), "+f"(d[78]), "+f"(d[79]), "+f"(d[80]), "+f"(d[81]), "+f"(d[82]), "+f"(d[83]), "+f"(d[84]), "+f"(d[85]), "+f"(d[86]), "+f"(d[87]), "+f"(d[88]), "+f"(d[89]), "+f"(d[90]), "+f"(d[91]), "+f"(d[92]), "+f"(d[93]), "+f"(d[94]), "+f"(d[95]) : "l"(da), "l"(db), "r"(sc));
}


__device__ __forceinline__ uint64_t mkdesc(uint32_t addr, uint32_t lbo, uint32_t sbo) {
  return (uint64_t)((addr & 0x3FFFF) >> 4) | ((uint64_t)(lbo >> 4) << 16) | ((uint64_t)(sbo >> 4) << 32) | (1ull << 62);
}
template <int n> __device__ __forceinline__ void fence_regs(float* a) {
#pragma unroll
  for (int i = 0; i < n; i++) asm volatile("" : "+f"(a[i])::"memory");
}

struct Ctx {
  uint32_t full;
  uint32_t emb;
  bool sig;
  uint32_t stage, phase, prev;
  bool has_prev;
  uint32_t sb;
  uint64_t descA;
  __device__ __forceinline__ void release_prev() { if (sig && has_prev) mbar_arrive_cl(emb + 8 * prev); }
  __device__ __forceinline__ void adv() { prev = stage; has_prev = true; if (++stage == NSTAGE) { stage = 0; phase ^= 1; } }
};

template <int N, int PERM, class Pre, class Epi>
__device__ __forceinline__ void tile_ss(float* acc, Ctx& c, Pre pre, Epi epi, int sc0 = 0) {
#pragma unroll
  for (int s = 0; s < 18; s++) {
    pre(s);
    mbar_wait(c.full + 8 * c.stage, c.phase);
    wg_fence();
    uint64_t db = mkdesc(c.sb + c.stage * STAGE_BYTES, 4096, 1024);
#pragma unroll
    for (int kk = 0; kk < 2; kk++) {
      const int kg = s * 2 + kk;
      wgmma_ss<N>(acc, c.descA + (uint64_t)(((kg >> 2) * 16384 + (kg & 3) * 32) >> 4), db + kk * 128, kg != 0 ? 1 : sc0);
    }
    wg_commit();
    wg_wait<1>();
    c.release_prev();
    epi(s);
    c.adv();
  }
}
__device__ __forceinline__ void drain(Ctx& c) { wg_wait<0>(); c.release_prev(); c.has_prev = false; }

__device__ __forceinline__ float gelu2(float x) {
  float u = x * fmaf(x * x, 0.0356774081f, 0.7978845608f);
  return fmaf(x, tanh_fast(u), x);
}
__device__ __forceinline__ void gelu_group(const float* a, uint32_t* h, const float* bias  ) {
  float2 b0 = *reinterpret_cast<const float2*>(bias);
  float2 b1 = *reinterpret_cast<const float2*>(bias + 8);
  h[0] = pack_bf16(gelu2(a[0] + b0.x), gelu2(a[1] + b0.y));
  h[1] = pack_bf16(gelu2(a[2] + b0.x), gelu2(a[3] + b0.y));
  h[2] = pack_bf16(gelu2(a[4] + b1.x), gelu2(a[5] + b1.y));
  h[3] = pack_bf16(gelu2(a[6] + b1.x), gelu2(a[7] + b1.y));
}
__device__ __forceinline__ void stsm4(uint32_t addr, uint32_t r0, uint32_t r1, uint32_t r2, uint32_t r3) {
  asm volatile("stmatrix.sync.aligned.m8n8.x4.shared.b16 [%0], {%1,%2,%3,%4};" ::"r"(addr), "r"(r0), "r"(r1), "r"(r2), "r"(r3) : "memory");
}
__device__ __forceinline__ float phi(float t) { return (t > 0.f ? t + 1.f : __expf(t)) + 1e-6f; }
__device__ __forceinline__ void qkv_group(const float* a, __nv_bfloat16* p  , bool do_phi) {
  float v[8];
#pragma unroll
  for (int i = 0; i < 8; i++) v[i] = do_phi ? phi(a[i]) : a[i];
  *reinterpret_cast<uint32_t*>(p) = pack_bf16(v[0], v[1]);
  *reinterpret_cast<uint32_t*>(p + 8 * Q3_) = pack_bf16(v[2], v[3]);
  *reinterpret_cast<uint32_t*>(p + 8) = pack_bf16(v[4], v[5]);
  *reinterpret_cast<uint32_t*>(p + 8 * Q3_ + 8) = pack_bf16(v[6], v[7]);
}
__device__ __forceinline__ void part_group(const float* a, uint4* p) {
  *p = make_uint4(pack_bf16(a[0], a[1]), pack_bf16(a[2], a[3]), pack_bf16(a[4], a[5]), pack_bf16(a[6], a[7]));
}
__device__ __forceinline__ float silu(float y) { return __fdividef(y, 1.f + __expf(-y)); }

struct Params {
  CUtensorMap tm_wqkv, tm_w1, tm_w2, tm_wo, tm_o;
  const __nv_bfloat16 *x, *b1, *b2, *wqkv, *w1, *w2, *wo;
  __nv_bfloat16* out;
  int zero;
};

__global__ void __launch_bounds__(NTHREADS, 1) fused_kernel(const __grid_constant__ Params P) {
  extern __shared__ __align__(1024) uint8_t smem[];
  const uint32_t sbase = smem_u32(smem);
  const int tid = threadIdx.x, warp = tid >> 5, lane = tid & 31;
  const int g = lane >> 2, t = lane & 3;
  const uint32_t ep = g_epoch[blockIdx.x] + 1;

  if (blockIdx.x >= 128) {
    const int a = blockIdx.x - 128;
    if (warp < 8) {
      const int head = a * 8 + warp;
      if (lane == 0) flag_wait(&g_f_kvp[head], 16 * ep);
      __syncwarp();
      float s4[3][4], s2[3][2];
#pragma unroll
      for (int j = 0; j < 3; j++) { s4[j][0] = s4[j][1] = s4[j][2] = s4[j][3] = 0.f; s2[j][0] = s2[j][1] = 0.f; }
#pragma unroll 4
      for (int m = 0; m < 16; m++) {
#pragma unroll
        for (int j = 0; j < 3; j++) {
          uint4 v = ldcg128(&g_kvp4[((head * 16 + m) * 3 + j) * 32 + lane]);
          uint2 w = ldcg64(&g_kvp2[((head * 16 + m) * 3 + j) * 32 + lane]);
          s4[j][0] += __uint_as_float(v.x); s4[j][1] += __uint_as_float(v.y); s4[j][2] += __uint_as_float(v.z); s4[j][3] += __uint_as_float(v.w);
          s2[j][0] += __uint_as_float(w.x); s2[j][1] += __uint_as_float(w.y);
        }
      }
#pragma unroll
      for (int j = 0; j < 3; j++) {
        g_kvt[(head * 9 + 0 + j) * 32 + lane] = pack_bf16(s4[j][0], s4[j][1]);
        g_kvt[(head * 9 + 3 + j) * 32 + lane] = pack_bf16(s4[j][2], s4[j][3]);
        g_kvt[(head * 9 + 6 + j) * 32 + lane] = pack_bf16(s2[j][0], s2[j][1]);
      }
      flag_signal_warp(&g_f_kvt[head]);
    } else if (lane == 0) {
      const int id = a * 4 + (warp - 8);
      constexpr uint32_t CH = 9216 * 2;
      const char* w1 = (const char*)P.w1; const char* w2 = (const char*)P.w2; const char* wo = (const char*)P.wo;
      for (int i = id; i < 288; i += 16) asm volatile("cp.async.bulk.prefetch.L2.global [%0], %1;" ::"l"(w1 + (size_t)i * CH), "r"(CH) : "memory");
      for (int i = id; i < 288; i += 16) asm volatile("cp.async.bulk.prefetch.L2.global [%0], %1;" ::"l"(w2 + (size_t)i * CH), "r"(CH) : "memory");
      for (int i = id; i < 36; i += 16) asm volatile("cp.async.bulk.prefetch.L2.global [%0], %1;" ::"l"(wo + (size_t)i * CH), "r"(CH) : "memory");
    }
    __syncthreads();
    if (tid == 0) g_epoch[blockIdx.x] = ep;
    return;
  }

  const int cl = blockIdx.x >> 1, rank = blockIdx.x & 1;
  const int f = cl & 7, m = (cl >> 3) * 2 + rank;
  const bool srole = f >= 6;
  const uint32_t bar_full = sbase + SM_BAR, bar_empty = bar_full + 8 * NSTAGE, bar_xfree = bar_empty + 8 * NSTAGE, bar_ofull = bar_xfree + 72;

  if (tid == 0) {
    for (int i = 0; i < NSTAGE; i++) { mbar_init(bar_full + 8 * i, 1); mbar_init(bar_empty + 8 * i, 4); }
    for (int i = 0; i < 9; i++) { mbar_init(bar_xfree + 8 * i, 2); mbar_init(bar_ofull + 8 * i, 1); }
    asm volatile("fence.mbarrier_init.release.cluster;" ::: "memory");
  }
  __syncwarp();
  cluster_arrive();

  if (warp >= 8) {
    asm volatile("setmaxnreg.dec.sync.aligned.u32 56;");
    cluster_wait();
    if (warp == 8) {
      if (lane == 0) {
        uint32_t stage = 0, phase = 1;
        const uint32_t sb = sbase + SM_B;
        auto tile = [&](const CUtensorMap* map, int col, int row0, bool three, bool perm) {
          for (int st = 0; st < 18; st++) {
            int row = row0 + st * 32;
            if (perm) row += (st < 6) ? 192 : (st < 12 ? -192 : 0);
            mbar_wait(bar_empty + 8 * stage, phase);
            mbar_expect(bar_full + 8 * stage, three ? 12288 : 8192);
            uint32_t dst = sb + stage * STAGE_BYTES;
            if (((st ^ rank) & 1) == 0) {
              tma2d_mc(dst, map, col, row, bar_full + 8 * stage);
              if (three) tma2d_mc(dst + 8192, map, col + 128, row, bar_full + 8 * stage);
            } else {
              tma2d_mc(dst + 4096, map, col + 64, row, bar_full + 8 * stage);
            }
            if (++stage == NSTAGE) { stage = 0; phase ^= 1; }
          }
        };
        if (!srole) { tile(&P.tm_wqkv, 288 * f, 0, true, false); tile(&P.tm_wqkv, 288 * f + 160, 0, false, false); }
        for (int i = 0; i < 3; i++) tile(&P.tm_w1, 576 * f + 192 * i, 0, true, false);
        for (int i = 0; i < 3; i++) tile(&P.tm_w2, 192 * i, 576 * f, true, true);
        if (srole) { tile(&P.tm_wo, 288 * (f - 6), 0, true, false); tile(&P.tm_wo, 288 * (f - 6) + 160, 0, false, false); }
      }
      __syncwarp();
    } else {
      const int aw = warp - 9;
      const int hi = f >> 2;
      const __nv_bfloat16* qrow = g_qkv + (size_t)(m * 128 + g) * Q3_ + 2 * t;
      if (aw < 2) {
        if (lane == 0) { flag_wait(&g_f_qkv[m * 8 + 2 + hi], 16 * ep); flag_wait(&g_f_qkv[m * 8 + 4 + hi], 16 * ep); }
        __syncwarp();
#pragma unroll 1
        for (int hh = 0; hh < 2; hh++) {
          const int head = 4 * f + 2 * aw + hh;
          float c0[3][4], c1[3][4];
#pragma unroll
          for (int j = 0; j < 3; j++) { c0[j][0] = c0[j][1] = c0[j][2] = c0[j][3] = 0.f; c1[j][0] = c1[j][1] = c1[j][2] = c1[j][3] = 0.f; }
#pragma unroll 2
          for (int ks = 0; ks < 8; ks++) {
            const __nv_bfloat16* pk = qrow + (size_t)ks * 16 * Q3_ + 576 + head * 18;
            const __nv_bfloat16* pv = pk + 576;
            uint32_t kf[3][2], vf[3][2];
#pragma unroll
            for (int r = 0; r < 2; r++) {
              kf[0][r] = ldcg32(pk + r * 8 * Q3_); kf[1][r] = ldcg32(pk + r * 8 * Q3_ + 8);
              kf[2][r] = (t == 0) ? ldcg32(pk + r * 8 * Q3_ + 16) : 0u;
              vf[0][r] = ldcg32(pv + r * 8 * Q3_); vf[1][r] = ldcg32(pv + r * 8 * Q3_ + 8);
              vf[2][r] = (t == 0) ? ldcg32(pv + r * 8 * Q3_ + 16) : (t == 1 ? 0x00003f80u : 0u);
            }
#pragma unroll
            for (int j = 0; j < 3; j++) { kf[j][0] = movmat(kf[j][0]); kf[j][1] = movmat(kf[j][1]); vf[j][0] = movmat(vf[j][0]); vf[j][1] = movmat(vf[j][1]); }
#pragma unroll
            for (int j = 0; j < 3; j++) {
              mma16816(c0[j], vf[0][0], vf[1][0], vf[0][1], vf[1][1], kf[j][0], kf[j][1]);
              mma16816(c1[j], vf[2][0], 0u, vf[2][1], 0u, kf[j][0], kf[j][1]);
            }
          }
#pragma unroll
          for (int j = 0; j < 3; j++) {
            g_kvp4[((head * 16 + m) * 3 + j) * 32 + lane] = make_float4(c0[j][0], c0[j][1], c0[j][2], c0[j][3]);
            g_kvp2[((head * 16 + m) * 3 + j) * 32 + lane] = make_float2(c1[j][0], c1[j][1]);
          }
          flag_signal_warp(&g_f_kvp[head]);
        }
      }
      if (lane == 0) flag_wait(&g_f_qkv[m * 8 + hi], 16 * ep);
      if (lane < 4) flag_wait(&g_f_kvt[4 * f + lane], ep);
      __syncwarp();
#pragma unroll 1
      for (int hh = 0; hh < 4; hh++) {
        const int head = 4 * f + hh;
        uint32_t bf[9];
#pragma unroll
        for (int i = 0; i < 9; i++) bf[i] = ldcg32(&g_kvt[(head * 9 + i) * 32 + lane]);
#pragma unroll 1
        for (int rb = (aw + hh) % 3; rb < 8; rb += 3) {
          const __nv_bfloat16* pq = qrow + (size_t)rb * 16 * Q3_ + head * 18;
          uint32_t a0 = ldcg32(pq), a1 = ldcg32(pq + 8 * Q3_), a2 = ldcg32(pq + 8), a3 = ldcg32(pq + 8 * Q3_ + 8);
          uint32_t a4 = (t == 0) ? ldcg32(pq + 16) : 0u, a5 = (t == 0) ? ldcg32(pq + 8 * Q3_ + 16) : 0u;
          float c[3][4];
#pragma unroll
          for (int e = 0; e < 3; e++) {
            c[e][0] = c[e][1] = c[e][2] = c[e][3] = 0.f;
            mma16816(c[e], a0, a1, a2, a3, bf[e * 3 + 0], bf[e * 3 + 1]);
            mma16816(c[e], a4, a5, 0u, 0u, bf[e * 3 + 2], 0u);
          }
          float d0 = __shfl_sync(0xffffffffu, c[2][0], (lane & ~3) | 1) + 1e-6f;
          float d1 = __shfl_sync(0xffffffffu, c[2][2], (lane & ~3) | 1) + 1e-6f;
          float r0 = 1.f / d0, r1 = 1.f / d1;
          __nv_bfloat16* po = g_o + (size_t)(m * 128 + rb * 16 + g) * D_ + head * 18 + 2 * t;
          *reinterpret_cast<uint32_t*>(po) = pack_bf16(c[0][0] * r0, c[0][1] * r0);
          *reinterpret_cast<uint32_t*>(po + 8) = pack_bf16(c[1][0] * r0, c[1][1] * r0);
          *reinterpret_cast<uint32_t*>(po + 8 * D_) = pack_bf16(c[0][2] * r1, c[0][3] * r1);
          *reinterpret_cast<uint32_t*>(po + 8 * D_ + 8) = pack_bf16(c[1][2] * r1, c[1][3] * r1);
          if (t == 0) {
            *reinterpret_cast<uint32_t*>(po + 16) = pack_bf16(c[2][0] * r0, c[2][1] * r0);
            *reinterpret_cast<uint32_t*>(po + 8 * D_ + 16) = pack_bf16(c[2][2] * r1, c[2][3] * r1);
          }
        }
      }
      asm volatile("fence.proxy.async.global;" ::: "memory");
      flag_signal_warp(&g_f_o[m]);
      if (srole && aw == 2) {
        if (lane == 0) {
          flag_wait(&g_f_o[m], 24 * ep);
          asm volatile("fence.proxy.async.global;" ::: "memory");
          for (int kb = 0; kb < 9; kb++) {
            mbar_wait(bar_xfree + 8 * kb, 0);
            mbar_expect(bar_ofull + 8 * kb, 16384);
            tma2d(sbase + SM_A + kb * 16384, &P.tm_o, kb * 64, m * 128, bar_ofull + 8 * kb);
          }
        }
        __syncwarp();
      }
    }
    cluster_arrive();
    cluster_wait();
  } else {
    asm volatile("setmaxnreg.inc.sync.aligned.u32 224;");
    const int wg = warp >> 2;
    float* sbias = reinterpret_cast<float*>(smem + SM_BIAS);
    {
      const int rs = lane >> 3, j = lane & 7;
      uint4 xv[4][9];
#pragma unroll
      for (int it = 0; it < 4; it++) {
        const uint4* src = reinterpret_cast<const uint4*>(P.x + (size_t)(m * 128 + warp * 16 + it * 4 + rs) * D_) + j;
#pragma unroll
        for (int kb = 0; kb < 9; kb++) xv[it][kb] = __ldg(src + kb * 8);
      }
      for (int i = tid; i < 576; i += 256) sbias[i] = __bfloat162float(P.b1[576 * f + i]);
#pragma unroll
      for (int it = 0; it < 4; it++) {
        float sum = 0.f;
#pragma unroll
        for (int kb = 0; kb < 9; kb++) {
          const uint32_t* w = reinterpret_cast<const uint32_t*>(&xv[it][kb]);
#pragma unroll
          for (int q = 0; q < 4; q++) sum += bf_lo(w[q]) + bf_hi(w[q]);
        }
        sum += __shfl_xor_sync(0xffffffffu, sum, 1); sum += __shfl_xor_sync(0xffffffffu, sum, 2); sum += __shfl_xor_sync(0xffffffffu, sum, 4);
        const float mean = sum * (1.f / 576.f);
        float sq = 0.f;
#pragma unroll
        for (int kb = 0; kb < 9; kb++) {
          const uint32_t* w = reinterpret_cast<const uint32_t*>(&xv[it][kb]);
#pragma unroll
          for (int q = 0; q < 4; q++) { float a = bf_lo(w[q]) - mean, b = bf_hi(w[q]) - mean; sq = fmaf(a, a, sq); sq = fmaf(b, b, sq); }
        }
        sq += __shfl_xor_sync(0xffffffffu, sq, 1); sq += __shfl_xor_sync(0xffffffffu, sq, 2); sq += __shfl_xor_sync(0xffffffffu, sq, 4);
        const float rstd = rsqrtf(sq * (1.f / 576.f) + 1e-5f);
        const float nb = -mean * rstd;
        const int row = warp * 16 + it * 4 + rs;
        uint8_t* dst = smem + SM_A + row * 128 + ((j ^ (row & 7)) << 4);
#pragma unroll
        for (int kb = 0; kb < 9; kb++) {
          const uint32_t* w = reinterpret_cast<const uint32_t*>(&xv[it][kb]);
          uint4 o;
          o.x = pack_bf16(fmaf(bf_lo(w[0]), rstd, nb), fmaf(bf_hi(w[0]), rstd, nb));
          o.y = pack_bf16(fmaf(bf_lo(w[1]), rstd, nb), fmaf(bf_hi(w[1]), rstd, nb));
          o.z = pack_bf16(fmaf(bf_lo(w[2]), rstd, nb), fmaf(bf_hi(w[2]), rstd, nb));
          o.w = pack_bf16(fmaf(bf_lo(w[3]), rstd, nb), fmaf(bf_hi(w[3]), rstd, nb));
          *reinterpret_cast<uint4*>(dst + kb * 16384) = o;
        }
      }
      asm volatile("fence.proxy.async.shared::cta;" ::: "memory");
    }
    cluster_wait();
    asm volatile("bar.sync 1, 256;" ::: "memory");

    Ctx c;
    c.full = bar_full;
    c.sig = (lane == 0) && ((warp & 3) < 2);
    c.emb = mapa(bar_empty, (warp & 3) == 0 ? rank : (rank ^ 1));
    c.stage = 0; c.phase = 0; c.prev = 0; c.has_prev = false;
    c.sb = sbase + SM_B;
    c.descA = mkdesc(sbase + SM_A + wg * 8192, 16, 1024);

    const float* bias_t = sbias + 2 * t;
    uint4* part = g_part + (size_t)(((m * 8 + warp) * 9 + f) * 36) * 32 + lane;
    uint32_t* fpart = g_f_part + (m * 8 + warp) * 16;
    const uint32_t hst = sbase + SM_A + (warp * 16 + (lane & 7) + ((lane >> 3) & 1) * 8) * 128 + (((lane >> 4) ^ (lane & 7)) << 4);
    auto nop = [](int) {};
    auto wg_sync = [&]() {
      asm volatile("fence.proxy.async.shared::cta;" ::: "memory");
      if (wg == 0) asm volatile("bar.sync 2, 128;" ::: "memory"); else asm volatile("bar.sync 3, 128;" ::: "memory");
    };
    float A[96], B[96];
    if (!srole) {
      __nv_bfloat16* qp = g_qkv + (size_t)(m * 128 + warp * 16 + g) * Q3_ + 288 * f + 2 * t;
      const bool do_phi = f < 4;
#pragma unroll
      for (int i = 80; i < 96; i++) A[i] = 0.f;
      tile_ss<160, 0>(A, c, nop, nop);
      tile_ss<128, 0>(B, c, nop, [&](int s) {
        if (s == 0) fence_regs<80>(A);
        if (s < 10) qkv_group(&A[8 * (s < 10 ? s : 0)], qp + 16 * s, do_phi);
        if (s == 14) flag_signal_warp(&g_f_qkv[m * 8 + f]);
      });
      tile_ss<192, 0>(A, c, nop, [&](int s) {
        if (s == 0) fence_regs<64>(B);
        if (s < 8) qkv_group(&B[8 * (s < 8 ? s : 0)], qp + 160 + 16 * s, do_phi);
        if (s == 11) flag_signal_warp(&g_f_qkv[m * 8 + f]);
      }, P.zero);
    } else {
      tile_ss<192, 0>(A, c, nop, nop);
    }
    uint4* hsp = g_hsp + (size_t)blockIdx.x * 12 * 256 + tid;
    tile_ss<192, 0>(B, c, nop, [&](int s) {
      if (s == 0) fence_regs<96>(A);
      if (s < 12) {
        uint32_t hh[4];
        gelu_group(&A[8 * (s < 12 ? s : 0)], hh, bias_t + 16 * s);
        hsp[s * 256] = make_uint4(hh[0], hh[1], hh[2], hh[3]);
      }
    });
    {
      uint4 pk[4];
      tile_ss<192, 0>(A, c, nop, [&](int s) {
        if (s == 0) fence_regs<96>(B);
        if (s >= 2 && s < 14) {
          const int q = (s >= 2 && s < 14) ? s - 2 : 0;
          uint32_t hh[4];
          gelu_group(&B[8 * q], hh, bias_t + 16 * (12 + q));
          stsm4((hst ^ ((q & 3) << 5)) + (q >> 2) * 16384, hh[0], hh[1], hh[2], hh[3]);
        }
        if (s == 10 || s == 12 || s == 14) {
          const int kb = (s - 10) / 2;
#pragma unroll
          for (int q = 0; q < 4; q++) stsm4((hst ^ (q << 5)) + (3 + kb) * 16384, pk[q].x, pk[q].y, pk[q].z, pk[q].w);
        }
        if (s == 8 || s == 10 || s == 12) {
          const int kb = (s - 8) / 2;
#pragma unroll
          for (int q = 0; q < 4; q++) pk[q] = ldcg128(hsp + (kb * 4 + q) * 256);
        }
        if (s == 16) wg_sync();
      });
    }
    tile_ss<192, 1>(B, c, nop, [&](int s) {
      if (s == 0) fence_regs<96>(A);
      if (s < 10) {
#pragma unroll
        for (int q = 0; q < 12; q++) if (q * 10 / 12 == s) {
          uint32_t hh[4];
          gelu_group(&A[8 * q], hh, bias_t + 16 * (24 + q));
          stsm4((hst ^ ((q & 3) << 5)) + (6 + (q >> 2)) * 16384, hh[0], hh[1], hh[2], hh[3]);
        }
      }
      if (s == 11) wg_sync();
    });
    tile_ss<192, 1>(A, c, nop, [&](int s) {
      if (s == 0) fence_regs<96>(B);
      if (s < 12) part_group(&B[8 * (s < 12 ? s : 0)], part + s * 32);
      if (s == 14) flag_signal_warp(fpart + 0);
    });
    tile_ss<192, 1>(B, c, nop, [&](int s) {
      if (s == 0) fence_regs<96>(A);
      if (s < 12) part_group(&A[8 * (s < 12 ? s : 0)], part + (12 + s) * 32);
      if (s == 14) flag_signal_warp(fpart + 1);
      if (s >= 2 && (s & 1) == 0 && srole && lane == 0 && (warp & 3) == 0) mbar_arrive(bar_xfree + 8 * (s / 2 - 1));
    });
    if (!srole) {
      drain(c);
      fence_regs<96>(B);
#pragma unroll
      for (int q = 0; q < 12; q++) part_group(&B[8 * q], part + (24 + q) * 32);
      flag_signal_warp(fpart + 2);
    } else {
      uint4* sp = g_part + (size_t)(((m * 8 + warp) * 9 + 8) * 36 + (f - 6) * 18) * 32 + lane;
      float sa[80];
      tile_ss<160, 0>(sa, c, [&](int s) { if ((s & 1) == 0) mbar_wait(bar_ofull + 8 * (s / 2), 0); }, [&](int s) {
        if (s == 0) { fence_regs<96>(B); if (lane == 0 && (warp & 3) == 0) mbar_arrive(bar_xfree + 64); }
        if (s < 12) part_group(&B[8 * (s < 12 ? s : 0)], part + (24 + s) * 32);
        if (s == 14) flag_signal_warp(fpart + 2);
      });
      float sb2[64];
      tile_ss<128, 0>(sb2, c, nop, [&](int s) {
        if (s == 0) fence_regs<80>(sa);
        if (s < 10) part_group(&sa[8 * (s < 10 ? s : 0)], sp + s * 32);
        if (s == 13) flag_signal_warp(fpart + 3 + (f - 6) * 2);
      });
      drain(c);
      fence_regs<64>(sb2);
#pragma unroll
      for (int q = 0; q < 8; q++) part_group(&sb2[8 * q], sp + (10 + q) * 32);
      flag_signal_warp(fpart + 4 + (f - 6) * 2);
    }
    {
      const uint32_t* fo = g_f_part + (m * 8 + f) * 16;
      if (lane < 7) flag_wait(fo + lane, (lane < 3 ? 8u : 1u) * ep);
      __syncwarp();
      const uint4* src = g_part + (size_t)((m * 8 + f) * 9 * 36) * 32 + lane;
      const size_t r0 = (size_t)(m * 128 + f * 16 + g) * D_;
#pragma unroll 1
      for (int v = warp; v < 36; v += 8) {
        uint4 p[9];
#pragma unroll
        for (int i = 0; i < 9; i++) p[i] = ldcg128(src + (i * 36 + v) * 32);
        const int col = 16 * v + 2 * t;
        uint32_t xx[4], bb[2];
        xx[0] = __ldg(reinterpret_cast<const uint32_t*>(P.x + r0 + col));
        xx[1] = __ldg(reinterpret_cast<const uint32_t*>(P.x + r0 + 8 * D_ + col));
        xx[2] = __ldg(reinterpret_cast<const uint32_t*>(P.x + r0 + col + 8));
        xx[3] = __ldg(reinterpret_cast<const uint32_t*>(P.x + r0 + 8 * D_ + col + 8));
        bb[0] = __ldg(reinterpret_cast<const uint32_t*>(P.b2 + col));
        bb[1] = __ldg(reinterpret_cast<const uint32_t*>(P.b2 + col + 8));
        uint32_t res[4];
#pragma unroll
        for (int q = 0; q < 4; q++) {
          float lo = 0.f, hi2 = 0.f;
#pragma unroll
          for (int i = 0; i < 8; i++) { uint32_t w = reinterpret_cast<const uint32_t*>(&p[i])[q]; lo += bf_lo(w); hi2 += bf_hi(w); }
          uint32_t sw = reinterpret_cast<const uint32_t*>(&p[8])[q];
          float ylo = fmaf(lo, 0.5f, bf_lo(bb[q >> 1])), yhi = fmaf(hi2, 0.5f, bf_hi(bb[q >> 1]));
          res[q] = pack_bf16(fmaf(bf_lo(sw), silu(ylo), bf_lo(xx[q])), fmaf(bf_hi(sw), silu(yhi), bf_hi(xx[q])));
        }
        *reinterpret_cast<uint32_t*>(P.out + r0 + col) = res[0];
        *reinterpret_cast<uint32_t*>(P.out + r0 + 8 * D_ + col) = res[1];
        *reinterpret_cast<uint32_t*>(P.out + r0 + col + 8) = res[2];
        *reinterpret_cast<uint32_t*>(P.out + r0 + 8 * D_ + col + 8) = res[3];
      }
    }
    cluster_arrive();
    cluster_wait();
    if (tid == 0) g_epoch[blockIdx.x] = ep;
  }
}

typedef CUresult (*EncFn)(CUtensorMap*, CUtensorMapDataType, cuuint32_t, void*, const cuuint64_t*, const cuuint64_t*, const cuuint32_t*, const cuuint32_t*,
                          CUtensorMapInterleave, CUtensorMapSwizzle, CUtensorMapL2promotion, CUtensorMapFloatOOBfill);

void make_map(EncFn enc, CUtensorMap* tm, const void* ptr, int rows, int cols, int box_rows) {
  cuuint64_t gd[2] = {(cuuint64_t)cols, (cuuint64_t)rows};
  cuuint64_t gs[1] = {(cuuint64_t)cols * 2};
  cuuint32_t bx[2] = {64, (cuuint32_t)box_rows};
  cuuint32_t es[2] = {1, 1};
  enc(tm, CU_TENSOR_MAP_DATA_TYPE_BFLOAT16, 2, const_cast<void*>(ptr), gd, gs, bx, es, CU_TENSOR_MAP_INTERLEAVE_NONE, CU_TENSOR_MAP_SWIZZLE_128B,
      CU_TENSOR_MAP_L2_PROMOTION_L2_256B, CU_TENSOR_MAP_FLOAT_OOB_FILL_NONE);
}

}

extern "C" void kernel_launch(void* const* d_in, const int* in_sizes, int n_in, void* d_out, int out_size) {
  (void)in_sizes; (void)n_in; (void)out_size;
  static EncFn enc = nullptr;
  static void* o_ptr = nullptr;
  if (!enc) {
    void* fn = nullptr; cudaDriverEntryPointQueryResult q;
    cudaGetDriverEntryPoint("cuTensorMapEncodeTiled", &fn, cudaEnableDefault, &q);
    enc = (EncFn)fn;
    cudaFuncSetAttribute(fused_kernel, cudaFuncAttributeMaxDynamicSharedMemorySize, SMEM_BYTES);
    cudaGetSymbolAddress(&o_ptr, g_o);
  }
  Params P;
  P.x = (const __nv_bfloat16*)d_in[0];
  P.wqkv = (const __nv_bfloat16*)d_in[1];
  P.wo = (const __nv_bfloat16*)d_in[2];
  P.w1 = (const __nv_bfloat16*)d_in[4];
  P.b1 = (const __nv_bfloat16*)d_in[5];
  P.w2 = (const __nv_bfloat16*)d_in[6];
  P.b2 = (const __nv_bfloat16*)d_in[7];
  P.out = (__nv_bfloat16*)d_out;
  P.zero = 0;
  make_map(enc, &P.tm_wqkv, P.wqkv, D_, Q3_, 32);
  make_map(enc, &P.tm_w1, P.w1, D_, F_, 32);
  make_map(enc, &P.tm_w2, P.w2, F_, D_, 32);
  make_map(enc, &P.tm_wo, P.wo, D_, D_, 32);
  make_map(enc, &P.tm_o, o_ptr, S_, D_, 128);
  cudaLaunchConfig_t cfg = {};
  cfg.gridDim = dim3(NCTAS); cfg.blockDim = dim3(NTHREADS); cfg.dynamicSmemBytes = SMEM_BYTES; cfg.stream = cudaStreamPerThread;
  cudaLaunchAttribute at[1];
  at[0].id = cudaLaunchAttributeClusterDimension; at[0].val.clusterDim.x = 2; at[0].val.clusterDim.y = 1; at[0].val.clusterDim.z = 1;
  cfg.attrs = at; cfg.numAttrs = 1;
  cudaLaunchKernelEx(&cfg, fused_kernel, P);
}
```

```cpp
#include <cuda_runtime.h>
#include <cuda.h>
#include <cuda_bf16.h>
#include <stdint.h>

namespace {

constexpr int S_ = 2048, D_ = 576, F_ = 4608, Q3_ = 1728;
constexpr int NSTAGE = 6, STAGE_BYTES = 12288;
constexpr int SM_A = 0, SM_B = 147456, SM_BIAS = SM_B + NSTAGE * STAGE_BYTES, SM_BAR = SM_BIAS + 2304;
constexpr int SMEM_BYTES = SM_BAR + 320;
constexpr int NTHREADS = 384;
constexpr int NCTAS = 132;

__device__ uint4 g_qkvf[(128 * 108 + 1) * 32];
__device__ __align__(1024) __nv_bfloat16 g_o[S_ * D_];
__device__ float4 g_kvp4[32 * 32 * 3 * 32];
__device__ float2 g_kvp2[32 * 32 * 3 * 32];
__device__ uint32_t g_kvt[32 * 9 * 32];
__device__ uint4 g_part[128 * 8 * 36 * 32];
__device__ uint4 g_s2[128 * 12 * 32];
__device__ uint4 g_g[128 * 24 * 32];
__device__ uint4 g_hsp[128 * 12 * 256];
__device__ uint32_t g_f_qkv[16 * 8];
__device__ uint32_t g_f_kvp[32];
__device__ uint32_t g_f_kvt[32];
__device__ uint32_t g_f_o[16];
__device__ uint32_t g_f_rb[128 * 8];
__device__ uint32_t g_epoch[NCTAS];

#define STAMP(i)
#define STAMPW(w, i)
__device__ __forceinline__ uint32_t smem_u32(const void* p) { return (uint32_t)__cvta_generic_to_shared(p); }
__device__ __forceinline__ void mbar_init(uint32_t a, int c) { asm volatile("mbarrier.init.shared::cta.b64 [%0], %1;" ::"r"(a), "r"(c)); }
__device__ __forceinline__ void mbar_expect(uint32_t a, uint32_t b) { asm volatile("mbarrier.arrive.expect_tx.shared::cta.b64 _, [%0], %1;" ::"r"(a), "r"(b) : "memory"); }
__device__ __forceinline__ void mbar_arrive(uint32_t a) { asm volatile("mbarrier.arrive.shared::cta.b64 _, [%0];" ::"r"(a) : "memory"); }
__device__ __forceinline__ void mbar_arrive_cl(uint32_t a) { asm volatile("mbarrier.arrive.shared::cluster.b64 _, [%0];" ::"r"(a) : "memory"); }
__device__ __forceinline__ uint32_t mapa(uint32_t a, uint32_t cta) { uint32_t r; asm volatile("mapa.shared::cluster.u32 %0, %1, %2;" : "=r"(r) : "r"(a), "r"(cta)); return r; }
__device__ __forceinline__ void mbar_wait(uint32_t a, uint32_t ph) {
  uint32_t ok; int it = 0;
  do {
    asm volatile("{.reg .pred p; mbarrier.try_wait.parity.shared::cta.b64 p, [%1], %2; selp.u32 %0,1,0,p;}" : "=r"(ok) : "r"(a), "r"(ph) : "memory");
  } while (!ok && ++it < (1 << 18));
}
__device__ __forceinline__ void tma2d(uint32_t dst, const CUtensorMap* m, int c0, int c1, uint32_t bar) {
  asm volatile("cp.async.bulk.tensor.2d.shared::cluster.global.mbarrier::complete_tx::bytes [%0], [%1, {%3,%4}], [%2];" ::"r"(dst), "l"(m), "r"(bar), "r"(c0), "r"(c1) : "memory");
}
__device__ __forceinline__ void tma2d_mc(uint32_t dst, const CUtensorMap* m, int c0, int c1, uint32_t bar) {
  asm volatile("cp.async.bulk.tensor.2d.shared::cluster.global.mbarrier::complete_tx::bytes.multicast::cluster [%0], [%1, {%3,%4}], [%2], %5;" ::"r"(dst), "l"(m), "r"(bar), "r"(c0), "r"(c1), "h"((uint16_t)3) : "memory");
}
__device__ __forceinline__ void cluster_arrive() { asm volatile("barrier.cluster.arrive.release.aligned;" ::: "memory"); }
__device__ __forceinline__ void cluster_arrive_relaxed() { asm volatile("barrier.cluster.arrive.relaxed.aligned;" ::: "memory"); }
__device__ __forceinline__ void cluster_wait() { asm volatile("barrier.cluster.wait.acquire.aligned;" ::: "memory"); }
__device__ __forceinline__ void wg_fence() { asm volatile("wgmma.fence.sync.aligned;" ::: "memory"); }
__device__ __forceinline__ void wg_commit() { asm volatile("wgmma.commit_group.sync.aligned;" ::: "memory"); }
template <int n> __device__ __forceinline__ void wg_wait() { asm volatile("wgmma.wait_group.sync.aligned %0;" ::"n"(n) : "memory"); }
__device__ __forceinline__ uint32_t ld_acquire(const uint32_t* p) { uint32_t v; asm volatile("ld.acquire.gpu.global.u32 %0, [%1];" : "=r"(v) : "l"(p) : "memory"); return v; }
__device__ __forceinline__ void flag_wait(const uint32_t* p, uint32_t target) {
  int it = 0;
  while ((int)(ld_acquire(p) - target) < 0 && ++it < (1 << 21)) __nanosleep(40);
}
__device__ __forceinline__ void flag_signal_warp(uint32_t* p) {
  __syncwarp();
  if ((threadIdx.x & 31) == 0) asm volatile("red.release.gpu.global.add.u32 [%0], 1;" ::"l"(p) : "memory");
}
__device__ __forceinline__ uint32_t pack_bf16(float lo, float hi) { uint32_t r; asm("cvt.rn.bf16x2.f32 %0, %1, %2;" : "=r"(r) : "f"(hi), "f"(lo)); return r; }
__device__ __forceinline__ float bf_lo(uint32_t v) { return __uint_as_float(v << 16); }
__device__ __forceinline__ float bf_hi(uint32_t v) { return __uint_as_float(v & 0xffff0000u); }
__device__ __forceinline__ float tanh_fast(float x) { float r; asm("tanh.approx.f32 %0, %1;" : "=f"(r) : "f"(x)); return r; }
__device__ __forceinline__ uint32_t movmat(uint32_t a) { uint32_t d; asm volatile("movmatrix.sync.aligned.m8n8.trans.b16 %0, %1;" : "=r"(d) : "r"(a)); return d; }
__device__ __forceinline__ void mma16816(float* c, uint32_t a0, uint32_t a1, uint32_t a2, uint32_t a3, uint32_t b0, uint32_t b1) {
  asm volatile("mma.sync.aligned.m16n8k16.row.col.f32.bf16.bf16.f32 {%0,%1,%2,%3}, {%4,%5,%6,%7}, {%8,%9}, {%0,%1,%2,%3};"
               : "+f"(c[0]), "+f"(c[1]), "+f"(c[2]), "+f"(c[3]) : "r"(a0), "r"(a1), "r"(a2), "r"(a3), "r"(b0), "r"(b1));
}
__device__ __forceinline__ uint32_t ldcg32(const void* p) { uint32_t v; asm volatile("ld.global.cg.u32 %0, [%1];" : "=r"(v) : "l"(p) : "memory"); return v; }
__device__ __forceinline__ uint4 ldcg128(const void* p) { uint4 v; asm volatile("ld.global.cg.v4.u32 {%0,%1,%2,%3}, [%4];" : "=r"(v.x), "=r"(v.y), "=r"(v.z), "=r"(v.w) : "l"(p) : "memory"); return v; }
__device__ __forceinline__ uint2 ldcg64(const void* p) { uint2 v; asm volatile("ld.global.cg.v2.u32 {%0,%1}, [%2];" : "=r"(v.x), "=r"(v.y) : "l"(p) : "memory"); return v; }

template <int N> __device__ __forceinline__ void wgmma_ss(float* d, uint64_t da, uint64_t db, int sc);
template <int N> __device__ __forceinline__ void wgmma_rs(float* d, const uint32_t* a, uint64_t db, int sc);
template <> __device__ __forceinline__ void wgmma_ss<96>(float* d, uint64_t da, uint64_t db, int sc) {
  asm volatile("{.reg .pred p; setp.ne.b32 p, %50, 0; wgmma.mma_async.sync.aligned.m64n96k16.f32.bf16.bf16 {%0, %1, %2, %3, %4, %5, %6, %7, %8, %9, %10, %11, %12, %13, %14, %15, %16, %17, %18, %19, %20, %21, %22, %23, %24, %25, %26, %27, %28, %29, %30, %31, %32, %33, %34, %35, %36, %37, %38, %39, %40, %41, %42, %43, %44, %45, %46, %47}, %48, %49, p, 1, 1, 0, 1;}"
   : "+f"(d[0]), "+f"(d[1]), "+f"(d[2]), "+f"(d[3]), "+f"(d[4]), "+f"(d[5]), "+f"(d[6]), "+f"(d[7]), "+f"(d[8]), "+f"(d[9]), "+f"(d[10]), "+f"(d[11]), "+f"(d[12]), "+f"(d[13]), "+f"(d[14]), "+f"(d[15]), "+f"(d[16]), "+f"(d[17]), "+f"(d[18]), "+f"(d[19]), "+f"(d[20]), "+f"(d[21]), "+f"(d[22]), "+f"(d[23]), "+f"(d[24]), "+f"(d[25]), "+f"(d[26]), "+f"(d[27]), "+f"(d[28]), "+f"(d[29]), "+f"(d[30]), "+f"(d[31]), "+f"(d[32]), "+f"(d[33]), "+f"(d[34]), "+f"(d[35]), "+f"(d[36]), "+f"(d[37]), "+f"(d[38]), "+f"(d[39]), "+f"(d[40]), "+f"(d[41]), "+f"(d[42]), "+f"(d[43]), "+f"(d[44]), "+f"(d[45]), "+f"(d[46]), "+f"(d[47]) : "l"(da), "l"(db), "r"(sc));
}
template <> __device__ __forceinline__ void wgmma_ss<192>(float* d, uint64_t da, uint64_t db, int sc) {
  asm volatile("{.reg .pred p; setp.ne.b32 p, %98, 0; wgmma.mma_async.sync.aligned.m64n192k16.f32.bf16.bf16 {%0, %1, %2, %3, %4, %5, %6, %7, %8, %9, %10, %11, %12, %13, %14, %15, %16, %17, %18, %19, %20, %21, %22, %23, %24, %25, %26, %27, %28, %29, %30, %31, %32, %33, %34, %35, %36, %37, %38, %39, %40, %41, %42, %43, %44, %45, %46, %47, %48, %49, %50, %51, %52, %53, %54, %55, %56, %57, %58, %59, %60, %61, %62, %63, %64, %65, %66, %67, %68, %69, %70, %71, %72, %73, %74, %75, %76, %77, %78, %79, %80, %81, %82, %83, %84, %85, %86, %87, %88, %89, %90, %91, %92, %93, %94, %95}, %96, %97, p, 1, 1, 0, 1;}"
   : "+f"(d[0]), "+f"(d[1]), "+f"(d[2]), "+f"(d[3]), "+f"(d[4]), "+f"(d[5]), "+f"(d[6]), "+f"(d[7]), "+f"(d[8]), "+f"(d[9]), "+f"(d[10]), "+f"(d[11]), "+f"(d[12]), "+f"(d[13]), "+f"(d[14]), "+f"(d[15]), "+f"(d[16]), "+f"(d[17]), "+f"(d[18]), "+f"(d[19]), "+f"(d[20]), "+f"(d[21]), "+f"(d[22]), "+f"(d[23]), "+f"(d[24]), "+f"(d[25]), "+f"(d[26]), "+f"(d[27]), "+f"(d[28]), "+f"(d[29]), "+f"(d[30]), "+f"(d[31]), "+f"(d[32]), "+f"(d[33]), "+f"(d[34]), "+f"(d[35]), "+f"(d[36]), "+f"(d[37]), "+f"(d[38]), "+f"(d[39]), "+f"(d[40]), "+f"(d[41]), "+f"(d[42]), "+f"(d[43]), "+f"(d[44]), "+f"(d[45]), "+f"(d[46]), "+f"(d[47]), "+f"(d[48]), "+f"(d[49]), "+f"(d[50]), "+f"(d[51]), "+f"(d[52]), "+f"(d[53]), "+f"(d[54]), "+f"(d[55]), "+f"(d[56]), "+f"(d[57]), "+f"(d[58]), "+f"(d[59]), "+f"(d[60]), "+f"(d[61]), "+f"(d[62]), "+f"(d[63]), "+f"(d[64]), "+f"(d[65]), "+f"(d[66]), "+f"(d[67]), "+f"(d[68]), "+f"(d[69]), "+f"(d[70]), "+f"(d[71]), "+f"(d[72]), "+f"(d[73]), "+f"(d[74]), "+f"(d[75]), "+f"(d[76]), "+f"(d[77]), "+f"(d[78]), "+f"(d[79]), "+f"(d[80]), "+f"(d[81]), "+f"(d[82]), "+f"(d[83]), "+f"(d[84]), "+f"(d[85]), "+f"(d[86]), "+f"(d[87]), "+f"(d[88]), "+f"(d[89]), "+f"(d[90]), "+f"(d[91]), "+f"(d[92]), "+f"(d[93]), "+f"(d[94]), "+f"(d[95]) : "l"(da), "l"(db), "r"(sc));
}

__device__ __forceinline__ uint64_t desc64(uint32_t lo, uint32_t hi) { uint64_t d; asm("mov.b64 %0, {%1, %2};" : "=l"(d) : "r"(lo), "r"(hi)); return d; }
constexpr uint32_t DESC_HI = (1024u >> 4) | (1u << 30);
template <int n> __device__ __forceinline__ void fence_regs(float* a) {
#pragma unroll
  for (int i = 0; i < n; i++) asm volatile("" : "+f"(a[i])::"memory");
}

struct Ctx {
  uint32_t full;
  uint32_t emb;
  uint32_t stage, phase, prev;
  uint32_t dB, dA;
  uint32_t xfree;
  uint32_t owait;
  __device__ __forceinline__ void release_prev() { if (emb != 0 && prev != ~0u) mbar_arrive_cl(emb + prev); }
};

template <int N>
__device__ __forceinline__ void stage_ss(float* acc, Ctx& c, int s, bool first) {
  if (c.owait != 0 && (s & 1) == 0) mbar_wait(c.owait + 4 * s, 0);
  mbar_wait(c.full + 8 * c.stage, c.phase);
  wg_fence();
  const uint32_t db = c.dB + c.stage * (STAGE_BYTES >> 4);
  const uint32_t da = c.dA + (s >> 1) * 1024 + (s & 1) * 4;
  wgmma_ss<N>(acc, desc64(da, DESC_HI), desc64(db, DESC_HI), first ? 0 : 1);
  wgmma_ss<N>(acc, desc64(da + 2, DESC_HI), desc64(db + 128, DESC_HI), 1);
  wg_commit();
  wg_wait<1>();
  c.release_prev();
  if (c.xfree != 0 && (s & 1) == 0) mbar_arrive(c.xfree + 4 * s);
  c.prev = 8 * c.stage;
  if (++c.stage == NSTAGE) { c.stage = 0; c.phase ^= 1; }
}

__device__ __forceinline__ float gelu2(float x) {
  float u = x * fmaf(x * x, 0.0356774081f, 0.7978845608f);
  return fmaf(x, tanh_fast(u), x);
}
__device__ __forceinline__ uint4 gelu_group(const float* a, const float* bias  ) {
  float2 b0 = *reinterpret_cast<const float2*>(bias);
  float2 b1 = *reinterpret_cast<const float2*>(bias + 8);
  uint4 h;
  h.x = pack_bf16(gelu2(a[0] + b0.x), gelu2(a[1] + b0.y));
  h.y = pack_bf16(gelu2(a[2] + b0.x), gelu2(a[3] + b0.y));
  h.z = pack_bf16(gelu2(a[4] + b1.x), gelu2(a[5] + b1.y));
  h.w = pack_bf16(gelu2(a[6] + b1.x), gelu2(a[7] + b1.y));
  return h;
}
__device__ __forceinline__ void stsm4(uint32_t addr, uint4 r) {
  asm volatile("stmatrix.sync.aligned.m8n8.x4.shared.b16 [%0], {%1,%2,%3,%4};" ::"r"(addr), "r"(r.x), "r"(r.y), "r"(r.z), "r"(r.w) : "memory");
}
__device__ __forceinline__ float ex2f(float x) { float r; asm("ex2.approx.ftz.f32 %0, %1;" : "=f"(r) : "f"(x)); return r; }
__device__ __forceinline__ float phi(float t) { return (t > 0.f ? t + 1.f : ex2f(t * 1.4426950408889634f)) + 1e-6f; }
__device__ __forceinline__ uint32_t phi2(uint32_t w) { return pack_bf16(phi(bf_lo(w)), phi(bf_hi(w))); }
template <int q0, int q1>
__device__ __forceinline__ void part_groups(const float* a, uint4* p) {
#pragma unroll
  for (int q = q0; q < q1; q++)
    p[q * 32] = make_uint4(pack_bf16(a[8 * q], a[8 * q + 1]), pack_bf16(a[8 * q + 2], a[8 * q + 3]), pack_bf16(a[8 * q + 4], a[8 * q + 5]), pack_bf16(a[8 * q + 6], a[8 * q + 7]));
}
__device__ __forceinline__ float silu(float y) { return __fdividef(y, 1.f + ex2f(y * -1.4426950408889634f)); }
__device__ __forceinline__ void gate_vec(const uint4* p, uint32_t b0, uint32_t b1, float* gt) {
#pragma unroll
  for (int q = 0; q < 4; q++) {
    float lo = 0.f, hi = 0.f;
#pragma unroll
    for (int i = 0; i < 8; i++) { uint32_t w = reinterpret_cast<const uint32_t*>(&p[i])[q]; lo += bf_lo(w); hi += bf_hi(w); }
    const uint32_t bb = q < 2 ? b0 : b1;
    gt[2 * q] = silu(fmaf(lo, 0.5f, bf_lo(bb)));
    gt[2 * q + 1] = silu(fmaf(hi, 0.5f, bf_hi(bb)));
  }
}

struct Params {
  CUtensorMap tm_wqkv, tm_w1, tm_w2, tm_wo, tm_o, tm_x;
  const __nv_bfloat16 *x, *b1, *b2, *wqkv, *w1, *w2, *wo;
  __nv_bfloat16* out;
};

__global__ void __cluster_dims__(2, 1, 1) __launch_bounds__(NTHREADS, 1) fused_kernel(const __grid_constant__ Params P) {
  extern __shared__ __align__(1024) uint8_t smem[];
  const uint32_t sbase = smem_u32(smem);
  const int tid = threadIdx.x, lane = tid & 31;
  const int warp = __shfl_sync(0xffffffffu, tid >> 5, 0);
  const int g = lane >> 2, t = lane & 3;
  const uint32_t ep = g_epoch[blockIdx.x] + 1;
  STAMPW(0, 0);

  if (blockIdx.x >= 128) {
    const int a = blockIdx.x - 128;
    if (warp < 8) {
      const int head = a * 8 + warp;
      if (lane == 0) flag_wait(&g_f_kvp[head], 32 * ep);
      __syncwarp();
      STAMPW(0, 1);
      float s4[3][4], s2[3][2];
#pragma unroll
      for (int j = 0; j < 3; j++) { s4[j][0] = s4[j][1] = s4[j][2] = s4[j][3] = 0.f; s2[j][0] = s2[j][1] = 0.f; }
#pragma unroll 1
      for (int m0 = 0; m0 < 32; m0 += 8) {
        uint4 v[8][3]; uint2 w[8][3];
#pragma unroll
        for (int m = 0; m < 8; m++)
#pragma unroll
          for (int j = 0; j < 3; j++) {
            v[m][j] = ldcg128(&g_kvp4[((head * 32 + m0 + m) * 3 + j) * 32 + lane]);
            w[m][j] = ldcg64(&g_kvp2[((head * 32 + m0 + m) * 3 + j) * 32 + lane]);
          }
#pragma unroll
        for (int m = 0; m < 8; m++)
#pragma unroll
          for (int j = 0; j < 3; j++) {
            s4[j][0] += __uint_as_float(v[m][j].x); s4[j][1] += __uint_as_float(v[m][j].y); s4[j][2] += __uint_as_float(v[m][j].z); s4[j][3] += __uint_as_float(v[m][j].w);
            s2[j][0] += __uint_as_float(w[m][j].x); s2[j][1] += __uint_as_float(w[m][j].y);
          }
      }
#pragma unroll
      for (int j = 0; j < 3; j++) {
        g_kvt[(head * 9 + 0 + j) * 32 + lane] = pack_bf16(s4[j][0], s4[j][1]);
        g_kvt[(head * 9 + 3 + j) * 32 + lane] = pack_bf16(s4[j][2], s4[j][3]);
        g_kvt[(head * 9 + 6 + j) * 32 + lane] = pack_bf16(s2[j][0], s2[j][1]);
      }
      flag_signal_warp(&g_f_kvt[head]);
      STAMPW(0, 2);
    } else if (lane == 0) {
      const int id = a * 4 + (warp - 8);
      constexpr uint32_t CH = 9216 * 2;
#pragma unroll 1
      for (int i = id; i < 612; i += 16) {
        const char* p = i < 288 ? (const char*)P.w1 + (size_t)i * CH : (i < 576 ? (const char*)P.w2 + (size_t)(i - 288) * CH : (const char*)P.wo + (size_t)(i - 576) * CH);
        asm volatile("cp.async.bulk.prefetch.L2.global [%0], %1;" ::"l"(p), "r"(CH) : "memory");
      }
    }
    __syncthreads();
    if (tid == 0) g_epoch[blockIdx.x] = ep;
    return;
  }

  const int cl = blockIdx.x >> 1, rank = blockIdx.x & 1;
  const int f = cl & 7, m = (cl >> 3) * 2 + rank;
  const int srole = f >= 6 ? 1 : 0;
  const uint32_t bar_full = sbase + SM_BAR, bar_empty = bar_full + 8 * NSTAGE, bar_xfree = bar_empty + 8 * NSTAGE, bar_ofull = bar_xfree + 72, bar_x = bar_ofull + 72;

  if (tid == 256) {
#pragma unroll 1
    for (int i = 0; i < 4; i++) mbar_init(bar_x + 8 * i, 1);
    asm volatile("fence.mbarrier_init.release.cluster;" ::: "memory");
#pragma unroll 1
    for (int i = 0; i < 4; i++) {
      mbar_expect(bar_x + 8 * i, 36864);
#pragma unroll 1
      for (int kb = 0; kb < 9; kb++) tma2d(sbase + SM_A + kb * 16384 + i * 4096, &P.tm_x, kb * 64, m * 128 + i * 32, bar_x + 8 * i);
    }
  } else if (tid == 0) {
#pragma unroll 1
    for (int i = 0; i < NSTAGE; i++) { mbar_init(bar_full + 8 * i, 1); mbar_init(bar_empty + 8 * i, 4); }
#pragma unroll 1
    for (int i = 0; i < 9; i++) { mbar_init(bar_xfree + 8 * i, 2); mbar_init(bar_ofull + 8 * i, 1); }
    asm volatile("fence.mbarrier_init.release.cluster;" ::: "memory");
  }
  __syncwarp();
  cluster_arrive_relaxed();

  if (warp >= 8) {
    asm volatile("setmaxnreg.dec.sync.aligned.u32 56;");
    cluster_wait();
    if (warp == 8) {
      if (lane == 0) {
        uint32_t stage = 0, phase = 1;
        const uint32_t sb = sbase + SM_B;
#pragma unroll 1
        for (int tl = 2 * srole; tl < 8 + 2 * srole; tl++) {
          const CUtensorMap* map = tl < 2 ? &P.tm_wqkv : (tl < 5 ? &P.tm_w1 : (tl < 8 ? &P.tm_w2 : &P.tm_wo));
          const int col = tl < 2 ? 288 * f + 96 * tl : (tl < 5 ? 576 * f + 192 * (tl - 2) : (tl < 8 ? 192 * (tl - 5) : (tl == 8 ? 384 + 96 * (f - 6) : 192 * (f - 6))));
          const bool perm = tl >= 5 && tl < 8;
          const bool three = (tl & 7) != 0;
#pragma unroll 1
          for (int st = 0; st < 18; st++) {
            int row = st * 32;
            if (perm) row += 576 * f + ((st < 6) ? 192 : (st < 12 ? -192 : 0));
            mbar_wait(bar_empty + 8 * stage, phase);
            mbar_expect(bar_full + 8 * stage, three ? 12288 : 8192);
            const uint32_t dst = sb + stage * STAGE_BYTES;
            if (((st ^ rank) & 1) == 0) {
              tma2d_mc(dst, map, col, row, bar_full + 8 * stage);
              if (three) tma2d_mc(dst + 8192, map, col + 128, row, bar_full + 8 * stage);
            } else {
              tma2d_mc(dst + 4096, map, col + 64, row, bar_full + 8 * stage);
            }
            if (++stage == NSTAGE) { stage = 0; phase ^= 1; }
          }
        }
      }
      __syncwarp();
    } else {
      const int aw = warp - 9;
      const int hi = f >> 2;
      const uint32_t* qf = reinterpret_cast<const uint32_t*>(g_qkvf) + (size_t)m * 8 * 108 * 128 + g * 16;
      auto coloff = [&](int c) { return (c >> 4) * 128 + ((c & 7) >> 1) * 4 + ((c >> 3) & 1) * 2; };
      if (lane < 2) flag_wait(&g_f_qkv[m * 8 + 2 + 2 * lane + hi], 16 * ep);
      __syncwarp();
      STAMPW(9, 20);
#pragma unroll 1
      for (int u = aw; u < 8; u += 3) {
        const int head = 4 * f + (u >> 1), half = u & 1;
        int off[3];
#pragma unroll
        for (int b = 0; b < 3; b++) off[b] = coloff(576 + head * 18 + 8 * b + 2 * t);
        float c0[3][4], c1[3][4];
#pragma unroll
        for (int j = 0; j < 3; j++) { c0[j][0] = c0[j][1] = c0[j][2] = c0[j][3] = 0.f; c1[j][0] = c1[j][1] = c1[j][2] = c1[j][3] = 0.f; }
#pragma unroll 1
        for (int k2 = 0; k2 < 2; k2++) {
          uint2 kf[2][3], vf[2][3];
#pragma unroll
          for (int ks = 0; ks < 2; ks++) {
            const uint32_t* p = qf + (half * 4 + k2 * 2 + ks) * 108 * 128;
#pragma unroll
            for (int b = 0; b < 3; b++) { kf[ks][b] = ldcg64(p + off[b]); vf[ks][b] = ldcg64(p + off[b] + 36 * 128); }
          }
#pragma unroll
          for (int ks = 0; ks < 2; ks++) {
#pragma unroll
            for (int b = 0; b < 3; b++) { kf[ks][b].x = phi2(kf[ks][b].x); kf[ks][b].y = phi2(kf[ks][b].y); }
            if (t != 0) { kf[ks][2].x = kf[ks][2].y = 0u; vf[ks][2].x = vf[ks][2].y = (t == 1 ? 0x00003f80u : 0u); }
#pragma unroll
            for (int b = 0; b < 3; b++) { kf[ks][b].x = movmat(kf[ks][b].x); kf[ks][b].y = movmat(kf[ks][b].y); vf[ks][b].x = movmat(vf[ks][b].x); vf[ks][b].y = movmat(vf[ks][b].y); }
#pragma unroll
            for (int j = 0; j < 3; j++) {
              mma16816(c0[j], vf[ks][0].x, vf[ks][1].x, vf[ks][0].y, vf[ks][1].y, kf[ks][j].x, kf[ks][j].y);
              mma16816(c1[j], vf[ks][2].x, 0u, vf[ks][2].y, 0u, kf[ks][j].x, kf[ks][j].y);
            }
          }
        }
#pragma unroll
        for (int j = 0; j < 3; j++) {
          g_kvp4[((head * 32 + m * 2 + half) * 3 + j) * 32 + lane] = make_float4(c0[j][0], c0[j][1], c0[j][2], c0[j][3]);
          g_kvp2[((head * 32 + m * 2 + half) * 3 + j) * 32 + lane] = make_float2(c1[j][0], c1[j][1]);
        }
        flag_signal_warp(&g_f_kvp[head]);
      }
      STAMPW(9, 21);
      if (lane < 5) flag_wait(lane < 4 ? &g_f_kvt[4 * f + lane] : &g_f_qkv[m * 8 + hi], lane < 4 ? ep : 16 * ep);
      __syncwarp();
      STAMPW(9, 22);
#pragma unroll 1
      for (int hh = 0; hh < 4; hh++) {
        const int head = 4 * f + hh;
        const int rb0 = (aw + hh) % 3;
        uint32_t bf[9];
        uint2 qa[3][3];
#pragma unroll
        for (int i = 0; i < 9; i++) bf[i] = ldcg32(&g_kvt[(head * 9 + i) * 32 + lane]);
#pragma unroll
        for (int b = 0; b < 3; b++) {
          const int o = coloff(head * 18 + 8 * b + 2 * t);
#pragma unroll
          for (int j = 0; j < 3; j++) qa[j][b] = ldcg64(qf + min(rb0 + 3 * j, 7) * 108 * 128 + o);
        }
#pragma unroll
        for (int j = 0; j < 3; j++) {
          const int rb = rb0 + 3 * j;
          if (rb < 8) {
#pragma unroll
            for (int b = 0; b < 3; b++) { qa[j][b].x = phi2(qa[j][b].x); qa[j][b].y = phi2(qa[j][b].y); }
            if (t != 0) qa[j][2].x = qa[j][2].y = 0u;
            float c[3][4];
#pragma unroll
            for (int e = 0; e < 3; e++) {
              c[e][0] = c[e][1] = c[e][2] = c[e][3] = 0.f;
              mma16816(c[e], qa[j][0].x, qa[j][0].y, qa[j][1].x, qa[j][1].y, bf[e * 3 + 0], bf[e * 3 + 1]);
              mma16816(c[e], qa[j][2].x, qa[j][2].y, 0u, 0u, bf[e * 3 + 2], 0u);
            }
            const float r0 = __fdividef(1.f, __shfl_sync(0xffffffffu, c[2][0], (lane & ~3) | 1) + 1e-6f);
            const float r1 = __fdividef(1.f, __shfl_sync(0xffffffffu, c[2][2], (lane & ~3) | 1) + 1e-6f);
            __nv_bfloat16* po = g_o + (size_t)(m * 128 + rb * 16 + g) * D_ + head * 18 + 2 * t;
            *reinterpret_cast<uint32_t*>(po) = pack_bf16(c[0][0] * r0, c[0][1] * r0);
            *reinterpret_cast<uint32_t*>(po + 8) = pack_bf16(c[1][0] * r0, c[1][1] * r0);
            *reinterpret_cast<uint32_t*>(po + 8 * D_) = pack_bf16(c[0][2] * r1, c[0][3] * r1);
            *reinterpret_cast<uint32_t*>(po + 8 * D_ + 8) = pack_bf16(c[1][2] * r1, c[1][3] * r1);
            if (t == 0) {
              *reinterpret_cast<uint32_t*>(po + 16) = pack_bf16(c[2][0] * r0, c[2][1] * r0);
              *reinterpret_cast<uint32_t*>(po + 8 * D_ + 16) = pack_bf16(c[2][2] * r1, c[2][3] * r1);
            }
          }
        }
      }
      asm volatile("fence.proxy.async.global;" ::: "memory");
      flag_signal_warp(&g_f_o[m]);
      STAMPW(9, 23);
      if (srole && aw == 2) {
        if (lane == 0) {
          flag_wait(&g_f_o[m], 24 * ep);
          asm volatile("fence.proxy.async.global;" ::: "memory");
#pragma unroll 1
          for (int kb = 0; kb < 9; kb++) {
            mbar_wait(bar_xfree + 8 * kb, 0);
            mbar_expect(bar_ofull + 8 * kb, 16384);
            tma2d(sbase + SM_A + kb * 16384, &P.tm_o, kb * 64, m * 128, bar_ofull + 8 * kb);
          }
        }
        __syncwarp();
      }
      const int rbg = m * 8 + f;
#pragma unroll 1
      for (int ch = 0; ch < 2; ch++) {
        if (lane == 0) flag_wait(&g_f_rb[rbg * 8 + ch], 8 * ep);
        __syncwarp();
        STAMPW(9, 24 + 2 * ch);
#pragma unroll 1
        for (int v = ch * 12 + aw * 4; v < ch * 12 + aw * 4 + 4; v++) {
          uint4 p[8];
#pragma unroll
          for (int i = 0; i < 8; i++) p[i] = ldcg128(&g_part[((rbg * 8 + i) * 36 + v) * 32 + lane]);
          const uint32_t b0 = __ldg(reinterpret_cast<const uint32_t*>(P.b2 + 16 * v + 2 * t)), b1 = __ldg(reinterpret_cast<const uint32_t*>(P.b2 + 16 * v + 8 + 2 * t));
          float gt[8];
          gate_vec(p, b0, b1, gt);
          g_g[(rbg * 24 + v) * 32 + lane] = make_uint4(pack_bf16(gt[0], gt[1]), pack_bf16(gt[2], gt[3]), pack_bf16(gt[4], gt[5]), pack_bf16(gt[6], gt[7]));
        }
        flag_signal_warp(&g_f_rb[rbg * 8 + 4 + ch]);
        STAMPW(9, 25 + 2 * ch);
      }
    }
    cluster_arrive_relaxed();
    cluster_wait();
  } else {
    asm volatile("setmaxnreg.inc.sync.aligned.u32 224;");
    const int wg = warp >> 2;
    float* sbias = reinterpret_cast<float*>(smem + SM_BIAS);
    for (int i = tid; i < 576; i += 256) sbias[i] = __bfloat162float(P.b1[576 * f + i]);
    cluster_wait();
#pragma unroll 1
    for (int it = 0; it < 4; it++) {
      mbar_wait(bar_x + 8 * it, 0);
      uint8_t* rowp = smem + SM_A + (it * 32 + warp * 4 + (lane >> 3)) * 128 + (lane & 7) * 16;
      float v[72];
      float sum = 0.f;
#pragma unroll
      for (int kb = 0; kb < 9; kb++) {
        const uint4 w = *reinterpret_cast<const uint4*>(rowp + kb * 16384);
        v[8 * kb + 0] = bf_lo(w.x); v[8 * kb + 1] = bf_hi(w.x); v[8 * kb + 2] = bf_lo(w.y); v[8 * kb + 3] = bf_hi(w.y);
        v[8 * kb + 4] = bf_lo(w.z); v[8 * kb + 5] = bf_hi(w.z); v[8 * kb + 6] = bf_lo(w.w); v[8 * kb + 7] = bf_hi(w.w);
        sum += ((v[8 * kb] + v[8 * kb + 1]) + (v[8 * kb + 2] + v[8 * kb + 3])) + ((v[8 * kb + 4] + v[8 * kb + 5]) + (v[8 * kb + 6] + v[8 * kb + 7]));
      }
      sum += __shfl_xor_sync(0xffffffffu, sum, 1); sum += __shfl_xor_sync(0xffffffffu, sum, 2); sum += __shfl_xor_sync(0xffffffffu, sum, 4);
      const float mean = sum * (1.f / 576.f);
      float sq0 = 0.f, sq1 = 0.f;
#pragma unroll
      for (int i = 0; i < 72; i += 2) { v[i] -= mean; v[i + 1] -= mean; sq0 = fmaf(v[i], v[i], sq0); sq1 = fmaf(v[i + 1], v[i + 1], sq1); }
      float sq = sq0 + sq1;
      sq += __shfl_xor_sync(0xffffffffu, sq, 1); sq += __shfl_xor_sync(0xffffffffu, sq, 2); sq += __shfl_xor_sync(0xffffffffu, sq, 4);
      const float rstd = rsqrtf(sq * (1.f / 576.f) + 1e-5f);
#pragma unroll
      for (int kb = 0; kb < 9; kb++)
        *reinterpret_cast<uint4*>(rowp + kb * 16384) = make_uint4(pack_bf16(v[8 * kb] * rstd, v[8 * kb + 1] * rstd), pack_bf16(v[8 * kb + 2] * rstd, v[8 * kb + 3] * rstd),
                                                                   pack_bf16(v[8 * kb + 4] * rstd, v[8 * kb + 5] * rstd), pack_bf16(v[8 * kb + 6] * rstd, v[8 * kb + 7] * rstd));
    }
    asm volatile("fence.proxy.async.shared::cta;" ::: "memory");
    asm volatile("bar.sync 1, 256;" ::: "memory");
    STAMPW(0, 1);

    Ctx c;
    c.full = bar_full;
    c.emb = (lane == 0 && (warp & 3) < 2) ? mapa(bar_empty, (warp & 3) == 0 ? rank : (rank ^ 1)) : 0u;
    c.stage = 0; c.phase = 0; c.prev = ~0u;
    c.dB = (((sbase + SM_B) & 0x3FFFF) >> 4) | ((4096u >> 4) << 16);
    c.dA = (((sbase + SM_A + wg * 8192) & 0x3FFFF) >> 4) | (1u << 16);
    c.xfree = 0; c.owait = 0;
    const bool leader = (lane == 0) && ((warp & 3) == 0);

    const int rb = m * 8 + warp;
    const float* bias_t = sbias + 2 * t;
    uint4* part = g_part + (size_t)((rb * 8 + f) * 36) * 32 + lane;
    uint4* qkvp = g_qkvf + (size_t)(rb * 108 + 18 * f) * 32 + lane;
    uint4* hsp = g_hsp + (size_t)blockIdx.x * 12 * 256 + tid;
    const uint32_t hst = sbase + SM_A + (warp * 16 + (lane & 7) + ((lane >> 3) & 1) * 8) * 128 + (((lane >> 4) ^ (lane & 7)) << 4);
    auto wg_sync = [&]() {
      asm volatile("fence.proxy.async.shared::cta;" ::: "memory");
      if (wg == 0) asm volatile("bar.sync 2, 128;" ::: "memory"); else asm volatile("bar.sync 3, 128;" ::: "memory");
    };
    float A[96], B[96];
#pragma unroll
    for (int i = 0; i < 96; i++) A[i] = 0.f;

#pragma unroll 1
    for (int i = srole; i < 4 + srole; i++) {
      uint4* dstA = i == 1 ? qkvp + 6 * 32 : part + (i == 3 ? 0 : 24 * 32);
      uint32_t* flgA = i == 1 ? &g_f_qkv[m * 8 + f] : &g_f_rb[rb * 8 + (i == 3 ? 0 : 2)];
      const bool partA = (i == 1 && !srole) || i >= 3;
      if ((i & 3) == 0) {
        if (i == 4) c.owait = bar_ofull;
        stage_ss<96>(B, c, 0, true);
        c.xfree = 0;
        fence_regs<96>(A);
        if (partA) part_groups<0, 6>(A, dstA);
        stage_ss<96>(B, c, 1, false);
        if (partA) part_groups<6, 12>(A, dstA);
#pragma unroll 1
        for (int s = 2; s < 17; s++) {
          stage_ss<96>(B, c, s, false);
          if (s == 5 && partA) flag_signal_warp(flgA);
        }
        stage_ss<96>(B, c, 17, false);
        c.owait = 0;
      } else {
        const bool gel = i == 2;
        stage_ss<192>(B, c, 0, true);
        fence_regs<96>(A);
        if (partA) part_groups<0, 6>(A, dstA);
        stage_ss<192>(B, c, 1, false);
        if (partA) part_groups<6, 12>(A, dstA);
#pragma unroll
        for (int s = 2; s < 8; s++) {
          stage_ss<192>(B, c, s, false);
          if (gel) {
#pragma unroll
            for (int q = 2 * (s - 2); q < 2 * (s - 2) + 2; q++) stsm4((hst ^ ((q & 3) << 5)) + (q >> 2) * 16384, gelu_group(&A[8 * q], bias_t + 16 * (12 + q)));
          } else if (s == 3 && partA) flag_signal_warp(flgA);
        }
        uint4 pk[4];
#pragma unroll
        for (int q = 0; q < 4; q++) pk[q] = make_uint4(0, 0, 0, 0);
#pragma unroll 1
        for (int s = 8; s < 17; s++) {
          stage_ss<192>(B, c, s, false);
          if (gel && (s & 1) == 0) {
            if (s >= 10 && s <= 14) {
#pragma unroll
              for (int q = 0; q < 4; q++) stsm4((hst ^ (q << 5)) + (s / 2 - 2) * 16384, pk[q]);
            }
            if (s <= 12) {
#pragma unroll
              for (int q = 0; q < 4; q++) pk[q] = ldcg128(hsp + ((s - 8) * 2 + q) * 256);
            }
            if (s == 16) wg_sync();
          }
        }
        stage_ss<192>(B, c, 17, false);
      }
      STAMPW(0, 2 + 2 * i);
      {
        uint4* dstB = i == 0 ? qkvp : (i == 3 ? part + 12 * 32 : g_s2 + (size_t)(rb * 12 + 6 * (f - 6)) * 32 + lane);
        uint32_t* flgB = i == 0 ? &g_f_qkv[m * 8 + f] : &g_f_rb[rb * 8 + (i == 3 ? 1 : 3)];
        const bool gel = (i == 1) || (i == 2);
        stage_ss<192>(A, c, 0, true);
        if (i == 3 && srole && leader) c.xfree = bar_xfree - 8;
        fence_regs<96>(B);
        if (!gel) part_groups<0, 6>(B, dstB);
        stage_ss<192>(A, c, 1, false);
        if (i == 3) part_groups<6, 12>(B, dstB);
        const float* bs = bias_t + (i == 1 ? 0 : 16 * 24);
#pragma unroll
        for (int s = 2; s < 8; s++) {
          stage_ss<192>(A, c, s, false);
          if (gel) {
#pragma unroll
            for (int q = 2 * (s - 2); q < 2 * (s - 2) + 2; q++) {
              const uint4 hv = gelu_group(&B[8 * q], bs + 16 * q);
              if (i == 1) hsp[q * 256] = hv; else stsm4((hst ^ ((q & 3) << 5)) + (6 + (q >> 2)) * 16384, hv);
            }
          } else if (s == 3) flag_signal_warp(flgB);
        }
#pragma unroll 1
        for (int s = 8; s < 17; s++) {
          stage_ss<192>(A, c, s, false);
          if (s == 10 && i == 2) wg_sync();
        }
        stage_ss<192>(A, c, 17, false);
        if (c.xfree != 0) c.xfree = bar_xfree + 64;
      }
      STAMPW(0, 3 + 2 * i);
    }

    const size_t r0 = (size_t)(rb * 16 + g) * D_ + 2 * t;
    if (srole) {
      const int cb = 192 * (f - 6);
      uint32_t xx[48];
      uint4 gg[12];
#pragma unroll
      for (int q = 0; q < 12; q++) {
        xx[4 * q + 0] = __ldg(reinterpret_cast<const uint32_t*>(P.x + r0 + cb + 16 * q));
        xx[4 * q + 1] = __ldg(reinterpret_cast<const uint32_t*>(P.x + r0 + 8 * D_ + cb + 16 * q));
        xx[4 * q + 2] = __ldg(reinterpret_cast<const uint32_t*>(P.x + r0 + cb + 16 * q + 8));
        xx[4 * q + 3] = __ldg(reinterpret_cast<const uint32_t*>(P.x + r0 + 8 * D_ + cb + 16 * q + 8));
      }
      if (lane == 0) flag_wait(&g_f_rb[rb * 8 + 4 + (f - 6)], 3 * ep);
      __syncwarp();
      STAMPW(0, 14);
#pragma unroll
      for (int q = 0; q < 12; q++) gg[q] = ldcg128(&g_g[(rb * 24 + 12 * (f - 6) + q) * 32 + lane]);
      wg_wait<0>();
      c.release_prev();
      fence_regs<96>(A);
#pragma unroll
      for (int q = 0; q < 12; q++) {
        const uint32_t* gw = reinterpret_cast<const uint32_t*>(&gg[q]);
        uint32_t res[4];
#pragma unroll
        for (int k = 0; k < 4; k++)
          res[k] = pack_bf16(fmaf(A[8 * q + 2 * k], bf_lo(gw[k]), bf_lo(xx[4 * q + k])), fmaf(A[8 * q + 2 * k + 1], bf_hi(gw[k]), bf_hi(xx[4 * q + k])));
        *reinterpret_cast<uint32_t*>(P.out + r0 + cb + 16 * q) = res[0];
        *reinterpret_cast<uint32_t*>(P.out + r0 + 8 * D_ + cb + 16 * q) = res[1];
        *reinterpret_cast<uint32_t*>(P.out + r0 + cb + 16 * q + 8) = res[2];
        *reinterpret_cast<uint32_t*>(P.out + r0 + 8 * D_ + cb + 16 * q + 8) = res[3];
      }
    } else {
      wg_wait<0>();
      c.release_prev();
      fence_regs<96>(A);
      part_groups<0, 12>(A, part + 24 * 32);
      flag_signal_warp(&g_f_rb[rb * 8 + 2]);
      STAMPW(0, 12);
      const int cb = 384 + 32 * f;
      uint32_t xx[8], bb[4];
#pragma unroll
      for (int j = 0; j < 2; j++) {
        xx[4 * j + 0] = __ldg(reinterpret_cast<const uint32_t*>(P.x + r0 + cb + 16 * j));
        xx[4 * j + 1] = __ldg(reinterpret_cast<const uint32_t*>(P.x + r0 + 8 * D_ + cb + 16 * j));
        xx[4 * j + 2] = __ldg(reinterpret_cast<const uint32_t*>(P.x + r0 + cb + 16 * j + 8));
        xx[4 * j + 3] = __ldg(reinterpret_cast<const uint32_t*>(P.x + r0 + 8 * D_ + cb + 16 * j + 8));
        bb[2 * j] = __ldg(reinterpret_cast<const uint32_t*>(P.b2 + cb + 16 * j + 2 * t));
        bb[2 * j + 1] = __ldg(reinterpret_cast<const uint32_t*>(P.b2 + cb + 16 * j + 8 + 2 * t));
      }
      if (lane < 2) flag_wait(&g_f_rb[rb * 8 + 2 + lane], (lane == 0 ? 8u : 2u) * ep);
      __syncwarp();
      STAMPW(0, 14);
      uint4 p[2][8], sv[2];
#pragma unroll
      for (int j = 0; j < 2; j++) {
#pragma unroll
        for (int i = 0; i < 8; i++) p[j][i] = ldcg128(&g_part[((rb * 8 + i) * 36 + 24 + 2 * f + j) * 32 + lane]);
        sv[j] = ldcg128(&g_s2[(rb * 12 + 2 * f + j) * 32 + lane]);
      }
#pragma unroll
      for (int j = 0; j < 2; j++) {
        float gt[8];
        gate_vec(p[j], bb[2 * j], bb[2 * j + 1], gt);
        const uint32_t* sw = reinterpret_cast<const uint32_t*>(&sv[j]);
        uint32_t res[4];
#pragma unroll
        for (int k = 0; k < 4; k++) res[k] = pack_bf16(fmaf(bf_lo(sw[k]), gt[2 * k], bf_lo(xx[4 * j + k])), fmaf(bf_hi(sw[k]), gt[2 * k + 1], bf_hi(xx[4 * j + k])));
        *reinterpret_cast<uint32_t*>(P.out + r0 + cb + 16 * j) = res[0];
        *reinterpret_cast<uint32_t*>(P.out + r0 + 8 * D_ + cb + 16 * j) = res[1];
        *reinterpret_cast<uint32_t*>(P.out + r0 + cb + 16 * j + 8) = res[2];
        *reinterpret_cast<uint32_t*>(P.out + r0 + 8 * D_ + cb + 16 * j + 8) = res[3];
      }
    }
    STAMPW(0, 15);
    cluster_arrive_relaxed();
    cluster_wait();
    STAMPW(0, 16);
    if (tid == 0) g_epoch[blockIdx.x] = ep;
  }
}

typedef CUresult (*EncFn)(CUtensorMap*, CUtensorMapDataType, cuuint32_t, void*, const cuuint64_t*, const cuuint64_t*, const cuuint32_t*, const cuuint32_t*,
                          CUtensorMapInterleave, CUtensorMapSwizzle, CUtensorMapL2promotion, CUtensorMapFloatOOBfill);

void make_map(EncFn enc, CUtensorMap* tm, const void* ptr, int rows, int cols, int box_rows) {
  cuuint64_t gd[2] = {(cuuint64_t)cols, (cuuint64_t)rows};
  cuuint64_t gs[1] = {(cuuint64_t)cols * 2};
  cuuint32_t bx[2] = {64, (cuuint32_t)box_rows};
  cuuint32_t es[2] = {1, 1};
  enc(tm, CU_TENSOR_MAP_DATA_TYPE_BFLOAT16, 2, const_cast<void*>(ptr), gd, gs, bx, es, CU_TENSOR_MAP_INTERLEAVE_NONE, CU_TENSOR_MAP_SWIZZLE_128B,
      CU_TENSOR_MAP_L2_PROMOTION_L2_256B, CU_TENSOR_MAP_FLOAT_OOB_FILL_NONE);
}

}

extern "C" void kernel_launch(void* const* d_in, const int* in_sizes, int n_in, void* d_out, int out_size) {
  (void)in_sizes; (void)n_in; (void)out_size;
  static EncFn enc = nullptr;
  static void* o_ptr = nullptr;
  if (!enc) {
    void* fn = nullptr; cudaDriverEntryPointQueryResult q;
    cudaGetDriverEntryPoint("cuTensorMapEncodeTiled", &fn, cudaEnableDefault, &q);
    enc = (EncFn)fn;
    cudaFuncSetAttribute(fused_kernel, cudaFuncAttributeMaxDynamicSharedMemorySize, SMEM_BYTES);
    cudaGetSymbolAddress(&o_ptr, g_o);
  }
  Params P;
  P.x = (const __nv_bfloat16*)d_in[0];
  P.wqkv = (const __nv_bfloat16*)d_in[1];
  P.wo = (const __nv_bfloat16*)d_in[2];
  P.w1 = (const __nv_bfloat16*)d_in[4];
  P.b1 = (const __nv_bfloat16*)d_in[5];
  P.w2 = (const __nv_bfloat16*)d_in[6];
  P.b2 = (const __nv_bfloat16*)d_in[7];
  P.out = (__nv_bfloat16*)d_out;
  make_map(enc, &P.tm_wqkv, P.wqkv, D_, Q3_, 32);
  make_map(enc, &P.tm_w1, P.w1, D_, F_, 32);
  make_map(enc, &P.tm_w2, P.w2, F_, D_, 32);
  make_map(enc, &P.tm_wo, P.wo, D_, D_, 32);
  make_map(enc, &P.tm_o, o_ptr, S_, D_, 128);
  make_map(enc, &P.tm_x, P.x, S_, D_, 32);
  fused_kernel<<<NCTAS, NTHREADS, SMEM_BYTES, cudaStreamPerThread>>>(P);
}
```

```cpp
#include <cuda_runtime.h>
#include <cuda.h>
#include <cuda_bf16.h>
#include <stdint.h>

namespace {

constexpr int S_ = 2048, D_ = 576, F_ = 4608, Q3_ = 1728;
constexpr int NSTAGE = 6, STAGE_BYTES = 12288;
constexpr int SM_A = 0, SM_B = 147456, SM_BIAS = SM_B + NSTAGE * STAGE_BYTES, SM_BAR = SM_BIAS + 2304;
constexpr int SMEM_BYTES = SM_BAR + 320;
constexpr int NTHREADS = 384;
constexpr int NCTAS = 132;

__device__ uint4 g_qkvf[(128 * 108 + 1) * 32];
__device__ __align__(1024) __nv_bfloat16 g_o[S_ * D_];
__device__ uint4 g_kvp[32 * 32 * 5 * 32];
__device__ uint4 g_kvt[32 * 3 * 32];
__device__ uint4 g_part[128 * 8 * 36 * 32];
__device__ uint4 g_s2[128 * 12 * 32];
__device__ uint4 g_g[128 * 24 * 32];
__device__ uint4 g_hsp[128 * 12 * 256];
__device__ uint32_t g_f_qkv[16 * 8];
__device__ uint32_t g_f_kvp[32];
__device__ uint32_t g_f_kvt[32];
__device__ uint32_t g_f_o[16];
__device__ uint32_t g_f_rb[128 * 8];
__device__ uint32_t g_epoch[NCTAS];

#define STAMP(i)
#define STAMPW(w, i)
__device__ __forceinline__ uint32_t smem_u32(const void* p) { return (uint32_t)__cvta_generic_to_shared(p); }
__device__ __forceinline__ void mbar_init(uint32_t a, int c) { asm volatile("mbarrier.init.shared::cta.b64 [%0], %1;" ::"r"(a), "r"(c)); }
__device__ __forceinline__ void mbar_expect(uint32_t a, uint32_t b) { asm volatile("mbarrier.arrive.expect_tx.shared::cta.b64 _, [%0], %1;" ::"r"(a), "r"(b) : "memory"); }
__device__ __forceinline__ void mbar_arrive(uint32_t a) { asm volatile("mbarrier.arrive.shared::cta.b64 _, [%0];" ::"r"(a) : "memory"); }
__device__ __forceinline__ void mbar_arrive_cl(uint32_t a) { asm volatile("mbarrier.arrive.shared::cluster.b64 _, [%0];" ::"r"(a) : "memory"); }
__device__ __forceinline__ uint32_t mapa(uint32_t a, uint32_t cta) { uint32_t r; asm volatile("mapa.shared::cluster.u32 %0, %1, %2;" : "=r"(r) : "r"(a), "r"(cta)); return r; }
__device__ __forceinline__ void mbar_wait(uint32_t a, uint32_t ph) {
  uint32_t ok; int it = 0;
  do {
    asm volatile("{.reg .pred p; mbarrier.try_wait.parity.shared::cta.b64 p, [%1], %2; selp.u32 %0,1,0,p;}" : "=r"(ok) : "r"(a), "r"(ph) : "memory");
  } while (!ok && ++it < (1 << 18));
}
__device__ __forceinline__ void tma2d(uint32_t dst, const CUtensorMap* m, int c0, int c1, uint32_t bar) {
  asm volatile("cp.async.bulk.tensor.2d.shared::cluster.global.mbarrier::complete_tx::bytes [%0], [%1, {%3,%4}], [%2];" ::"r"(dst), "l"(m), "r"(bar), "r"(c0), "r"(c1) : "memory");
}
__device__ __forceinline__ void tma2d_mc(uint32_t dst, const CUtensorMap* m, int c0, int c1, uint32_t bar) {
  asm volatile("cp.async.bulk.tensor.2d.shared::cluster.global.mbarrier::complete_tx::bytes.multicast::cluster [%0], [%1, {%3,%4}], [%2], %5;" ::"r"(dst), "l"(m), "r"(bar), "r"(c0), "r"(c1), "h"((uint16_t)3) : "memory");
}
__device__ __forceinline__ void cluster_arrive() { asm volatile("barrier.cluster.arrive.release.aligned;" ::: "memory"); }
__device__ __forceinline__ void cluster_arrive_relaxed() { asm volatile("barrier.cluster.arrive.relaxed.aligned;" ::: "memory"); }
__device__ __forceinline__ void cluster_wait() { asm volatile("barrier.cluster.wait.acquire.aligned;" ::: "memory"); }
__device__ __forceinline__ void wg_fence() { asm volatile("wgmma.fence.sync.aligned;" ::: "memory"); }
__device__ __forceinline__ void wg_commit() { asm volatile("wgmma.commit_group.sync.aligned;" ::: "memory"); }
template <int n> __device__ __forceinline__ void wg_wait() { asm volatile("wgmma.wait_group.sync.aligned %0;" ::"n"(n) : "memory"); }
__device__ __forceinline__ uint32_t ld_acquire(const uint32_t* p) { uint32_t v; asm volatile("ld.acquire.gpu.global.u32 %0, [%1];" : "=r"(v) : "l"(p) : "memory"); return v; }
__device__ __forceinline__ void flag_wait(const uint32_t* p, uint32_t target) {
  int it = 0;
  while ((int)(ld_acquire(p) - target) < 0 && ++it < (1 << 21)) __nanosleep(40);
}
__device__ __forceinline__ void flag_signal_warp(uint32_t* p) {
  __syncwarp();
  if ((threadIdx.x & 31) == 0) asm volatile("red.release.gpu.global.add.u32 [%0], 1;" ::"l"(p) : "memory");
}
__device__ __forceinline__ void hint_signal(uint32_t* p) {
  if ((threadIdx.x & 31) == 0) asm volatile("red.relaxed.gpu.global.add.u32 [%0], 1;" ::"l"(p) : "memory");
}
__device__ __forceinline__ void hint_wait(const uint32_t* p, uint32_t target) {
  int it = 0; uint32_t v;
  do { asm volatile("ld.relaxed.gpu.global.u32 %0, [%1];" : "=r"(v) : "l"(p) : "memory"); if ((int)(v - target) >= 0) break; __nanosleep(32); } while (++it < (1 << 21));
}
__device__ __forceinline__ void st_ll(uint4* p, uint4 v, uint32_t par) {
  asm volatile("{.reg .b128 r; .reg .b64 a, b; mov.b64 a, {%1,%2}; mov.b64 b, {%3,%4}; mov.b128 r, {a, b}; st.relaxed.gpu.global.b128 [%0], r;}"
               ::"l"(p), "r"((v.x & ~1u) | par), "r"(v.y), "r"(v.z), "r"(v.w) : "memory");
}
__device__ __forceinline__ uint4 ld_ll(const uint4* p) {
  uint4 v;
  asm volatile("{.reg .b128 r; .reg .b64 a, b; ld.relaxed.gpu.global.b128 r, [%4]; mov.b128 {a, b}, r; mov.b64 {%0,%1}, a; mov.b64 {%2,%3}, b;}"
               : "=r"(v.x), "=r"(v.y), "=r"(v.z), "=r"(v.w) : "l"(p) : "memory");
  return v;
}
__device__ __forceinline__ uint32_t pack_bf16(float lo, float hi) { uint32_t r; asm("cvt.rn.bf16x2.f32 %0, %1, %2;" : "=r"(r) : "f"(hi), "f"(lo)); return r; }
__device__ __forceinline__ float bf_lo(uint32_t v) { return __uint_as_float(v << 16); }
__device__ __forceinline__ float bf_hi(uint32_t v) { return __uint_as_float(v & 0xffff0000u); }
__device__ __forceinline__ float tanh_fast(float x) { float r; asm("tanh.approx.f32 %0, %1;" : "=f"(r) : "f"(x)); return r; }
__device__ __forceinline__ uint32_t movmat(uint32_t a) { uint32_t d; asm volatile("movmatrix.sync.aligned.m8n8.trans.b16 %0, %1;" : "=r"(d) : "r"(a)); return d; }
__device__ __forceinline__ void mma16816(float* c, uint32_t a0, uint32_t a1, uint32_t a2, uint32_t a3, uint32_t b0, uint32_t b1) {
  asm volatile("mma.sync.aligned.m16n8k16.row.col.f32.bf16.bf16.f32 {%0,%1,%2,%3}, {%4,%5,%6,%7}, {%8,%9}, {%0,%1,%2,%3};"
               : "+f"(c[0]), "+f"(c[1]), "+f"(c[2]), "+f"(c[3]) : "r"(a0), "r"(a1), "r"(a2), "r"(a3), "r"(b0), "r"(b1));
}
__device__ __forceinline__ uint32_t ldcg32(const void* p) { uint32_t v; asm volatile("ld.global.cg.u32 %0, [%1];" : "=r"(v) : "l"(p) : "memory"); return v; }
__device__ __forceinline__ uint4 ldcg128(const void* p) { uint4 v; asm volatile("ld.global.cg.v4.u32 {%0,%1,%2,%3}, [%4];" : "=r"(v.x), "=r"(v.y), "=r"(v.z), "=r"(v.w) : "l"(p) : "memory"); return v; }
__device__ __forceinline__ uint2 ldcg64(const void* p) { uint2 v; asm volatile("ld.global.cg.v2.u32 {%0,%1}, [%2];" : "=r"(v.x), "=r"(v.y) : "l"(p) : "memory"); return v; }

template <int N> __device__ __forceinline__ void wgmma_ss(float* d, uint64_t da, uint64_t db, int sc);
template <int N> __device__ __forceinline__ void wgmma_rs(float* d, const uint32_t* a, uint64_t db, int sc);
template <> __device__ __forceinline__ void wgmma_ss<96>(float* d, uint64_t da, uint64_t db, int sc) {
  asm volatile("{.reg .pred p; setp.ne.b32 p, %50, 0; wgmma.mma_async.sync.aligned.m64n96k16.f32.bf16.bf16 {%0, %1, %2, %3, %4, %5, %6, %7, %8, %9, %10, %11, %12, %13, %14, %15, %16, %17, %18, %19, %20, %21, %22, %23, %24, %25, %26, %27, %28, %29, %30, %31, %32, %33, %34, %35, %36, %37, %38, %39, %40, %41, %42, %43, %44, %45, %46, %47}, %48, %49, p, 1, 1, 0, 1;}"
   : "+f"(d[0]), "+f"(d[1]), "+f"(d[2]), "+f"(d[3]), "+f"(d[4]), "+f"(d[5]), "+f"(d[6]), "+f"(d[7]), "+f"(d[8]), "+f"(d[9]), "+f"(d[10]), "+f"(d[11]), "+f"(d[12]), "+f"(d[13]), "+f"(d[14]), "+f"(d[15]), "+f"(d[16]), "+f"(d[17]), "+f"(d[18]), "+f"(d[19]), "+f"(d[20]), "+f"(d[21]), "+f"(d[22]), "+f"(d[23]), "+f"(d[24]), "+f"(d[25]), "+f"(d[26]), "+f"(d[27]), "+f"(d[28]), "+f"(d[29]), "+f"(d[30]), "+f"(d[31]), "+f"(d[32]), "+f"(d[33]), "+f"(d[34]), "+f"(d[35]), "+f"(d[36]), "+f"(d[37]), "+f"(d[38]), "+f"(d[39]), "+f"(d[40]), "+f"(d[41]), "+f"(d[42]), "+f"(d[43]), "+f"(d[44]), "+f"(d[45]), "+f"(d[46]), "+f"(d[47]) : "l"(da), "l"(db), "r"(sc));
}
template <> __device__ __forceinline__ void wgmma_ss<192>(float* d, uint64_t da, uint64_t db, int sc) {
  asm volatile("{.reg .pred p; setp.ne.b32 p, %98, 0; wgmma.mma_async.sync.aligned.m64n192k16.f32.bf16.bf16 {%0, %1, %2, %3, %4, %5, %6, %7, %8, %9, %10, %11, %12, %13, %14, %15, %16, %17, %18, %19, %20, %21, %22, %23, %24, %25, %26, %27, %28, %29, %30, %31, %32, %33, %34, %35, %36, %37, %38, %39, %40, %41, %42, %43, %44, %45, %46, %47, %48, %49, %50, %51, %52, %53, %54, %55, %56, %57, %58, %59, %60, %61, %62, %63, %64, %65, %66, %67, %68, %69, %70, %71, %72, %73, %74, %75, %76, %77, %78, %79, %80, %81, %82, %83, %84, %85, %86, %87, %88, %89, %90, %91, %92, %93, %94, %95}, %96, %97, p, 1, 1, 0, 1;}"
   : "+f"(d[0]), "+f"(d[1]), "+f"(d[2]), "+f"(d[3]), "+f"(d[4]), "+f"(d[5]), "+f"(d[6]), "+f"(d[7]), "+f"(d[8]), "+f"(d[9]), "+f"(d[10]), "+f"(d[11]), "+f"(d[12]), "+f"(d[13]), "+f"(d[14]), "+f"(d[15]), "+f"(d[16]), "+f"(d[17]), "+f"(d[18]), "+f"(d[19]), "+f"(d[20]), "+f"(d[21]), "+f"(d[22]), "+f"(d[23]), "+f"(d[24]), "+f"(d[25]), "+f"(d[26]), "+f"(d[27]), "+f"(d[28]), "+f"(d[29]), "+f"(d[30]), "+f"(d[31]), "+f"(d[32]), "+f"(d[33]), "+f"(d[34]), "+f"(d[35]), "+f"(d[36]), "+f"(d[37]), "+f"(d[38]), "+f"(d[39]), "+f"(d[40]), "+f"(d[41]), "+f"(d[42]), "+f"(d[43]), "+f"(d[44]), "+f"(d[45]), "+f"(d[46]), "+f"(d[47]), "+f"(d[48]), "+f"(d[49]), "+f"(d[50]), "+f"(d[51]), "+f"(d[52]), "+f"(d[53]), "+f"(d[54]), "+f"(d[55]), "+f"(d[56]), "+f"(d[57]), "+f"(d[58]), "+f"(d[59]), "+f"(d[60]), "+f"(d[61]), "+f"(d[62]), "+f"(d[63]), "+f"(d[64]), "+f"(d[65]), "+f"(d[66]), "+f"(d[67]), "+f"(d[68]), "+f"(d[69]), "+f"(d[70]), "+f"(d[71]), "+f"(d[72]), "+f"(d[73]), "+f"(d[74]), "+f"(d[75]), "+f"(d[76]), "+f"(d[77]), "+f"(d[78]), "+f"(d[79]), "+f"(d[80]), "+f"(d[81]), "+f"(d[82]), "+f"(d[83]), "+f"(d[84]), "+f"(d[85]), "+f"(d[86]), "+f"(d[87]), "+f"(d[88]), "+f"(d[89]), "+f"(d[90]), "+f"(d[91]), "+f"(d[92]), "+f"(d[93]), "+f"(d[94]), "+f"(d[95]) : "l"(da), "l"(db), "r"(sc));
}

__device__ __forceinline__ uint64_t desc64(uint32_t lo, uint32_t hi) { uint64_t d; asm("mov.b64 %0, {%1, %2};" : "=l"(d) : "r"(lo), "r"(hi)); return d; }
constexpr uint32_t DESC_HI = (1024u >> 4) | (1u << 30);
template <int n> __device__ __forceinline__ void fence_regs(float* a) {
#pragma unroll
  for (int i = 0; i < n; i++) asm volatile("" : "+f"(a[i])::"memory");
}

struct Ctx {
  uint32_t full;
  uint32_t emb;
  uint32_t stage, phase, prev;
  uint32_t dB, dA;
  uint32_t xfree;
  uint32_t owait;
  __device__ __forceinline__ void release_prev() { if (emb != 0 && prev != ~0u) mbar_arrive_cl(emb + prev); }
};

template <int N>
__device__ __forceinline__ void stage_ss(float* acc, Ctx& c, int s, bool first) {
  if (c.owait != 0 && (s & 1) == 0) mbar_wait(c.owait + 4 * s, 0);
  mbar_wait(c.full + 8 * c.stage, c.phase);
  wg_fence();
  const uint32_t db = c.dB + c.stage * (STAGE_BYTES >> 4);
  const uint32_t da = c.dA + (s >> 1) * 1024 + (s & 1) * 4;
  wgmma_ss<N>(acc, desc64(da, DESC_HI), desc64(db, DESC_HI), first ? 0 : 1);
  wgmma_ss<N>(acc, desc64(da + 2, DESC_HI), desc64(db + 128, DESC_HI), 1);
  wg_commit();
}
__device__ __forceinline__ void retire(Ctx& c, int s) {
  wg_wait<1>();
  c.release_prev();
  if (c.xfree != 0 && (s & 1) == 0) mbar_arrive(c.xfree + 4 * s);
  c.prev = 8 * c.stage;
  if (++c.stage == NSTAGE) { c.stage = 0; c.phase ^= 1; }
}

__device__ __forceinline__ float gelu2(float x) {
  float u = x * fmaf(x * x, 0.0356774081f, 0.7978845608f);
  return fmaf(x, tanh_fast(u), x);
}
__device__ __forceinline__ uint4 gelu_group(const float* a, const float* bias  ) {
  float2 b0 = *reinterpret_cast<const float2*>(bias);
  float2 b1 = *reinterpret_cast<const float2*>(bias + 8);
  uint4 h;
  h.x = pack_bf16(gelu2(a[0] + b0.x), gelu2(a[1] + b0.y));
  h.y = pack_bf16(gelu2(a[2] + b0.x), gelu2(a[3] + b0.y));
  h.z = pack_bf16(gelu2(a[4] + b1.x), gelu2(a[5] + b1.y));
  h.w = pack_bf16(gelu2(a[6] + b1.x), gelu2(a[7] + b1.y));
  return h;
}
__device__ __forceinline__ void stsm4(uint32_t addr, uint4 r) {
  asm volatile("stmatrix.sync.aligned.m8n8.x4.shared.b16 [%0], {%1,%2,%3,%4};" ::"r"(addr), "r"(r.x), "r"(r.y), "r"(r.z), "r"(r.w) : "memory");
}
__device__ __forceinline__ float ex2f(float x) { float r; asm("ex2.approx.ftz.f32 %0, %1;" : "=f"(r) : "f"(x)); return r; }
__device__ __forceinline__ float phi(float t) { return (t > 0.f ? t + 1.f : ex2f(t * 1.4426950408889634f)) + 1e-6f; }
__device__ __forceinline__ uint32_t phi2(uint32_t w) { return pack_bf16(phi(bf_lo(w)), phi(bf_hi(w))); }
template <int q0, int q1>
__device__ __forceinline__ void part_groups(const float* a, uint4* p, uint32_t keep, uint32_t par) {
#pragma unroll
  for (int q = q0; q < q1; q++) {
    const uint32_t x = (pack_bf16(a[8 * q], a[8 * q + 1]) & keep) | par;
    asm volatile("{.reg .b128 r; .reg .b64 a, b; mov.b64 a, {%1,%2}; mov.b64 b, {%3,%4}; mov.b128 r, {a, b}; st.relaxed.gpu.global.b128 [%0], r;}"
                 ::"l"(p + q * 32), "r"(x), "r"(pack_bf16(a[8 * q + 2], a[8 * q + 3])), "r"(pack_bf16(a[8 * q + 4], a[8 * q + 5])), "r"(pack_bf16(a[8 * q + 6], a[8 * q + 7])) : "memory");
  }
}
__device__ __forceinline__ float silu(float y) { return __fdividef(y, 1.f + ex2f(y * -1.4426950408889634f)); }
__device__ __forceinline__ void gate_vec(const uint4* p, uint32_t b0, uint32_t b1, float* gt) {
#pragma unroll
  for (int q = 0; q < 4; q++) {
    float lo = 0.f, hi = 0.f;
#pragma unroll
    for (int i = 0; i < 8; i++) { uint32_t w = reinterpret_cast<const uint32_t*>(&p[i])[q]; lo += bf_lo(w); hi += bf_hi(w); }
    const uint32_t bb = q < 2 ? b0 : b1;
    gt[2 * q] = silu(fmaf(lo, 0.5f, bf_lo(bb)));
    gt[2 * q + 1] = silu(fmaf(hi, 0.5f, bf_hi(bb)));
  }
}

struct Params {
  CUtensorMap tm_wqkv, tm_w1, tm_w2, tm_wo, tm_o, tm_x;
  const __nv_bfloat16 *x, *b1, *b2, *wqkv, *w1, *w2, *wo;
  __nv_bfloat16* out;
};

__global__ void __cluster_dims__(2, 1, 1) __launch_bounds__(NTHREADS, 1) fused_kernel(const __grid_constant__ Params P) {
  extern __shared__ __align__(1024) uint8_t smem[];
  const uint32_t sbase = smem_u32(smem);
  const int tid = threadIdx.x, lane = tid & 31;
  const int warp = __shfl_sync(0xffffffffu, tid >> 5, 0);
  const int g = lane >> 2, t = lane & 3;
  const uint32_t ep = g_epoch[blockIdx.x] + 1;
  const uint32_t par = ep & 1;
  STAMPW(0, 0);

  if (blockIdx.x >= 128) {
    const int a = blockIdx.x - 128;
    if (warp < 8) {
      const int head = a * 8 + warp;
      if (lane == 0) hint_wait(&g_f_kvp[head], 32 * ep);
      __syncwarp();
      STAMPW(0, 1);
      float sm[20];
#pragma unroll
      for (int j = 0; j < 20; j++) sm[j] = 0.f;
#pragma unroll 1
      for (int m0 = 0; m0 < 32; m0 += 4) {
        uint4 v[20];
        int tries = 0;
        uint32_t bad;
        do {
          bad = 0;
#pragma unroll
          for (int j = 0; j < 20; j++) v[j] = ld_ll(&g_kvp[((head * 32 + m0) * 5 + j) * 32 + lane]);
#pragma unroll
          for (int j = 0; j < 20; j++) bad |= v[j].x ^ par;
        } while (__any_sync(0xffffffffu, bad & 1) && ++tries < (1 << 20));
#pragma unroll
        for (int j = 0; j < 20; j++) {
          sm[(j % 5) * 4 + 0] += __uint_as_float(v[j].x); sm[(j % 5) * 4 + 1] += __uint_as_float(v[j].y); sm[(j % 5) * 4 + 2] += __uint_as_float(v[j].z); sm[(j % 5) * 4 + 3] += __uint_as_float(v[j].w);
        }
      }
      st_ll(&g_kvt[(head * 3 + 0) * 32 + lane], make_uint4(0u, pack_bf16(sm[0], sm[1]), pack_bf16(sm[4], sm[5]), pack_bf16(sm[8], sm[9])), par);
      st_ll(&g_kvt[(head * 3 + 1) * 32 + lane], make_uint4(0u, pack_bf16(sm[2], sm[3]), pack_bf16(sm[6], sm[7]), pack_bf16(sm[10], sm[11])), par);
      st_ll(&g_kvt[(head * 3 + 2) * 32 + lane], make_uint4(0u, pack_bf16(sm[12], sm[13]), pack_bf16(sm[14], sm[15]), pack_bf16(sm[16], sm[17])), par);
      hint_signal(&g_f_kvt[head]);
      STAMPW(0, 2);
    } else if (lane == 0) {
      const int id = a * 4 + (warp - 8);
      constexpr uint32_t CH = 9216 * 2;
#pragma unroll 1
      for (int i = id; i < 612; i += 16) {
        const char* p = i < 288 ? (const char*)P.w1 + (size_t)i * CH : (i < 576 ? (const char*)P.w2 + (size_t)(i - 288) * CH : (const char*)P.wo + (size_t)(i - 576) * CH);
        asm volatile("cp.async.bulk.prefetch.L2.global [%0], %1;" ::"l"(p), "r"(CH) : "memory");
      }
    }
    __syncthreads();
    if (tid == 0) g_epoch[blockIdx.x] = ep;
    return;
  }

  const int cl = blockIdx.x >> 1, rank = blockIdx.x & 1;
  const int f = cl & 7, m = (cl >> 3) * 2 + rank;
  const int srole = f >= 6 ? 1 : 0;
  const uint32_t bar_full = sbase + SM_BAR, bar_empty = bar_full + 8 * NSTAGE, bar_xfree = bar_empty + 8 * NSTAGE, bar_ofull = bar_xfree + 72, bar_x = bar_ofull + 72, bar_q = bar_x + 32;

  if (tid == 256) {
#pragma unroll 1
    for (int i = 0; i < 4; i++) mbar_init(bar_x + 8 * i, 1);
    asm volatile("fence.mbarrier_init.release.cluster;" ::: "memory");
#pragma unroll 1
    for (int i = 0; i < 4; i++) {
      mbar_expect(bar_x + 8 * i, 36864);
#pragma unroll 1
      for (int kb = 0; kb < 9; kb++) tma2d(sbase + SM_A + kb * 16384 + i * 4096, &P.tm_x, kb * 64, m * 128 + i * 32, bar_x + 8 * i);
    }
  } else if (tid == 0) {
#pragma unroll 1
    for (int i = 0; i < NSTAGE; i++) { mbar_init(bar_full + 8 * i, 1); mbar_init(bar_empty + 8 * i, 4); }
#pragma unroll 1
    for (int i = 0; i < 9; i++) { mbar_init(bar_xfree + 8 * i, 2); mbar_init(bar_ofull + 8 * i, 1); }
    mbar_init(bar_q, 16);
    asm volatile("fence.mbarrier_init.release.cluster;" ::: "memory");
  }
  __syncwarp();
  cluster_arrive_relaxed();

  if (warp >= 8) {
    asm volatile("setmaxnreg.dec.sync.aligned.u32 56;");
    cluster_wait();
    if (warp == 8) {
      if (lane == 0) {
        uint32_t stage = 0, phase = 1;
        const uint32_t sb = sbase + SM_B;
#pragma unroll 1
        for (int tl = 2 * srole; tl < 8 + 2 * srole; tl++) {
          const CUtensorMap* map = tl < 2 ? &P.tm_wqkv : (tl < 5 ? &P.tm_w1 : (tl < 8 ? &P.tm_w2 : &P.tm_wo));
          const int col = tl < 2 ? 288 * f + 96 * tl : (tl < 5 ? 576 * f + 192 * (tl - 2) : (tl < 8 ? 192 * (tl - 5) : (tl == 8 ? 384 + 96 * (f - 6) : 192 * (f - 6))));
          const bool perm = tl >= 5 && tl < 8;
          const bool three = (tl & 7) != 0;
#pragma unroll 1
          for (int st = 0; st < 18; st++) {
            int row = st * 32;
            if (perm) row += 576 * f + ((st < 6) ? 192 : (st < 12 ? -192 : 0));
            mbar_wait(bar_empty + 8 * stage, phase);
            mbar_expect(bar_full + 8 * stage, three ? 12288 : 8192);
            const uint32_t dst = sb + stage * STAGE_BYTES;
            if (((st ^ rank) & 1) == 0) {
              tma2d_mc(dst, map, col, row, bar_full + 8 * stage);
              if (three) tma2d_mc(dst + 8192, map, col + 128, row, bar_full + 8 * stage);
            } else {
              tma2d_mc(dst + 4096, map, col + 64, row, bar_full + 8 * stage);
            }
            if (++stage == NSTAGE) { stage = 0; phase ^= 1; }
          }
        }
      }
      __syncwarp();
    } else {
      const int aw = warp - 9;
      const int hi = f >> 2;
      const uint32_t* qf = reinterpret_cast<const uint32_t*>(g_qkvf) + (size_t)m * 8 * 108 * 128 + g * 16;
      auto coloff = [&](int c) { return (c >> 4) * 128 + ((c & 7) >> 1) * 4 + ((c >> 3) & 1) * 2; };
      if (aw == 2 && !srole && lane == 0) {
        mbar_wait(bar_q, 0);
        asm volatile("red.release.gpu.global.add.u32 [%0], 1;" ::"l"(&g_f_qkv[m * 8 + f]) : "memory");
      }
      if (lane < 2) flag_wait(&g_f_qkv[m * 8 + 2 + 2 * lane + hi], ep);
      __syncwarp();
      STAMPW(9, 20);
#pragma unroll 1
      for (int u = aw; u < 8; u += 3) {
        const int head = 4 * f + (u >> 1), half = u & 1;
        int off[3];
#pragma unroll
        for (int b = 0; b < 3; b++) off[b] = coloff(576 + head * 18 + 8 * b + 2 * t);
        float c0[3][4], c1[3][4];
#pragma unroll
        for (int j = 0; j < 3; j++) { c0[j][0] = c0[j][1] = c0[j][2] = c0[j][3] = 0.f; c1[j][0] = c1[j][1] = c1[j][2] = c1[j][3] = 0.f; }
#pragma unroll 1
        for (int k2 = 0; k2 < 2; k2++) {
          uint2 kf[2][3], vf[2][3];
#pragma unroll
          for (int ks = 0; ks < 2; ks++) {
            const uint32_t* p = qf + (half * 4 + k2 * 2 + ks) * 108 * 128;
#pragma unroll
            for (int b = 0; b < 3; b++) { kf[ks][b] = ldcg64(p + off[b]); vf[ks][b] = ldcg64(p + off[b] + 36 * 128); }
          }
#pragma unroll
          for (int ks = 0; ks < 2; ks++) {
#pragma unroll
            for (int b = 0; b < 3; b++) { kf[ks][b].x = phi2(kf[ks][b].x); kf[ks][b].y = phi2(kf[ks][b].y); }
            if (t != 0) { kf[ks][2].x = kf[ks][2].y = 0u; vf[ks][2].x = vf[ks][2].y = (t == 1 ? 0x00003f80u : 0u); }
#pragma unroll
            for (int b = 0; b < 3; b++) { kf[ks][b].x = movmat(kf[ks][b].x); kf[ks][b].y = movmat(kf[ks][b].y); vf[ks][b].x = movmat(vf[ks][b].x); vf[ks][b].y = movmat(vf[ks][b].y); }
#pragma unroll
            for (int j = 0; j < 3; j++) {
              mma16816(c0[j], vf[ks][0].x, vf[ks][1].x, vf[ks][0].y, vf[ks][1].y, kf[ks][j].x, kf[ks][j].y);
              mma16816(c1[j], vf[ks][2].x, 0u, vf[ks][2].y, 0u, kf[ks][j].x, kf[ks][j].y);
            }
          }
        }
        uint4* dst = &g_kvp[((head * 32 + m * 2 + half) * 5) * 32 + lane];
#pragma unroll
        for (int j = 0; j < 3; j++) st_ll(dst + j * 32, make_uint4(__float_as_uint(c0[j][0]), __float_as_uint(c0[j][1]), __float_as_uint(c0[j][2]), __float_as_uint(c0[j][3])), par);
        st_ll(dst + 96, make_uint4(__float_as_uint(c1[0][0]), __float_as_uint(c1[0][1]), __float_as_uint(c1[1][0]), __float_as_uint(c1[1][1])), par);
        st_ll(dst + 128, make_uint4(__float_as_uint(c1[2][0]), __float_as_uint(c1[2][1]), 0u, 0u), par);
        hint_signal(&g_f_kvp[head]);
      }
      STAMPW(9, 21);
      if (lane < 5) flag_wait(lane < 4 ? &g_f_kvt[4 * f + lane] : &g_f_qkv[m * 8 + hi], ep);
      __syncwarp();
      STAMPW(9, 22);
#pragma unroll 1
      for (int hh = 0; hh < 4; hh++) {
        const int head = 4 * f + hh;
        const int rb0 = (aw + hh) % 3;
        uint4 bf[3];
        uint2 qa[3][3];
#pragma unroll
        for (int b = 0; b < 3; b++) {
          const int o = coloff(head * 18 + 8 * b + 2 * t);
#pragma unroll
          for (int j = 0; j < 3; j++) qa[j][b] = ldcg64(qf + min(rb0 + 3 * j, 7) * 108 * 128 + o);
        }
        int tries = 0;
        do {
#pragma unroll
          for (int i = 0; i < 3; i++) bf[i] = ld_ll(&g_kvt[(head * 3 + i) * 32 + lane]);
        } while (__any_sync(0xffffffffu, ((bf[0].x ^ par) | (bf[1].x ^ par) | (bf[2].x ^ par)) & 1) && ++tries < (1 << 20));
#pragma unroll
        for (int j = 0; j < 3; j++) {
          const int rb = rb0 + 3 * j;
          if (rb < 8) {
#pragma unroll
            for (int b = 0; b < 3; b++) { qa[j][b].x = phi2(qa[j][b].x); qa[j][b].y = phi2(qa[j][b].y); }
            if (t != 0) qa[j][2].x = qa[j][2].y = 0u;
            float c[3][4];
#pragma unroll
            for (int e = 0; e < 3; e++) {
              c[e][0] = c[e][1] = c[e][2] = c[e][3] = 0.f;
              mma16816(c[e], qa[j][0].x, qa[j][0].y, qa[j][1].x, qa[j][1].y, bf[e].y, bf[e].z);
              mma16816(c[e], qa[j][2].x, qa[j][2].y, 0u, 0u, bf[e].w, 0u);
            }
            const float r0 = __fdividef(1.f, __shfl_sync(0xffffffffu, c[2][0], (lane & ~3) | 1) + 1e-6f);
            const float r1 = __fdividef(1.f, __shfl_sync(0xffffffffu, c[2][2], (lane & ~3) | 1) + 1e-6f);
            __nv_bfloat16* po = g_o + (size_t)(m * 128 + rb * 16 + g) * D_ + head * 18 + 2 * t;
            *reinterpret_cast<uint32_t*>(po) = pack_bf16(c[0][0] * r0, c[0][1] * r0);
            *reinterpret_cast<uint32_t*>(po + 8) = pack_bf16(c[1][0] * r0, c[1][1] * r0);
            *reinterpret_cast<uint32_t*>(po + 8 * D_) = pack_bf16(c[0][2] * r1, c[0][3] * r1);
            *reinterpret_cast<uint32_t*>(po + 8 * D_ + 8) = pack_bf16(c[1][2] * r1, c[1][3] * r1);
            if (t == 0) {
              *reinterpret_cast<uint32_t*>(po + 16) = pack_bf16(c[2][0] * r0, c[2][1] * r0);
              *reinterpret_cast<uint32_t*>(po + 8 * D_ + 16) = pack_bf16(c[2][2] * r1, c[2][3] * r1);
            }
          }
        }
      }
      asm volatile("fence.proxy.async.global;" ::: "memory");
      flag_signal_warp(&g_f_o[m]);
      STAMPW(9, 23);
      if (srole && aw == 2) {
        if (lane == 0) {
          flag_wait(&g_f_o[m], 24 * ep);
          asm volatile("fence.proxy.async.global;" ::: "memory");
#pragma unroll 1
          for (int kb = 0; kb < 9; kb++) {
            mbar_wait(bar_xfree + 8 * kb, 0);
            mbar_expect(bar_ofull + 8 * kb, 16384);
            tma2d(sbase + SM_A + kb * 16384, &P.tm_o, kb * 64, m * 128, bar_ofull + 8 * kb);
          }
        }
        __syncwarp();
      }
      const int rbg = m * 8 + f;
#pragma unroll 1
      for (int ch = 0; ch < 2; ch++) {
        if (lane == 0) hint_wait(&g_f_rb[rbg * 8 + ch], 8 * ep);
        __syncwarp();
        STAMPW(9, 24 + 2 * ch);
#pragma unroll 1
        for (int v = ch * 12 + aw * 4; v < ch * 12 + aw * 4 + 4; v++) {
          uint4 p[8];
          int tries = 0;
          uint32_t bad;
          do {
            bad = 0;
#pragma unroll
            for (int i = 0; i < 8; i++) p[i] = ld_ll(&g_part[((rbg * 8 + i) * 36 + v) * 32 + lane]);
#pragma unroll
            for (int i = 0; i < 8; i++) bad |= p[i].x ^ par;
          } while (__any_sync(0xffffffffu, bad & 1) && ++tries < (1 << 20));
          const uint32_t b0 = __ldg(reinterpret_cast<const uint32_t*>(P.b2 + 16 * v + 2 * t)), b1 = __ldg(reinterpret_cast<const uint32_t*>(P.b2 + 16 * v + 8 + 2 * t));
          float gt[8];
          gate_vec(p, b0, b1, gt);
          st_ll(&g_g[(rbg * 24 + v) * 32 + lane], make_uint4(pack_bf16(gt[0], gt[1]), pack_bf16(gt[2], gt[3]), pack_bf16(gt[4], gt[5]), pack_bf16(gt[6], gt[7])), par);
        }
        hint_signal(&g_f_rb[rbg * 8 + 4 + ch]);
        STAMPW(9, 25 + 2 * ch);
      }
    }
    cluster_arrive_relaxed();
    cluster_wait();
  } else {
    asm volatile("setmaxnreg.inc.sync.aligned.u32 224;");
    const int wg = warp >> 2;
    float* sbias = reinterpret_cast<float*>(smem + SM_BIAS);
    for (int i = tid; i < 576; i += 256) sbias[i] = __bfloat162float(P.b1[576 * f + i]);
    cluster_wait();
#pragma unroll 1
    for (int it = 0; it < 4; it++) {
      mbar_wait(bar_x + 8 * it, 0);
      STAMPW(0, 28 + it);
      uint8_t* rowp = smem + SM_A + (it * 32 + warp * 4 + (lane >> 3)) * 128 + (lane & 7) * 16;
      float v[72];
      float sum = 0.f;
#pragma unroll
      for (int kb = 0; kb < 9; kb++) {
        const uint4 w = *reinterpret_cast<const uint4*>(rowp + kb * 16384);
        v[8 * kb + 0] = bf_lo(w.x); v[8 * kb + 1] = bf_hi(w.x); v[8 * kb + 2] = bf_lo(w.y); v[8 * kb + 3] = bf_hi(w.y);
        v[8 * kb + 4] = bf_lo(w.z); v[8 * kb + 5] = bf_hi(w.z); v[8 * kb + 6] = bf_lo(w.w); v[8 * kb + 7] = bf_hi(w.w);
        sum += ((v[8 * kb] + v[8 * kb + 1]) + (v[8 * kb + 2] + v[8 * kb + 3])) + ((v[8 * kb + 4] + v[8 * kb + 5]) + (v[8 * kb + 6] + v[8 * kb + 7]));
      }
      sum += __shfl_xor_sync(0xffffffffu, sum, 1); sum += __shfl_xor_sync(0xffffffffu, sum, 2); sum += __shfl_xor_sync(0xffffffffu, sum, 4);
      const float mean = sum * (1.f / 576.f);
      float sq0 = 0.f, sq1 = 0.f;
#pragma unroll
      for (int i = 0; i < 72; i += 2) { v[i] -= mean; v[i + 1] -= mean; sq0 = fmaf(v[i], v[i], sq0); sq1 = fmaf(v[i + 1], v[i + 1], sq1); }
      float sq = sq0 + sq1;
      sq += __shfl_xor_sync(0xffffffffu, sq, 1); sq += __shfl_xor_sync(0xffffffffu, sq, 2); sq += __shfl_xor_sync(0xffffffffu, sq, 4);
      const float rstd = rsqrtf(sq * (1.f / 576.f) + 1e-5f);
#pragma unroll
      for (int kb = 0; kb < 9; kb++)
        *reinterpret_cast<uint4*>(rowp + kb * 16384) = make_uint4(pack_bf16(v[8 * kb] * rstd, v[8 * kb + 1] * rstd), pack_bf16(v[8 * kb + 2] * rstd, v[8 * kb + 3] * rstd),
                                                                   pack_bf16(v[8 * kb + 4] * rstd, v[8 * kb + 5] * rstd), pack_bf16(v[8 * kb + 6] * rstd, v[8 * kb + 7] * rstd));
    }
    asm volatile("fence.proxy.async.shared::cta;" ::: "memory");
    asm volatile("bar.sync 1, 256;" ::: "memory");
    STAMPW(0, 1);

    Ctx c;
    c.full = bar_full;
    c.emb = (lane == 0 && (warp & 3) < 2) ? mapa(bar_empty, (warp & 3) == 0 ? rank : (rank ^ 1)) : 0u;
    c.stage = 0; c.phase = 0; c.prev = ~0u;
    c.dB = (((sbase + SM_B) & 0x3FFFF) >> 4) | ((4096u >> 4) << 16);
    c.dA = (((sbase + SM_A + wg * 8192) & 0x3FFFF) >> 4) | (1u << 16);
    c.xfree = 0; c.owait = 0;
    const bool leader = (lane == 0) && ((warp & 3) == 0);

    const int rb = m * 8 + warp;
    const float* bias_t = sbias + 2 * t;
    uint4* part = g_part + (size_t)((rb * 8 + f) * 36) * 32 + lane;
    uint4* qkvp = g_qkvf + (size_t)(rb * 108 + 18 * f) * 32 + lane;
    uint4* hsp = g_hsp + (size_t)blockIdx.x * 12 * 256 + tid;
    const uint32_t hst = sbase + SM_A + (warp * 16 + (lane & 7) + ((lane >> 3) & 1) * 8) * 128 + (((lane >> 4) ^ (lane & 7)) << 4);
    auto wg_sync = [&]() {
      asm volatile("fence.proxy.async.shared::cta;" ::: "memory");
      if (wg == 0) asm volatile("bar.sync 2, 128;" ::: "memory"); else asm volatile("bar.sync 3, 128;" ::: "memory");
    };
    float A[96], B[96];
#pragma unroll
    for (int i = 0; i < 96; i++) A[i] = 0.f;

    auto publish = [&](bool isq, uint32_t* flg) {
      if (isq) { __syncwarp(); if (lane == 0) mbar_arrive(bar_q); } else hint_signal(flg);
    };
#pragma unroll 1
    for (int i = srole; i < 4 + srole; i++) {
      const uint32_t keep = i <= 1 ? ~0u : ~1u, pbit = i <= 1 ? 0u : par;
      uint4* dstA = i == 1 ? qkvp + 6 * 32 : part + (i == 3 ? 0 : 24 * 32);
      uint32_t* flgA = &g_f_rb[rb * 8 + (i == 3 ? 0 : 2)];
      const bool partA = (i == 1 && !srole) || i >= 3;
      if ((i & 3) == 0) {
        if (i == 4) c.owait = bar_ofull;
        stage_ss<96>(B, c, 0, true);
        retire(c, 0);
        c.xfree = 0;
        fence_regs<96>(A);
        stage_ss<96>(B, c, 1, false);
        if (partA) { part_groups<0, 12>(A, dstA, keep, pbit); hint_signal(flgA); }
        retire(c, 1);
#pragma unroll 1
        for (int s = 2; s < 17; s++) { stage_ss<96>(B, c, s, false); retire(c, s); }
        stage_ss<96>(B, c, 17, false);
        retire(c, 17);
        c.owait = 0;
      } else {
        const bool gel = i == 2;
        stage_ss<192>(B, c, 0, true);
        retire(c, 0);
        fence_regs<96>(A);
#pragma unroll 1
        for (int s = 1; s < 3; s++) {
          stage_ss<192>(B, c, s, false);
          if (partA && s == 1) { part_groups<0, 12>(A, dstA, keep, pbit); publish(i == 1, flgA); }
          retire(c, s);
        }
#pragma unroll
        for (int s = 3; s < 9; s++) {
          stage_ss<192>(B, c, s, false);
          if (gel) {
#pragma unroll
            for (int q = 2 * (s - 3); q < 2 * (s - 3) + 2; q++) stsm4((hst ^ ((q & 3) << 5)) + (q >> 2) * 16384, gelu_group(&A[8 * q], bias_t + 16 * (12 + q)));
          }
          retire(c, s);
        }
        uint4 pk[4];
#pragma unroll
        for (int q = 0; q < 4; q++) pk[q] = make_uint4(0, 0, 0, 0);
#pragma unroll 1
        for (int s = 9; s < 17; s++) {
          stage_ss<192>(B, c, s, false);
          if (gel) {
            if (s & 1) {
              if (s >= 11) {
#pragma unroll
                for (int q = 0; q < 4; q++) stsm4((hst ^ (q << 5)) + ((s - 5) >> 1) * 16384, pk[q]);
              }
              if (s <= 13) {
#pragma unroll
                for (int q = 0; q < 4; q++) pk[q] = ldcg128(hsp + ((s - 9) * 2 + q) * 256);
              }
            }
            if (s == 16) wg_sync();
          }
          retire(c, s);
        }
        stage_ss<192>(B, c, 17, false);
        retire(c, 17);
      }
      STAMPW(0, 2 + 2 * i);
      {
        uint4* dstB = i == 0 ? qkvp : (i == 3 ? part + 12 * 32 : g_s2 + (size_t)(rb * 12 + 6 * (f - 6)) * 32 + lane);
        uint32_t* flgB = &g_f_rb[rb * 8 + (i == 3 ? 1 : 3)];
        const bool gel = (i == 1) || (i == 2);
        stage_ss<192>(A, c, 0, true);
        retire(c, 0);
        if (i == 3 && srole && leader) c.xfree = bar_xfree - 8;
        fence_regs<96>(B);
        const float* bs = bias_t + (i == 1 ? 0 : 16 * 24);
#pragma unroll
        for (int s = 1; s < 7; s++) {
          stage_ss<192>(A, c, s, false);
          if (gel) {
#pragma unroll
            for (int q = 2 * (s - 1); q < 2 * (s - 1) + 2; q++) {
              const uint4 hv = gelu_group(&B[8 * q], bs + 16 * q);
              if (i == 1) hsp[q * 256] = hv; else stsm4((hst ^ ((q & 3) << 5)) + (6 + (q >> 2)) * 16384, hv);
            }
          } else if (s == 1) {
            part_groups<0, 6>(B, dstB, keep, pbit);
            if (i == 3) part_groups<6, 12>(B, dstB, keep, pbit);
            publish(i == 0, flgB);
          }
          retire(c, s);
        }
#pragma unroll 1
        for (int s = 7; s < 17; s++) {
          stage_ss<192>(A, c, s, false);
          if (s == 9 && i == 2) wg_sync();
          retire(c, s);
        }
        stage_ss<192>(A, c, 17, false);
        retire(c, 17);
        if (c.xfree != 0) c.xfree = bar_xfree + 64;
      }
      STAMPW(0, 3 + 2 * i);
    }

    const size_t r0 = (size_t)(rb * 16 + g) * D_ + 2 * t;
    if (srole) {
      const int cb = 192 * (f - 6);
      uint32_t xx[48];
      uint4 gg[12];
#pragma unroll
      for (int q = 0; q < 12; q++) {
        xx[4 * q + 0] = __ldg(reinterpret_cast<const uint32_t*>(P.x + r0 + cb + 16 * q));
        xx[4 * q + 1] = __ldg(reinterpret_cast<const uint32_t*>(P.x + r0 + 8 * D_ + cb + 16 * q));
        xx[4 * q + 2] = __ldg(reinterpret_cast<const uint32_t*>(P.x + r0 + cb + 16 * q + 8));
        xx[4 * q + 3] = __ldg(reinterpret_cast<const uint32_t*>(P.x + r0 + 8 * D_ + cb + 16 * q + 8));
      }
      if (lane == 0) hint_wait(&g_f_rb[rb * 8 + 4 + (f - 6)], 3 * ep);
      __syncwarp();
      STAMPW(0, 14);
      int tries = 0;
      uint32_t bad;
      do {
        bad = 0;
#pragma unroll
        for (int q = 0; q < 12; q++) gg[q] = ld_ll(&g_g[(rb * 24 + 12 * (f - 6) + q) * 32 + lane]);
#pragma unroll
        for (int q = 0; q < 12; q++) bad |= gg[q].x ^ par;
      } while (__any_sync(0xffffffffu, bad & 1) && ++tries < (1 << 20));
      wg_wait<0>();
      c.release_prev();
      fence_regs<96>(A);
#pragma unroll
      for (int q = 0; q < 12; q++) {
        const uint32_t* gw = reinterpret_cast<const uint32_t*>(&gg[q]);
        uint32_t res[4];
#pragma unroll
        for (int k = 0; k < 4; k++)
          res[k] = pack_bf16(fmaf(A[8 * q + 2 * k], bf_lo(gw[k]), bf_lo(xx[4 * q + k])), fmaf(A[8 * q + 2 * k + 1], bf_hi(gw[k]), bf_hi(xx[4 * q + k])));
        *reinterpret_cast<uint32_t*>(P.out + r0 + cb + 16 * q) = res[0];
        *reinterpret_cast<uint32_t*>(P.out + r0 + 8 * D_ + cb + 16 * q) = res[1];
        *reinterpret_cast<uint32_t*>(P.out + r0 + cb + 16 * q + 8) = res[2];
        *reinterpret_cast<uint32_t*>(P.out + r0 + 8 * D_ + cb + 16 * q + 8) = res[3];
      }
    } else {
      wg_wait<0>();
      c.release_prev();
      fence_regs<96>(A);
      part_groups<0, 12>(A, part + 24 * 32, ~1u, par);
      hint_signal(&g_f_rb[rb * 8 + 2]);
      STAMPW(0, 12);
      const int cb = 384 + 32 * f;
      uint32_t xx[8], bb[4];
#pragma unroll
      for (int j = 0; j < 2; j++) {
        xx[4 * j + 0] = __ldg(reinterpret_cast<const uint32_t*>(P.x + r0 + cb + 16 * j));
        xx[4 * j + 1] = __ldg(reinterpret_cast<const uint32_t*>(P.x + r0 + 8 * D_ + cb + 16 * j));
        xx[4 * j + 2] = __ldg(reinterpret_cast<const uint32_t*>(P.x + r0 + cb + 16 * j + 8));
        xx[4 * j + 3] = __ldg(reinterpret_cast<const uint32_t*>(P.x + r0 + 8 * D_ + cb + 16 * j + 8));
        bb[2 * j] = __ldg(reinterpret_cast<const uint32_t*>(P.b2 + cb + 16 * j + 2 * t));
        bb[2 * j + 1] = __ldg(reinterpret_cast<const uint32_t*>(P.b2 + cb + 16 * j + 8 + 2 * t));
      }
      if (lane < 2) hint_wait(&g_f_rb[rb * 8 + 2 + lane], (lane == 0 ? 8u : 2u) * ep);
      __syncwarp();
      STAMPW(0, 14);
      uint4 p[2][8], sv[2];
      int tries = 0;
      uint32_t bad;
      do {
        bad = 0;
#pragma unroll
        for (int j = 0; j < 2; j++) {
#pragma unroll
          for (int i = 0; i < 8; i++) p[j][i] = ld_ll(&g_part[((rb * 8 + i) * 36 + 24 + 2 * f + j) * 32 + lane]);
          sv[j] = ld_ll(&g_s2[(rb * 12 + 2 * f + j) * 32 + lane]);
        }
#pragma unroll
        for (int j = 0; j < 2; j++) {
#pragma unroll
          for (int i = 0; i < 8; i++) bad |= p[j][i].x ^ par;
          bad |= sv[j].x ^ par;
        }
      } while (__any_sync(0xffffffffu, bad & 1) && ++tries < (1 << 20));
#pragma unroll
      for (int j = 0; j < 2; j++) {
        float gt[8];
        gate_vec(p[j], bb[2 * j], bb[2 * j + 1], gt);
        const uint32_t* sw = reinterpret_cast<const uint32_t*>(&sv[j]);
        uint32_t res[4];
#pragma unroll
        for (int k = 0; k < 4; k++) res[k] = pack_bf16(fmaf(bf_lo(sw[k]), gt[2 * k], bf_lo(xx[4 * j + k])), fmaf(bf_hi(sw[k]), gt[2 * k + 1], bf_hi(xx[4 * j + k])));
        *reinterpret_cast<uint32_t*>(P.out + r0 + cb + 16 * j) = res[0];
        *reinterpret_cast<uint32_t*>(P.out + r0 + 8 * D_ + cb + 16 * j) = res[1];
        *reinterpret_cast<uint32_t*>(P.out + r0 + cb + 16 * j + 8) = res[2];
        *reinterpret_cast<uint32_t*>(P.out + r0 + 8 * D_ + cb + 16 * j + 8) = res[3];
      }
    }
    STAMPW(0, 15);
    cluster_arrive_relaxed();
    cluster_wait();
    STAMPW(0, 16);
    if (tid == 0) g_epoch[blockIdx.x] = ep;
  }
}

typedef CUresult (*EncFn)(CUtensorMap*, CUtensorMapDataType, cuuint32_t, void*, const cuuint64_t*, const cuuint64_t*, const cuuint32_t*, const cuuint32_t*,
                          CUtensorMapInterleave, CUtensorMapSwizzle, CUtensorMapL2promotion, CUtensorMapFloatOOBfill);

void make_map(EncFn enc, CUtensorMap* tm, const void* ptr, int rows, int cols, int box_rows) {
  cuuint64_t gd[2] = {(cuuint64_t)cols, (cuuint64_t)rows};
  cuuint64_t gs[1] = {(cuuint64_t)cols * 2};
  cuuint32_t bx[2] = {64, (cuuint32_t)box_rows};
  cuuint32_t es[2] = {1, 1};
  enc(tm, CU_TENSOR_MAP_DATA_TYPE_BFLOAT16, 2, const_cast<void*>(ptr), gd, gs, bx, es, CU_TENSOR_MAP_INTERLEAVE_NONE, CU_TENSOR_MAP_SWIZZLE_128B,
      CU_TENSOR_MAP_L2_PROMOTION_L2_256B, CU_TENSOR_MAP_FLOAT_OOB_FILL_NONE);
}

}

extern "C" void kernel_launch(void* const* d_in, const int* in_sizes, int n_in, void* d_out, int out_size) {
  (void)in_sizes; (void)n_in; (void)out_size;
  static EncFn enc = nullptr;
  static void* o_ptr = nullptr;
  if (!enc) {
    void* fn = nullptr; cudaDriverEntryPointQueryResult q;
    cudaGetDriverEntryPoint("cuTensorMapEncodeTiled", &fn, cudaEnableDefault, &q);
    enc = (EncFn)fn;
    cudaFuncSetAttribute(fused_kernel, cudaFuncAttributeMaxDynamicSharedMemorySize, SMEM_BYTES);
    cudaGetSymbolAddress(&o_ptr, g_o);
  }
  Params P;
  P.x = (const __nv_bfloat16*)d_in[0];
  P.wqkv = (const __nv_bfloat16*)d_in[1];
  P.wo = (const __nv_bfloat16*)d_in[2];
  P.w1 = (const __nv_bfloat16*)d_in[4];
  P.b1 = (const __nv_bfloat16*)d_in[5];
  P.w2 = (const __nv_bfloat16*)d_in[6];
  P.b2 = (const __nv_bfloat16*)d_in[7];
  P.out = (__nv_bfloat16*)d_out;
  make_map(enc, &P.tm_wqkv, P.wqkv, D_, Q3_, 32);
  make_map(enc, &P.tm_w1, P.w1, D_, F_, 32);
  make_map(enc, &P.tm_w2, P.w2, F_, D_, 32);
  make_map(enc, &P.tm_wo, P.wo, D_, D_, 32);
  make_map(enc, &P.tm_o, o_ptr, S_, D_, 128);
  make_map(enc, &P.tm_x, P.x, S_, D_, 32);
  fused_kernel<<<NCTAS, NTHREADS, SMEM_BYTES, cudaStreamPerThread>>>(P);
}
```

```cpp
#include <cuda_runtime.h>
#include <cuda.h>
#include <cuda_bf16.h>
#include <stdint.h>

namespace {

constexpr int S_ = 2048, D_ = 576, F_ = 4608, Q3_ = 1728;
constexpr int NSTAGE = 6, STAGE_BYTES = 12288;
constexpr int SM_A = 0, SM_B = 147456, SM_BIAS = SM_B + NSTAGE * STAGE_BYTES, SM_BAR = SM_BIAS + 2304;
constexpr int SMEM_BYTES = SM_BAR + 320;
constexpr int NTHREADS = 384;
constexpr int NCTAS = 132;

__device__ uint4 g_qkvf[(128 * 108 + 1) * 32];
__device__ __align__(1024) __nv_bfloat16 g_o[S_ * D_];
__device__ uint4 g_kvp[32 * 32 * 5 * 32];
__device__ uint4 g_kvt[32 * 5 * 32];
__device__ uint4 g_part[128 * 8 * 36 * 32];
__device__ uint4 g_s2[128 * 12 * 32];
__device__ uint4 g_g[128 * 24 * 32];
__device__ uint4 g_hsp[128 * 12 * 256];
__device__ uint32_t g_f_qkv[16 * 8];
__device__ uint32_t g_f_kvp[32];
__device__ uint32_t g_f_kvt[32];
__device__ uint32_t g_f_o[16];
__device__ uint32_t g_f_rb[128 * 8];
__device__ uint32_t g_epoch[NCTAS];

#define STAMP(i)
#define STAMPW(w, i)
#define WSTAMP(i)
__device__ __forceinline__ uint32_t smem_u32(const void* p) { return (uint32_t)__cvta_generic_to_shared(p); }
__device__ __forceinline__ void mbar_init(uint32_t a, int c) { asm volatile("mbarrier.init.shared::cta.b64 [%0], %1;" ::"r"(a), "r"(c)); }
__device__ __forceinline__ void mbar_expect(uint32_t a, uint32_t b) { asm volatile("mbarrier.arrive.expect_tx.shared::cta.b64 _, [%0], %1;" ::"r"(a), "r"(b) : "memory"); }
__device__ __forceinline__ void mbar_arrive(uint32_t a) { asm volatile("mbarrier.arrive.shared::cta.b64 _, [%0];" ::"r"(a) : "memory"); }
__device__ __forceinline__ void mbar_arrive_cl(uint32_t a) { asm volatile("mbarrier.arrive.shared::cluster.b64 _, [%0];" ::"r"(a) : "memory"); }
__device__ __forceinline__ uint32_t mapa(uint32_t a, uint32_t cta) { uint32_t r; asm volatile("mapa.shared::cluster.u32 %0, %1, %2;" : "=r"(r) : "r"(a), "r"(cta)); return r; }
__device__ __forceinline__ void mbar_wait(uint32_t a, uint32_t ph) {
  uint32_t ok; int it = 0;
#pragma unroll 1
  do {
    asm volatile("{.reg .pred p; mbarrier.try_wait.parity.shared::cta.b64 p, [%1], %2; selp.u32 %0,1,0,p;}" : "=r"(ok) : "r"(a), "r"(ph) : "memory");
  } while (!ok && ++it < (1 << 18));
}
__device__ __forceinline__ void tma2d(uint32_t dst, const CUtensorMap* m, int c0, int c1, uint32_t bar) {
  asm volatile("cp.async.bulk.tensor.2d.shared::cluster.global.mbarrier::complete_tx::bytes [%0], [%1, {%3,%4}], [%2];" ::"r"(dst), "l"(m), "r"(bar), "r"(c0), "r"(c1) : "memory");
}
__device__ __forceinline__ void tma2d_mc(uint32_t dst, const CUtensorMap* m, int c0, int c1, uint32_t bar) {
  asm volatile("cp.async.bulk.tensor.2d.shared::cluster.global.mbarrier::complete_tx::bytes.multicast::cluster [%0], [%1, {%3,%4}], [%2], %5;" ::"r"(dst), "l"(m), "r"(bar), "r"(c0), "r"(c1), "h"((uint16_t)3) : "memory");
}
__device__ __forceinline__ void cluster_arrive_relaxed() { asm volatile("barrier.cluster.arrive.relaxed.aligned;" ::: "memory"); }
__device__ __forceinline__ void cluster_wait() { asm volatile("barrier.cluster.wait.acquire.aligned;" ::: "memory"); }
__device__ __forceinline__ void wg_fence() { asm volatile("wgmma.fence.sync.aligned;" ::: "memory"); }
__device__ __forceinline__ void wg_commit() { asm volatile("wgmma.commit_group.sync.aligned;" ::: "memory"); }
template <int n> __device__ __forceinline__ void wg_wait() { asm volatile("wgmma.wait_group.sync.aligned %0;" ::"n"(n) : "memory"); }
__device__ __forceinline__ uint32_t ld_acquire(const uint32_t* p) { uint32_t v; asm volatile("ld.acquire.gpu.global.u32 %0, [%1];" : "=r"(v) : "l"(p) : "memory"); return v; }
__device__ __forceinline__ void flag_wait(const uint32_t* p, uint32_t target) {
  int it = 0;
#pragma unroll 1
  while ((int)(ld_acquire(p) - target) < 0 && ++it < (1 << 21)) __nanosleep(40);
}
__device__ __forceinline__ void hint_signal(uint32_t* p) {
  if ((threadIdx.x & 31) == 0) asm volatile("red.relaxed.gpu.global.add.u32 [%0], 1;" ::"l"(p) : "memory");
}
__device__ __forceinline__ void hint_wait(const uint32_t* p, uint32_t target) {
  int it = 0; uint32_t v;
#pragma unroll 1
  do { asm volatile("ld.relaxed.gpu.global.u32 %0, [%1];" : "=r"(v) : "l"(p) : "memory"); if ((int)(v - target) >= 0) break; __nanosleep(32); } while (++it < (1 << 21));
}
__device__ __forceinline__ void st_ll(uint4* p, uint32_t x, uint32_t y, uint32_t z, uint32_t w, uint32_t par) {
  asm volatile("{.reg .b64 a, b; mov.b64 a, {%1,%2}; mov.b64 b, {%3,%4}; st.relaxed.gpu.global.v2.b64 [%0], {a, b};}"
               ::"l"(p), "r"((x & ~1u) | par), "r"(y), "r"((z & ~1u) | par), "r"(w) : "memory");
}
__device__ __forceinline__ uint4 ld_ll(const uint4* p) {
  uint4 v;
  asm volatile("{.reg .b64 a, b; ld.relaxed.gpu.global.v2.b64 {a, b}, [%4]; mov.b64 {%0,%1}, a; mov.b64 {%2,%3}, b;}"
               : "=r"(v.x), "=r"(v.y), "=r"(v.z), "=r"(v.w) : "l"(p) : "memory");
  return v;
}
__device__ __forceinline__ uint2 ld_ll64(const uint32_t* p) {
  uint2 v;
  asm volatile("{.reg .b64 a; ld.relaxed.gpu.global.b64 a, [%2]; mov.b64 {%0,%1}, a;}" : "=r"(v.x), "=r"(v.y) : "l"(p) : "memory");
  return v;
}
__device__ __forceinline__ uint32_t ll_bad(uint4 v, uint32_t par) { return (v.x ^ par) | (v.z ^ par); }
__device__ __forceinline__ uint32_t pack_bf16(float lo, float hi) { uint32_t r; asm("cvt.rn.bf16x2.f32 %0, %1, %2;" : "=r"(r) : "f"(hi), "f"(lo)); return r; }
__device__ __forceinline__ float bf_lo(uint32_t v) { return __uint_as_float(v << 16); }
__device__ __forceinline__ float bf_hi(uint32_t v) { return __uint_as_float(v & 0xffff0000u); }
__device__ __forceinline__ float tanh_fast(float x) { float r; asm("tanh.approx.f32 %0, %1;" : "=f"(r) : "f"(x)); return r; }
__device__ __forceinline__ uint32_t movmat(uint32_t a) { uint32_t d; asm volatile("movmatrix.sync.aligned.m8n8.trans.b16 %0, %1;" : "=r"(d) : "r"(a)); return d; }
__device__ __forceinline__ void mma16816(float* c, uint32_t a0, uint32_t a1, uint32_t a2, uint32_t a3, uint32_t b0, uint32_t b1) {
  asm volatile("mma.sync.aligned.m16n8k16.row.col.f32.bf16.bf16.f32 {%0,%1,%2,%3}, {%4,%5,%6,%7}, {%8,%9}, {%0,%1,%2,%3};"
               : "+f"(c[0]), "+f"(c[1]), "+f"(c[2]), "+f"(c[3]) : "r"(a0), "r"(a1), "r"(a2), "r"(a3), "r"(b0), "r"(b1));
}
__device__ __forceinline__ uint4 ldcg128(const void* p) { uint4 v; asm volatile("ld.global.cg.v4.u32 {%0,%1,%2,%3}, [%4];" : "=r"(v.x), "=r"(v.y), "=r"(v.z), "=r"(v.w) : "l"(p) : "memory"); return v; }

template <int N> __device__ __forceinline__ void wgmma_ss(float* d, uint64_t da, uint64_t db, int sc);
template <int N> __device__ __forceinline__ void wgmma_rs(float* d, const uint32_t* a, uint64_t db, int sc);
template <> __device__ __forceinline__ void wgmma_ss<96>(float* d, uint64_t da, uint64_t db, int sc) {
  asm volatile("{.reg .pred p; setp.ne.b32 p, %50, 0; wgmma.mma_async.sync.aligned.m64n96k16.f32.bf16.bf16 {%0, %1, %2, %3, %4, %5, %6, %7, %8, %9, %10, %11, %12, %13, %14, %15, %16, %17, %18, %19, %20, %21, %22, %23, %24, %25, %26, %27, %28, %29, %30, %31, %32, %33, %34, %35, %36, %37, %38, %39, %40, %41, %42, %43, %44, %45, %46, %47}, %48, %49, p, 1, 1, 0, 1;}"
   : "+f"(d[0]), "+f"(d[1]), "+f"(d[2]), "+f"(d[3]), "+f"(d[4]), "+f"(d[5]), "+f"(d[6]), "+f"(d[7]), "+f"(d[8]), "+f"(d[9]), "+f"(d[10]), "+f"(d[11]), "+f"(d[12]), "+f"(d[13]), "+f"(d[14]), "+f"(d[15]), "+f"(d[16]), "+f"(d[17]), "+f"(d[18]), "+f"(d[19]), "+f"(d[20]), "+f"(d[21]), "+f"(d[22]), "+f"(d[23]), "+f"(d[24]), "+f"(d[25]), "+f"(d[26]), "+f"(d[27]), "+f"(d[28]), "+f"(d[29]), "+f"(d[30]), "+f"(d[31]), "+f"(d[32]), "+f"(d[33]), "+f"(d[34]), "+f"(d[35]), "+f"(d[36]), "+f"(d[37]), "+f"(d[38]), "+f"(d[39]), "+f"(d[40]), "+f"(d[41]), "+f"(d[42]), "+f"(d[43]), "+f"(d[44]), "+f"(d[45]), "+f"(d[46]), "+f"(d[47]) : "l"(da), "l"(db), "r"(sc));
}
template <> __device__ __forceinline__ void wgmma_ss<192>(float* d, uint64_t da, uint64_t db, int sc) {
  asm volatile("{.reg .pred p; setp.ne.b32 p, %98, 0; wgmma.mma_async.sync.aligned.m64n192k16.f32.bf16.bf16 {%0, %1, %2, %3, %4, %5, %6, %7, %8, %9, %10, %11, %12, %13, %14, %15, %16, %17, %18, %19, %20, %21, %22, %23, %24, %25, %26, %27, %28, %29, %30, %31, %32, %33, %34, %35, %36, %37, %38, %39, %40, %41, %42, %43, %44, %45, %46, %47, %48, %49, %50, %51, %52, %53, %54, %55, %56, %57, %58, %59, %60, %61, %62, %63, %64, %65, %66, %67, %68, %69, %70, %71, %72, %73, %74, %75, %76, %77, %78, %79, %80, %81, %82, %83, %84, %85, %86, %87, %88, %89, %90, %91, %92, %93, %94, %95}, %96, %97, p, 1, 1, 0, 1;}"
   : "+f"(d[0]), "+f"(d[1]), "+f"(d[2]), "+f"(d[3]), "+f"(d[4]), "+f"(d[5]), "+f"(d[6]), "+f"(d[7]), "+f"(d[8]), "+f"(d[9]), "+f"(d[10]), "+f"(d[11]), "+f"(d[12]), "+f"(d[13]), "+f"(d[14]), "+f"(d[15]), "+f"(d[16]), "+f"(d[17]), "+f"(d[18]), "+f"(d[19]), "+f"(d[20]), "+f"(d[21]), "+f"(d[22]), "+f"(d[23]), "+f"(d[24]), "+f"(d[25]), "+f"(d[26]), "+f"(d[27]), "+f"(d[28]), "+f"(d[29]), "+f"(d[30]), "+f"(d[31]), "+f"(d[32]), "+f"(d[33]), "+f"(d[34]), "+f"(d[35]), "+f"(d[36]), "+f"(d[37]), "+f"(d[38]), "+f"(d[39]), "+f"(d[40]), "+f"(d[41]), "+f"(d[42]), "+f"(d[43]), "+f"(d[44]), "+f"(d[45]), "+f"(d[46]), "+f"(d[47]), "+f"(d[48]), "+f"(d[49]), "+f"(d[50]), "+f"(d[51]), "+f"(d[52]), "+f"(d[53]), "+f"(d[54]), "+f"(d[55]), "+f"(d[56]), "+f"(d[57]), "+f"(d[58]), "+f"(d[59]), "+f"(d[60]), "+f"(d[61]), "+f"(d[62]), "+f"(d[63]), "+f"(d[64]), "+f"(d[65]), "+f"(d[66]), "+f"(d[67]), "+f"(d[68]), "+f"(d[69]), "+f"(d[70]), "+f"(d[71]), "+f"(d[72]), "+f"(d[73]), "+f"(d[74]), "+f"(d[75]), "+f"(d[76]), "+f"(d[77]), "+f"(d[78]), "+f"(d[79]), "+f"(d[80]), "+f"(d[81]), "+f"(d[82]), "+f"(d[83]), "+f"(d[84]), "+f"(d[85]), "+f"(d[86]), "+f"(d[87]), "+f"(d[88]), "+f"(d[89]), "+f"(d[90]), "+f"(d[91]), "+f"(d[92]), "+f"(d[93]), "+f"(d[94]), "+f"(d[95]) : "l"(da), "l"(db), "r"(sc));
}

__device__ __forceinline__ uint64_t desc64(uint32_t lo, uint32_t hi) { uint64_t d; asm("mov.b64 %0, {%1, %2};" : "=l"(d) : "r"(lo), "r"(hi)); return d; }
constexpr uint32_t DESC_HI = (1024u >> 4) | (1u << 30);
constexpr uint32_t DESC_HI64 = (512u >> 4) | (2u << 30);
template <int n> __device__ __forceinline__ void fence_regs(float* a) {
#pragma unroll
  for (int i = 0; i < n; i++) asm volatile("" : "+f"(a[i])::"memory");
}

struct Ctx {
  uint32_t full;
  uint32_t emb;
  uint32_t stage, phase, prev;
  uint32_t dB, dA;
  __device__ __forceinline__ void release_prev() { if (emb != 0 && prev != ~0u) mbar_arrive_cl(emb + prev); }
  __device__ __forceinline__ void wait_full() {
    mbar_wait(full + 8 * stage, phase);
    wg_fence();
  }
};

__device__ __forceinline__ void issue192(float* acc, Ctx& c, int s, bool first = false) {
  c.wait_full();
  const uint32_t db = c.dB + c.stage * (STAGE_BYTES >> 4);
  const uint32_t da = c.dA + (s >> 1) * 1024 + (s & 1) * 4;
  wgmma_ss<192>(acc, desc64(da, DESC_HI), desc64(db, DESC_HI), first ? 0 : 1);
  wgmma_ss<192>(acc, desc64(da + 2, DESC_HI), desc64(db + 128, DESC_HI), 1);
  wg_commit();
}
__device__ __forceinline__ void issue96(float* acc, Ctx& c, int s, bool first) {
  c.wait_full();
  const uint32_t db = c.dB + c.stage * (STAGE_BYTES >> 4);
  const uint32_t da = c.dA + s * 1024;
#pragma unroll
  for (int kk = 0; kk < 4; kk++) wgmma_ss<96>(acc, desc64(da + 2 * kk, DESC_HI), desc64(db + 64 * kk, DESC_HI64), (first && kk == 0) ? 0 : 1);
  wg_commit();
}
__device__ __forceinline__ void retire(Ctx& c) {
  wg_wait<1>();
  c.release_prev();
  c.prev = 8 * c.stage;
  if (++c.stage == NSTAGE) { c.stage = 0; c.phase ^= 1; }
}
__device__ __forceinline__ float gelu2(float x) {
  float u = x * fmaf(x * x, 0.0356774081f, 0.7978845608f);
  return fmaf(x, tanh_fast(u), x);
}
__device__ __forceinline__ uint4 gelu_group(const float* a, float2 b0, float2 b1) {
  return make_uint4(pack_bf16(gelu2(a[0] + b0.x), gelu2(a[1] + b0.y)), pack_bf16(gelu2(a[2] + b0.x), gelu2(a[3] + b0.y)),
                    pack_bf16(gelu2(a[4] + b1.x), gelu2(a[5] + b1.y)), pack_bf16(gelu2(a[6] + b1.x), gelu2(a[7] + b1.y)));
}
__device__ __forceinline__ void lds_bias(float2* b, uint32_t addr) {
#pragma unroll
  for (int j = 0; j < 4; j++) asm volatile("ld.shared.v2.f32 {%0,%1}, [%2];" : "=f"(b[j].x), "=f"(b[j].y) : "r"(addr + 32 * j));
}
__device__ __forceinline__ int opaque(int v) { asm volatile("" : "+r"(v)); return v; }
__device__ __forceinline__ void stsm4(uint32_t addr, uint4 r) {
  asm volatile("stmatrix.sync.aligned.m8n8.x4.shared.b16 [%0], {%1,%2,%3,%4};" ::"r"(addr), "r"(r.x), "r"(r.y), "r"(r.z), "r"(r.w) : "memory");
}
__device__ __forceinline__ float ex2f(float x) { float r; asm("ex2.approx.ftz.f32 %0, %1;" : "=f"(r) : "f"(x)); return r; }
__device__ __forceinline__ float phi(float t) { float e = ex2f(t * 1.4426950408889634f); if (t > 0.f) e = t + 1.f; return e + 1e-6f; }
__device__ __forceinline__ uint32_t phi2(uint32_t w) { return pack_bf16(phi(bf_lo(w)), phi(bf_hi(w))); }
template <int q0, int q1>
__device__ __forceinline__ void part_groups(const float* a, uint4* p, uint32_t par) {
#pragma unroll
  for (int q = q0; q < q1; q++)
    st_ll(p + q * 32, pack_bf16(a[8 * q], a[8 * q + 1]), pack_bf16(a[8 * q + 2], a[8 * q + 3]), pack_bf16(a[8 * q + 4], a[8 * q + 5]), pack_bf16(a[8 * q + 6], a[8 * q + 7]), par);
}
__device__ __forceinline__ float silu(float y) { return __fdividef(y, 1.f + ex2f(y * -1.4426950408889634f)); }
__device__ __forceinline__ void gate_vec(const uint4* p, uint32_t b0, uint32_t b1, float* gt) {
#pragma unroll
  for (int q = 0; q < 4; q++) {
    float lo = 0.f, hi = 0.f;
#pragma unroll
    for (int i = 0; i < 8; i++) { uint32_t w = reinterpret_cast<const uint32_t*>(&p[i])[q]; lo += bf_lo(w); hi += bf_hi(w); }
    const uint32_t bb = q < 2 ? b0 : b1;
    gt[2 * q] = silu(fmaf(lo, 0.5f, bf_lo(bb)));
    gt[2 * q + 1] = silu(fmaf(hi, 0.5f, bf_hi(bb)));
  }
}
__device__ __forceinline__ int coloff(int c) { return (c >> 4) * 128 + ((c & 7) >> 1) * 4 + ((c >> 3) & 1) * 2; }

struct Params {
  CUtensorMap tm_wqkv, tm_w1, tm_w2, tm_wo, tm_wqkv64, tm_wo64, tm_o, tm_x;
  const __nv_bfloat16 *x, *b1, *b2, *wqkv, *w1, *w2, *wo;
  __nv_bfloat16* out;
};

__global__ void __cluster_dims__(2, 1, 1) __launch_bounds__(NTHREADS, 1) fused_kernel(const __grid_constant__ Params P) {
  extern __shared__ __align__(1024) uint8_t smem[];
  const uint32_t sbase = smem_u32(smem);
  const int tid = threadIdx.x, lane = tid & 31;
  const int warp = __shfl_sync(0xffffffffu, tid >> 5, 0);
  const int g = lane >> 2, t = lane & 3;
  const uint32_t ep = g_epoch[blockIdx.x] + 1;
  const uint32_t par = ep & 1;
  STAMPW(0, 0);

  if (blockIdx.x >= 128) {
    const int a = blockIdx.x - 128;
    if (warp < 8) {
      const int head = a * 8 + warp;
      if (lane == 0) hint_wait(&g_f_kvp[head], 32 * ep);
      __syncwarp();
      STAMPW(0, 1);
      float sm[20];
#pragma unroll
      for (int j = 0; j < 20; j++) sm[j] = 0.f;
#pragma unroll 1
      for (int m0 = 0; m0 < 32; m0 += 7) {
        uint4 v[35];
        int tries = 0;
        uint32_t bad;
#pragma unroll 1
        do {
          bad = 0;
#pragma unroll
          for (int j = 0; j < 35; j++) v[j] = ld_ll(&g_kvp[(head * 160 + min(m0 * 5 + j, 159)) * 32 + lane]);
#pragma unroll
          for (int j = 0; j < 35; j++) bad |= ll_bad(v[j], par);
        } while (__any_sync(0xffffffffu, bad & 1) && ++tries < (1 << 20));
#pragma unroll
        for (int j = 0; j < 35; j++) {
          if (m0 * 5 + j < 160) {
            sm[(j % 5) * 4 + 0] += __uint_as_float(v[j].x); sm[(j % 5) * 4 + 1] += __uint_as_float(v[j].y); sm[(j % 5) * 4 + 2] += __uint_as_float(v[j].z); sm[(j % 5) * 4 + 3] += __uint_as_float(v[j].w);
          }
        }
      }
      st_ll(&g_kvt[(head * 5 + 0) * 32 + lane], 0u, pack_bf16(sm[0], sm[1]), 0u, pack_bf16(sm[4], sm[5]), par);
      st_ll(&g_kvt[(head * 5 + 1) * 32 + lane], 0u, pack_bf16(sm[2], sm[3]), 0u, pack_bf16(sm[6], sm[7]), par);
      st_ll(&g_kvt[(head * 5 + 2) * 32 + lane], 0u, pack_bf16(sm[12], sm[13]), 0u, pack_bf16(sm[14], sm[15]), par);
      st_ll(&g_kvt[(head * 5 + 3) * 32 + lane], 0u, pack_bf16(sm[8], sm[9]), 0u, pack_bf16(sm[10], sm[11]), par);
      st_ll(&g_kvt[(head * 5 + 4) * 32 + lane], 0u, pack_bf16(sm[16], sm[17]), 0u, 0u, par);
      hint_signal(&g_f_kvt[head]);
      STAMPW(0, 2);
    } else if (lane == 0) {
      const int id = a * 4 + (warp - 8);
      constexpr uint32_t CH = 9216 * 2;
      __nanosleep(1500);
#pragma unroll 1
      for (int i = id; i < 612; i += 16) {
        const char* p = i < 288 ? (const char*)P.w1 + (size_t)i * CH : (i < 576 ? (const char*)P.w2 + (size_t)(i - 288) * CH : (const char*)P.wo + (size_t)(i - 576) * CH);
        asm volatile("cp.async.bulk.prefetch.L2.global [%0], %1;" ::"l"(p), "r"(CH) : "memory");
      }
    }
    __syncthreads();
    if (tid == 0) g_epoch[blockIdx.x] = ep;
    return;
  }

  const int cl = blockIdx.x >> 1, rank = blockIdx.x & 1;
  const int f = cl & 7, m = (cl >> 3) * 2 + rank;
  const int srole = f >= 6 ? 1 : 0;
  const uint32_t bar_full = sbase + SM_BAR, bar_empty = bar_full + 8 * NSTAGE, bar_xfree = bar_empty + 8 * NSTAGE, bar_ofull = bar_xfree + 72, bar_x = bar_ofull + 72,
                 bar_d = bar_x + 32, bar_o = bar_d + 16;

  if (warp >= 8 && lane == 0) {
    mbar_init(bar_x + 8 * (warp - 8), 1);
    asm volatile("fence.mbarrier_init.release.cluster;" ::: "memory");
  } else if (tid == 0) {
#pragma unroll 1
    for (int i = 0; i < NSTAGE; i++) { mbar_init(bar_full + 8 * i, 1); mbar_init(bar_empty + 8 * i, 4); }
#pragma unroll 1
    for (int i = 0; i < 9; i++) { mbar_init(bar_xfree + 8 * i, 2); mbar_init(bar_ofull + 8 * i, 1); }
    mbar_init(bar_d, 1); mbar_init(bar_d + 8, 1); mbar_init(bar_o, 8);
    asm volatile("fence.mbarrier_init.release.cluster;" ::: "memory");
  }
  __syncwarp();
  cluster_arrive_relaxed();
  if (warp >= 8 && lane == 0) {
    const int i = warp - 8;
    mbar_expect(bar_x + 8 * i, 36864);
#pragma unroll 1
    for (int kb = 0; kb < 9; kb++) tma2d(sbase + SM_A + kb * 16384 + i * 4096, &P.tm_x, kb * 64, m * 128 + i * 32, bar_x + 8 * i);
  }
  __syncwarp();
  const uint32_t bw = tid < 288 ? __ldg(reinterpret_cast<const uint32_t*>(P.b1 + 576 * f) + tid) : 0u;
  cluster_wait();
  STAMPW(0, 19);

  if (warp != 8) {
#pragma unroll 1
    for (int j = warp > 8 ? warp - 1 : warp; j < 32; j += 11) {
      mbar_wait(bar_x + (j & ~7), 0);
      uint8_t* rowp = smem + SM_A + (j * 4 + (lane >> 3)) * 128 + (lane & 7) * 16;
      float v[72];
      float s0 = 0.f, s1 = 0.f;
#pragma unroll
      for (int kb = 0; kb < 9; kb++) {
        const uint4 w = *reinterpret_cast<const uint4*>(rowp + kb * 16384);
        v[8 * kb + 0] = bf_lo(w.x); v[8 * kb + 1] = bf_hi(w.x); v[8 * kb + 2] = bf_lo(w.y); v[8 * kb + 3] = bf_hi(w.y);
        v[8 * kb + 4] = bf_lo(w.z); v[8 * kb + 5] = bf_hi(w.z); v[8 * kb + 6] = bf_lo(w.w); v[8 * kb + 7] = bf_hi(w.w);
        s0 += (v[8 * kb] + v[8 * kb + 1]) + (v[8 * kb + 2] + v[8 * kb + 3]);
        s1 += (v[8 * kb + 4] + v[8 * kb + 5]) + (v[8 * kb + 6] + v[8 * kb + 7]);
      }
      float sum = s0 + s1;
      sum += __shfl_xor_sync(0xffffffffu, sum, 1); sum += __shfl_xor_sync(0xffffffffu, sum, 2); sum += __shfl_xor_sync(0xffffffffu, sum, 4);
      const float mean = sum * (1.f / 576.f);
      float q0 = 0.f, q1 = 0.f, q2 = 0.f, q3 = 0.f;
#pragma unroll
      for (int i = 0; i < 72; i += 4) {
        v[i] -= mean; v[i + 1] -= mean; v[i + 2] -= mean; v[i + 3] -= mean;
        q0 = fmaf(v[i], v[i], q0); q1 = fmaf(v[i + 1], v[i + 1], q1); q2 = fmaf(v[i + 2], v[i + 2], q2); q3 = fmaf(v[i + 3], v[i + 3], q3);
      }
      float sq = (q0 + q1) + (q2 + q3);
      sq += __shfl_xor_sync(0xffffffffu, sq, 1); sq += __shfl_xor_sync(0xffffffffu, sq, 2); sq += __shfl_xor_sync(0xffffffffu, sq, 4);
      const float rstd = rsqrtf(sq * (1.f / 576.f) + 1e-5f);
#pragma unroll
      for (int kb = 0; kb < 9; kb++)
        *reinterpret_cast<uint4*>(rowp + kb * 16384) = make_uint4(pack_bf16(v[8 * kb] * rstd, v[8 * kb + 1] * rstd), pack_bf16(v[8 * kb + 2] * rstd, v[8 * kb + 3] * rstd),
                                                                   pack_bf16(v[8 * kb + 4] * rstd, v[8 * kb + 5] * rstd), pack_bf16(v[8 * kb + 6] * rstd, v[8 * kb + 7] * rstd));
      STAMPW(0, 28 + j / 11);
    }
    asm volatile("fence.proxy.async.shared::cta;" ::: "memory");
  }
  if (tid < 288) reinterpret_cast<float2*>(smem + SM_BIAS)[tid] = make_float2(bf_lo(bw), bf_hi(bw));

  if (warp >= 8) {
    asm volatile("bar.arrive 1, 384;" ::: "memory");
    asm volatile("setmaxnreg.dec.sync.aligned.u32 56;");
    if (warp == 8) {
      if (lane == 0) {
        uint32_t stage = 0, phase = 1;
        const uint32_t sb = sbase + SM_B;
#pragma unroll 1
        for (int tl = 2 * srole; tl < 8 + 2 * srole; tl++) {
          const CUtensorMap* map = tl == 0 ? &P.tm_wqkv64 : (tl == 1 ? &P.tm_wqkv : (tl < 5 ? &P.tm_w1 : (tl < 8 ? &P.tm_w2 : (tl == 8 ? &P.tm_wo64 : &P.tm_wo))));
          const int col = tl < 2 ? 288 * f + 96 * tl : (tl < 5 ? 576 * f + 192 * (tl - 2) : (tl < 8 ? 192 * (tl - 5) : (tl == 8 ? 384 + 96 * (f - 6) : 192 * (f - 6))));
          const bool perm = tl >= 5 && tl < 8;
          const bool z = (tl & 7) == 0;
          const int cs = z ? 32 : 64, rs = z ? 64 : 32, nst = z ? 9 : 18;
#pragma unroll 1
          for (int st = 0; st < nst; st++) {
            int row = st * rs;
            if (perm) row += 576 * f + ((st < 6) ? 192 : (st < 12 ? -192 : 0));
            mbar_wait(bar_empty + 8 * stage, phase);
            mbar_expect(bar_full + 8 * stage, 12288);
            const uint32_t dst = sb + stage * STAGE_BYTES;
            if (((st ^ rank) & 1) == 0) {
              tma2d_mc(dst, map, col, row, bar_full + 8 * stage);
              tma2d_mc(dst + 8192, map, col + 2 * cs, row, bar_full + 8 * stage);
            } else {
              tma2d_mc(dst + 4096, map, col + cs, row, bar_full + 8 * stage);
            }
            if (++stage == NSTAGE) { stage = 0; phase ^= 1; }
          }
        }
      }
      __syncwarp();
    } else {
      const int aw = warp - 9;
      const int hi = f >> 2;
      if (aw == 0) {
        if (lane < 2) hint_wait(&g_f_qkv[m * 8 + 2 + 2 * lane + hi], 16 * ep);
        __syncwarp();
        if (lane == 0) mbar_arrive(bar_d);
        STAMP(20);
        if (lane < 5) hint_wait(lane < 4 ? &g_f_kvt[4 * f + lane] : &g_f_qkv[m * 8 + hi], lane < 4 ? ep : 16 * ep);
        __syncwarp();
        if (lane == 0) mbar_arrive(bar_d + 8);
        STAMP(22);
        if (lane == 0) {
          mbar_wait(bar_o, 0);
          asm volatile("red.release.gpu.global.add.u32 [%0], 1;" ::"l"(&g_f_o[m]) : "memory");
        }
        __syncwarp();
        STAMP(23);
      }
      if (srole && aw == 2) {
        if (lane == 0) {
          flag_wait(&g_f_o[m], 8 * ep);
          asm volatile("fence.proxy.async.global;" ::: "memory");
#pragma unroll 1
          for (int kb = 0; kb < 9; kb++) {
            mbar_wait(bar_xfree + 8 * kb, 0);
            mbar_expect(bar_ofull + 8 * kb, 16384);
            tma2d(sbase + SM_A + kb * 16384, &P.tm_o, kb * 64, m * 128, bar_ofull + 8 * kb);
          }
        }
        __syncwarp();
      }
      const int rbg = m * 8 + f;
#pragma unroll 1
      for (int ch = 0; ch < 2; ch++) {
        if (lane == 0) hint_wait(&g_f_rb[rbg * 8 + ch], 8 * ep);
        __syncwarp();
        STAMPW(9, 24 + 2 * ch);
#pragma unroll 1
        for (int v = ch * 12 + aw * 4; v < ch * 12 + aw * 4 + 4; v++) {
          const uint32_t b0 = __ldg(reinterpret_cast<const uint32_t*>(P.b2 + 16 * v + 2 * t)), b1 = __ldg(reinterpret_cast<const uint32_t*>(P.b2 + 16 * v + 8 + 2 * t));
          uint4 p[8];
          int tries = 0;
          uint32_t bad;
#pragma unroll 1
          do {
            bad = 0;
#pragma unroll
            for (int i = 0; i < 8; i++) p[i] = ld_ll(&g_part[((rbg * 8 + i) * 36 + v) * 32 + lane]);
#pragma unroll
            for (int i = 0; i < 8; i++) bad |= ll_bad(p[i], par);
          } while (__any_sync(0xffffffffu, bad & 1) && ++tries < (1 << 20));
          float gt[8];
          gate_vec(p, b0, b1, gt);
          st_ll(&g_g[(rbg * 24 + v) * 32 + lane], pack_bf16(gt[0], gt[1]), pack_bf16(gt[2], gt[3]), pack_bf16(gt[4], gt[5]), pack_bf16(gt[6], gt[7]), par);
        }
        hint_signal(&g_f_rb[rbg * 8 + 4 + ch]);
        STAMPW(9, 25 + 2 * ch);
      }
    }
    cluster_arrive_relaxed();
    cluster_wait();
  } else {
    asm volatile("bar.sync 1, 384;" ::: "memory");
    asm volatile("setmaxnreg.inc.sync.aligned.u32 224;");
    STAMPW(0, 1);
    const int wg = warp >> 2;
    Ctx c;
    c.full = bar_full;
    c.emb = (lane == 0 && (warp & 3) < 2) ? mapa(bar_empty, (warp & 3) == 0 ? rank : (rank ^ 1)) : 0u;
    c.stage = 0; c.phase = 0; c.prev = ~0u;
    c.dB = (((sbase + SM_B) & 0x3FFFF) >> 4) | ((4096u >> 4) << 16);
    c.dA = (((sbase + SM_A + wg * 8192) & 0x3FFFF) >> 4) | (1u << 16);
    const bool leader = (lane == 0) && ((warp & 3) == 0);

    const int rb = m * 8 + warp;
    const uint32_t bias_t = sbase + SM_BIAS + 8 * t;
    const uint32_t hst = sbase + SM_A + (warp * 16 + (lane & 7) + ((lane >> 3) & 1) * 8) * 128 + (((lane >> 4) ^ (lane & 7)) << 4);
    auto wg_sync = [&]() {
      asm volatile("fence.proxy.async.shared::cta;" ::: "memory");
      if (wg == 0) asm volatile("bar.sync 2, 128;" ::: "memory"); else asm volatile("bar.sync 3, 128;" ::: "memory");
    };
    float A[96], B[96];
#pragma unroll
    for (int i = 0; i < 96; i++) A[i] = 0.f;

#define PART6(ACC, DST, FLG, LAST) \
  if (s == 1) part_groups<0, 2>(ACC, DST, par); if (s == 2) part_groups<2, 4>(ACC, DST, par); if (s == 3) part_groups<4, 6>(ACC, DST, par); \
  if (s == 4) part_groups<6, 8>(ACC, DST, par); if (s == 5) part_groups<8, 10>(ACC, DST, par); if (s == 6) part_groups<10, 12>(ACC, DST, par); \
  if (s == (LAST)) hint_signal(FLG);
#pragma unroll 1
    for (int i = srole; i < 4 + srole; i++) {
      const bool partA = (i == 1 && !srole) || i >= 3;
      {
        const int ln = opaque(lane);
        uint4* dstA = i == 1 ? g_qkvf + (rb * 108 + 18 * f + 6) * 32 + ln : g_part + ((rb * 8 + f) * 36 + (i == 3 ? 0 : 24)) * 32 + ln;
        uint32_t* flgA = i == 1 ? &g_f_qkv[m * 8 + f] : &g_f_rb[rb * 8 + (i == 3 ? 0 : 2)];
        if ((i & 3) == 0) {
          if (i == 4) mbar_wait(bar_ofull, 0);
          issue96(B, c, 0, true);
          retire(c);
          if (i == 4 && leader) mbar_arrive(bar_xfree + 64);
          fence_regs<96>(A);
#pragma unroll
          for (int s = 1; s < 9; s++) {
            if (i == 4) mbar_wait(bar_ofull + 8 * s, 0);
            issue96(B, c, s, false);
            if (partA) { PART6(A, dstA, flgA, 6) }
            retire(c);
          }
        } else {
          issue192(B, c, 0, true);
          retire(c);
          fence_regs<96>(A);
#pragma unroll
          for (int s = 1; s < 9; s++) {
            const int q = s >= 3 ? 2 * (s - 3) : 0;
            float2 bs[4];
            if (s >= 3) lds_bias(bs, bias_t + (192 + 16 * q) * 4);
            issue192(B, c, s);
            if (i == 2) {
              if (s >= 3) {
                const uint4 h0 = gelu_group(&A[8 * q], bs[0], bs[1]), h1 = gelu_group(&A[8 * q + 8], bs[2], bs[3]);
                stsm4((hst ^ ((q & 3) << 5)) + (q >> 2) * 16384, h0);
                stsm4((hst ^ (((q + 1) & 3) << 5)) + (q >> 2) * 16384, h1);
              }
            } else if (partA) { PART6(A, dstA, flgA, 6) }
            retire(c);
          }
        }
      }
      if ((i & 3) != 0) {
        const bool gel = i == 2, d1 = i == 1 + srole, d2 = i == 2 + srole;
        const int rel0 = d1 ? 12 : (d2 ? 9 : 100);
        uint4 pk[4];
        uint32_t W[61];
#pragma unroll
        for (int q = 0; q < 4; q++) pk[q] = make_uint4(0, 0, 0, 0);
#pragma unroll
        for (int q = 0; q < 61; q++) W[q] = 0;
#pragma unroll 1
        for (int s = 9; s < 17; s++) {
          issue192(B, c, s);
          if (gel) {
            if (s == 10) wg_sync();
            if ((s & 1) && s >= 13) {
#pragma unroll
              for (int q = 0; q < 4; q++) stsm4((hst ^ (q << 5)) + ((s - 7) >> 1) * 16384, pk[q]);
            }
            if ((s & 1) && s >= 11) {
              const uint4* hsp = g_hsp + (blockIdx.x * 12 + (s - 11) * 2) * 256 + opaque(tid);
#pragma unroll
              for (int q = 0; q < 4; q++) pk[q] = ldcg128(hsp + q * 256);
            }
          }
          const int rel = s - rel0;
          if (rel == 0 || rel == 2) {
            const int ln = opaque(lane), tt = ln & 3;
            if (rel == 0) mbar_wait(bar_d + (d1 ? 0 : 8), 0);
            int tries = 0;
#pragma unroll 1
            while (true) {
              if (rel == 2) {
                uint32_t bad = W[60];
#pragma unroll
                for (int q = 0; q < 12; q++) if ((q % 3) != 2 || tt == 0) bad |= (W[2 * q] ^ par) | (d1 ? W[24 + 2 * q] ^ par : 0u);
                if (!__any_sync(0xffffffffu, bad & 1) || ++tries > (1 << 20)) break;
              }
              const uint32_t* qf = reinterpret_cast<const uint32_t*>(g_qkvf) + (m * 8 + (d1 ? (warp & 1) * 4 : warp)) * 108 * 128 + (ln >> 2) * 16;
              const int col0 = (d1 ? 576 + (4 * f + (warp >> 1)) * 18 : 72 * f) + 2 * tt;
#pragma unroll
              for (int j = 0; j < 4; j++)
#pragma unroll
                for (int b = 0; b < 3; b++) {
                  const uint32_t* p = qf + (d1 ? j * 108 * 128 : 0) + coloff(col0 + (d1 ? 0 : 18 * j) + 8 * b);
                  const uint2 kk = ld_ll64(p);
                  W[6 * j + 2 * b] = kk.x; W[6 * j + 2 * b + 1] = kk.y;
                  if (d1) { const uint2 vv = ld_ll64(p + 36 * 128); W[24 + 6 * j + 2 * b] = vv.x; W[24 + 6 * j + 2 * b + 1] = vv.y; }
                }
              if (!d1) {
                uint32_t bad = 0;
#pragma unroll
                for (int hh = 0; hh < 4; hh++)
#pragma unroll
                  for (int j = 0; j < 5; j++) {
                    const uint4 kv = ld_ll(&g_kvt[((4 * f + hh) * 5 + j) * 32 + ln]);
                    W[24 + 9 * hh + 2 * j] = kv.y;
                    if (j < 4) W[24 + 9 * hh + 2 * j + 1] = kv.w;
                    bad |= ll_bad(kv, par);
                  }
                W[60] = bad;
              }
              if (rel == 0) break;
            }
            if (rel == 2) {
#pragma unroll
              for (int q = 0; q < 24; q++) W[q] = phi2(W[q]);
              if (tt != 0) {
#pragma unroll
                for (int j = 0; j < 4; j++) W[6 * j + 4] = W[6 * j + 5] = 0u;
              }
            }
          }
          if (rel == 3 && d1) {
            if (t != 0) {
#pragma unroll
              for (int j = 0; j < 4; j++) W[24 + 6 * j + 4] = W[24 + 6 * j + 5] = (t == 1 ? 0x00003f80u : 0u);
            }
#pragma unroll
            for (int q = 0; q < 48; q++) W[q] = movmat(W[q]);
          }
          if (rel == 4) {
            wg_wait<0>();
            asm volatile("bar.sync 4, 256;" ::: "memory");
            if (d1) {
              float c0[3][4], c1[3][4];
#pragma unroll
              for (int j = 0; j < 3; j++) { c0[j][0] = c0[j][1] = c0[j][2] = c0[j][3] = 0.f; c1[j][0] = c1[j][1] = c1[j][2] = c1[j][3] = 0.f; }
#pragma unroll
              for (int ks = 0; ks < 4; ks++)
#pragma unroll
                for (int j = 0; j < 3; j++) {
                  mma16816(c0[j], W[24 + 6 * ks], W[24 + 6 * ks + 2], W[24 + 6 * ks + 1], W[24 + 6 * ks + 3], W[6 * ks + 2 * j], W[6 * ks + 2 * j + 1]);
                  mma16816(c1[j], W[24 + 6 * ks + 4], 0u, W[24 + 6 * ks + 5], 0u, W[6 * ks + 2 * j], W[6 * ks + 2 * j + 1]);
                }
              const int head = 4 * f + (warp >> 1);
              uint4* dst = &g_kvp[((head * 32 + m * 2 + (warp & 1)) * 5) * 32 + opaque(lane)];
#pragma unroll
              for (int j = 0; j < 3; j++) st_ll(dst + j * 32, __float_as_uint(c0[j][0]), __float_as_uint(c0[j][1]), __float_as_uint(c0[j][2]), __float_as_uint(c0[j][3]), par);
              st_ll(dst + 96, __float_as_uint(c1[0][0]), __float_as_uint(c1[0][1]), __float_as_uint(c1[1][0]), __float_as_uint(c1[1][1]), par);
              st_ll(dst + 128, __float_as_uint(c1[2][0]), __float_as_uint(c1[2][1]), 0u, 0u, par);
              hint_signal(&g_f_kvp[head]);
              STAMPW(0, 21);
            } else {
              float cc[4][3][4];
#pragma unroll
              for (int hh = 0; hh < 4; hh++)
#pragma unroll
                for (int e = 0; e < 3; e++) {
                  cc[hh][e][0] = cc[hh][e][1] = cc[hh][e][2] = cc[hh][e][3] = 0.f;
                  mma16816(cc[hh][e], W[6 * hh], W[6 * hh + 1], W[6 * hh + 2], W[6 * hh + 3], W[24 + 9 * hh + 2 * e], W[24 + 9 * hh + 2 * e + 1]);
                  mma16816(cc[hh][e], W[6 * hh + 4], W[6 * hh + 5], 0u, 0u, W[24 + 9 * hh + 6 + e], 0u);
                }
#pragma unroll
              for (int hh = 0; hh < 4; hh++) {
                W[48 + 2 * hh] = __float_as_uint(__shfl_sync(0xffffffffu, cc[hh][2][0], (lane & ~3) | 1));
                W[49 + 2 * hh] = __float_as_uint(__shfl_sync(0xffffffffu, cc[hh][2][2], (lane & ~3) | 1));
              }
#pragma unroll
              for (int q = 0; q < 48; q++) W[q] = __float_as_uint(cc[q / 12][(q % 12) / 4][q % 4]);
            }
            asm volatile("bar.sync 4, 256;" ::: "memory");
          }
          if (rel == 5) {
            const int ln = opaque(lane);
            __nv_bfloat16* po = g_o + (rb * 16 + (ln >> 2)) * D_ + 72 * f + 2 * (ln & 3);
#pragma unroll
            for (int hh = 0; hh < 4; hh++) {
              const float r0 = __fdividef(1.f, __uint_as_float(W[48 + 2 * hh]) + 1e-6f), r1 = __fdividef(1.f, __uint_as_float(W[49 + 2 * hh]) + 1e-6f);
#pragma unroll
              for (int e = 0; e < 3; e++) {
                const uint32_t* w = &W[12 * hh + 4 * e];
                if (e < 2 || (ln & 3) == 0) {
                  *reinterpret_cast<uint32_t*>(po + 18 * hh + 8 * e) = pack_bf16(__uint_as_float(w[0]) * r0, __uint_as_float(w[1]) * r0);
                  *reinterpret_cast<uint32_t*>(po + 8 * D_ + 18 * hh + 8 * e) = pack_bf16(__uint_as_float(w[2]) * r1, __uint_as_float(w[3]) * r1);
                }
              }
            }
            asm volatile("fence.proxy.async.global;" ::: "memory");
            __syncwarp();
            if (ln == 0) mbar_arrive(bar_o);
          }
          retire(c);
        }
        issue192(B, c, 17);
        if (gel) {
#pragma unroll
          for (int q = 0; q < 4; q++) stsm4((hst ^ (q << 5)) + 5 * 16384, pk[q]);
        }
        retire(c);
      }
      STAMPW(0, 2 + 2 * i); WSTAMP(2 + 2 * i);
      {
        const int ln = opaque(lane);
        const bool gel = (i == 1) || (i == 2);
        uint4* dstB = i == 0 ? g_qkvf + (rb * 108 + 18 * f) * 32 + ln
                             : (i == 1 ? g_hsp + blockIdx.x * 12 * 256 + warp * 32 + ln : (i == 3 ? g_part + ((rb * 8 + f) * 36 + 12) * 32 + ln : g_s2 + (rb * 12 + 6 * (f - 6)) * 32 + ln));
        uint32_t* flgB = i == 0 ? &g_f_qkv[m * 8 + f] : &g_f_rb[rb * 8 + (i == 3 ? 1 : 3)];
        const bool xf = i == 3 && srole && leader;
        const uint32_t bsa = bias_t + (i == 1 ? 0 : 384 * 4);
        issue192(A, c, 0, true);
        retire(c);
        fence_regs<96>(B);
#pragma unroll
        for (int s = 1; s < 7; s++) {
          const int q = 2 * (s - 1);
          float2 bs[4];
          lds_bias(bs, bsa + 64 * q);
          issue192(A, c, s);
          if (gel) {
            const uint4 h0 = gelu_group(&B[8 * q], bs[0], bs[1]), h1 = gelu_group(&B[8 * q + 8], bs[2], bs[3]);
            if (i == 1) { dstB[q * 256] = h0; dstB[(q + 1) * 256] = h1; }
            else {
              stsm4((hst ^ ((q & 3) << 5)) + (6 + (q >> 2)) * 16384, h0);
              stsm4((hst ^ (((q + 1) & 3) << 5)) + (6 + (q >> 2)) * 16384, h1);
              if (s == 4) wg_sync();
            }
          } else if (s <= 3 || i == 3) { PART6(B, dstB, flgB, i == 3 ? 6 : 3) }
          retire(c);
          if ((s & 1) == 0 && xf) mbar_arrive(bar_xfree + 4 * s - 8);
        }
#pragma unroll 1
        for (int s = 7; s < 17; s++) {
          issue192(A, c, s);
          if (s == 9 && i == 2) wg_sync();
          retire(c);
          if ((s & 1) == 0 && xf) mbar_arrive(bar_xfree + 4 * s - 8);
        }
        issue192(A, c, 17);
        retire(c);
      }
      STAMPW(0, 3 + 2 * i); WSTAMP(3 + 2 * i);
    }

    const size_t r0 = (size_t)(rb * 16 + g) * D_ + 2 * t;
    if (srole) {
      const int cb = 192 * (f - 6);
      uint32_t xx[48];
      uint4 gg[12];
#pragma unroll
      for (int q = 0; q < 12; q++) {
        xx[4 * q + 0] = __ldg(reinterpret_cast<const uint32_t*>(P.x + r0 + cb + 16 * q));
        xx[4 * q + 1] = __ldg(reinterpret_cast<const uint32_t*>(P.x + r0 + 8 * D_ + cb + 16 * q));
        xx[4 * q + 2] = __ldg(reinterpret_cast<const uint32_t*>(P.x + r0 + cb + 16 * q + 8));
        xx[4 * q + 3] = __ldg(reinterpret_cast<const uint32_t*>(P.x + r0 + 8 * D_ + cb + 16 * q + 8));
      }
      if (lane == 0) hint_wait(&g_f_rb[rb * 8 + 4 + (f - 6)], 3 * ep);
      __syncwarp();
      STAMPW(0, 14);
      int tries = 0;
      uint32_t bad;
#pragma unroll 1
      do {
        bad = 0;
#pragma unroll
        for (int q = 0; q < 12; q++) gg[q] = ld_ll(&g_g[(rb * 24 + 12 * (f - 6) + q) * 32 + lane]);
#pragma unroll
        for (int q = 0; q < 12; q++) bad |= ll_bad(gg[q], par);
      } while (__any_sync(0xffffffffu, bad & 1) && ++tries < (1 << 20));
      wg_wait<0>();
      c.release_prev();
      fence_regs<96>(A);
#pragma unroll
      for (int q = 0; q < 12; q++) {
        const uint32_t* gw = reinterpret_cast<const uint32_t*>(&gg[q]);
        uint32_t res[4];
#pragma unroll
        for (int k = 0; k < 4; k++)
          res[k] = pack_bf16(fmaf(A[8 * q + 2 * k], bf_lo(gw[k]), bf_lo(xx[4 * q + k])), fmaf(A[8 * q + 2 * k + 1], bf_hi(gw[k]), bf_hi(xx[4 * q + k])));
        *reinterpret_cast<uint32_t*>(P.out + r0 + cb + 16 * q) = res[0];
        *reinterpret_cast<uint32_t*>(P.out + r0 + 8 * D_ + cb + 16 * q) = res[1];
        *reinterpret_cast<uint32_t*>(P.out + r0 + cb + 16 * q + 8) = res[2];
        *reinterpret_cast<uint32_t*>(P.out + r0 + 8 * D_ + cb + 16 * q + 8) = res[3];
      }
    } else {
      wg_wait<0>();
      c.release_prev();
      fence_regs<96>(A);
      part_groups<0, 12>(A, g_part + ((rb * 8 + f) * 36 + 24) * 32 + lane, par);
      hint_signal(&g_f_rb[rb * 8 + 2]);
      STAMPW(0, 12);
      const int cb = 384 + 32 * f;
      uint32_t xx[8], bb[4];
#pragma unroll
      for (int j = 0; j < 2; j++) {
        xx[4 * j + 0] = __ldg(reinterpret_cast<const uint32_t*>(P.x + r0 + cb + 16 * j));
        xx[4 * j + 1] = __ldg(reinterpret_cast<const uint32_t*>(P.x + r0 + 8 * D_ + cb + 16 * j));
        xx[4 * j + 2] = __ldg(reinterpret_cast<const uint32_t*>(P.x + r0 + cb + 16 * j + 8));
        xx[4 * j + 3] = __ldg(reinterpret_cast<const uint32_t*>(P.x + r0 + 8 * D_ + cb + 16 * j + 8));
        bb[2 * j] = __ldg(reinterpret_cast<const uint32_t*>(P.b2 + cb + 16 * j + 2 * t));
        bb[2 * j + 1] = __ldg(reinterpret_cast<const uint32_t*>(P.b2 + cb + 16 * j + 8 + 2 * t));
      }
      if (lane < 2) hint_wait(&g_f_rb[rb * 8 + 2 + lane], (lane == 0 ? 8u : 2u) * ep);
      __syncwarp();
      STAMPW(0, 14);
      uint4 p[2][8], sv[2];
      int tries = 0;
      uint32_t bad;
#pragma unroll 1
      do {
        bad = 0;
#pragma unroll
        for (int j = 0; j < 2; j++) {
#pragma unroll
          for (int i = 0; i < 8; i++) p[j][i] = ld_ll(&g_part[((rb * 8 + i) * 36 + 24 + 2 * f + j) * 32 + lane]);
          sv[j] = ld_ll(&g_s2[(rb * 12 + 2 * f + j) * 32 + lane]);
        }
#pragma unroll
        for (int j = 0; j < 2; j++) {
#pragma unroll
          for (int i = 0; i < 8; i++) bad |= ll_bad(p[j][i], par);
          bad |= ll_bad(sv[j], par);
        }
      } while (__any_sync(0xffffffffu, bad & 1) && ++tries < (1 << 20));
#pragma unroll
      for (int j = 0; j < 2; j++) {
        float gt[8];
        gate_vec(p[j], bb[2 * j], bb[2 * j + 1], gt);
        const uint32_t* sw = reinterpret_cast<const uint32_t*>(&sv[j]);
        uint32_t res[4];
#pragma unroll
        for (int k = 0; k < 4; k++) res[k] = pack_bf16(fmaf(bf_lo(sw[k]), gt[2 * k], bf_lo(xx[4 * j + k])), fmaf(bf_hi(sw[k]), gt[2 * k + 1], bf_hi(xx[4 * j + k])));
        *reinterpret_cast<uint32_t*>(P.out + r0 + cb + 16 * j) = res[0];
        *reinterpret_cast<uint32_t*>(P.out + r0 + 8 * D_ + cb + 16 * j) = res[1];
        *reinterpret_cast<uint32_t*>(P.out + r0 + cb + 16 * j + 8) = res[2];
        *reinterpret_cast<uint32_t*>(P.out + r0 + 8 * D_ + cb + 16 * j + 8) = res[3];
      }
    }
    STAMPW(0, 15);
    cluster_arrive_relaxed();
    cluster_wait();
    STAMPW(0, 16);
    if (tid == 0) g_epoch[blockIdx.x] = ep;
  }
}

typedef CUresult (*EncFn)(CUtensorMap*, CUtensorMapDataType, cuuint32_t, void*, const cuuint64_t*, const cuuint64_t*, const cuuint32_t*, const cuuint32_t*,
                          CUtensorMapInterleave, CUtensorMapSwizzle, CUtensorMapL2promotion, CUtensorMapFloatOOBfill);

void make_map(EncFn enc, CUtensorMap* tm, const void* ptr, int rows, int cols, int box_rows, bool sw64 = false) {
  cuuint64_t gd[2] = {(cuuint64_t)cols, (cuuint64_t)rows};
  cuuint64_t gs[1] = {(cuuint64_t)cols * 2};
  cuuint32_t bx[2] = {sw64 ? 32u : 64u, (cuuint32_t)box_rows};
  cuuint32_t es[2] = {1, 1};
  enc(tm, CU_TENSOR_MAP_DATA_TYPE_BFLOAT16, 2, const_cast<void*>(ptr), gd, gs, bx, es, CU_TENSOR_MAP_INTERLEAVE_NONE, sw64 ? CU_TENSOR_MAP_SWIZZLE_64B : CU_TENSOR_MAP_SWIZZLE_128B,
      CU_TENSOR_MAP_L2_PROMOTION_L2_256B, CU_TENSOR_MAP_FLOAT_OOB_FILL_NONE);
}

}

extern "C" void kernel_launch(void* const* d_in, const int* in_sizes, int n_in, void* d_out, int out_size) {
  (void)in_sizes; (void)n_in; (void)out_size;
  static EncFn enc = nullptr;
  static void* o_ptr = nullptr;
  if (!enc) {
    void* fn = nullptr; cudaDriverEntryPointQueryResult q;
    cudaGetDriverEntryPoint("cuTensorMapEncodeTiled", &fn, cudaEnableDefault, &q);
    enc = (EncFn)fn;
    cudaFuncSetAttribute(fused_kernel, cudaFuncAttributeMaxDynamicSharedMemorySize, SMEM_BYTES);
    cudaGetSymbolAddress(&o_ptr, g_o);
  }
  Params P;
  P.x = (const __nv_bfloat16*)d_in[0];
  P.wqkv = (const __nv_bfloat16*)d_in[1];
  P.wo = (const __nv_bfloat16*)d_in[2];
  P.w1 = (const __nv_bfloat16*)d_in[4];
  P.b1 = (const __nv_bfloat16*)d_in[5];
  P.w2 = (const __nv_bfloat16*)d_in[6];
  P.b2 = (const __nv_bfloat16*)d_in[7];
  P.out = (__nv_bfloat16*)d_out;
  make_map(enc, &P.tm_wqkv, P.wqkv, D_, Q3_, 32);
  make_map(enc, &P.tm_w1, P.w1, D_, F_, 32);
  make_map(enc, &P.tm_w2, P.w2, F_, D_, 32);
  make_map(enc, &P.tm_wo, P.wo, D_, D_, 32);
  make_map(enc, &P.tm_wqkv64, P.wqkv, D_, Q3_, 64, true);
  make_map(enc, &P.tm_wo64, P.wo, D_, D_, 64, true);
  make_map(enc, &P.tm_o, o_ptr, S_, D_, 128);
  make_map(enc, &P.tm_x, P.x, S_, D_, 32);
  fused_kernel<<<NCTAS, NTHREADS, SMEM_BYTES, cudaStreamPerThread>>>(P);
}
```

```cpp
#include <cuda_runtime.h>
#include <cuda.h>
#include <cuda_bf16.h>
#include <stdint.h>

namespace {

constexpr int S_ = 2048, D_ = 576, F_ = 4608, Q3_ = 1728;
constexpr int NSTAGE = 6, STAGE_BYTES = 12288;
constexpr int SM_A = 0, SM_B = 147456, SM_BIAS = SM_B + NSTAGE * STAGE_BYTES, SM_RSTD = SM_BIAS + 3072, SM_BAR = SM_RSTD + 1024;
constexpr int SMEM_BYTES = SM_BAR + 320;
constexpr int NTHREADS = 384;
constexpr int NCTAS = 132;

__device__ uint4 g_qkvf[(128 * 108 + 1) * 32];
__device__ __align__(1024) __nv_bfloat16 g_o[S_ * D_];
__device__ uint4 g_kvp[32 * 32 * 5 * 32];
__device__ uint4 g_kvt[32 * 5 * 32];
__device__ uint4 g_part[128 * 8 * 36 * 32];
__device__ uint4 g_s2[128 * 12 * 32];
__device__ uint4 g_g[128 * 24 * 32];
__device__ uint4 g_hsp[128 * 12 * 256];
__device__ uint32_t g_f_qkv[16 * 8];
__device__ uint32_t g_f_kvp[32];
__device__ uint32_t g_f_kvt[32];
__device__ uint32_t g_f_o[16];
__device__ uint32_t g_f_rb[128 * 8];
__device__ uint2 g_stat[S_];
__device__ uint32_t g_epoch[NCTAS];

#define STAMP(i)
#define STAMPW(w, i)
#define WSTAMP(i)
__device__ __forceinline__ uint32_t smem_u32(const void* p) { return (uint32_t)__cvta_generic_to_shared(p); }
__device__ __forceinline__ void mbar_init(uint32_t a, int c) { asm volatile("mbarrier.init.shared::cta.b64 [%0], %1;" ::"r"(a), "r"(c)); }
__device__ __forceinline__ void mbar_expect(uint32_t a, uint32_t b) { asm volatile("mbarrier.arrive.expect_tx.shared::cta.b64 _, [%0], %1;" ::"r"(a), "r"(b) : "memory"); }
__device__ __forceinline__ void mbar_arrive(uint32_t a) { asm volatile("mbarrier.arrive.shared::cta.b64 _, [%0];" ::"r"(a) : "memory"); }
__device__ __forceinline__ void mbar_arrive_cl(uint32_t a) { asm volatile("mbarrier.arrive.shared::cluster.b64 _, [%0];" ::"r"(a) : "memory"); }
__device__ __forceinline__ uint32_t mapa(uint32_t a, uint32_t cta) { uint32_t r; asm volatile("mapa.shared::cluster.u32 %0, %1, %2;" : "=r"(r) : "r"(a), "r"(cta)); return r; }
__device__ __forceinline__ void mbar_wait(uint32_t a, uint32_t ph) {
  uint32_t ok; int it = 0;
#pragma unroll 1
  do {
    asm volatile("{.reg .pred p; mbarrier.try_wait.parity.shared::cta.b64 p, [%1], %2; selp.u32 %0,1,0,p;}" : "=r"(ok) : "r"(a), "r"(ph) : "memory");
  } while (!ok && ++it < (1 << 18));
}
__device__ __forceinline__ void tma2d(uint32_t dst, const CUtensorMap* m, int c0, int c1, uint32_t bar) {
  asm volatile("cp.async.bulk.tensor.2d.shared::cluster.global.mbarrier::complete_tx::bytes [%0], [%1, {%3,%4}], [%2];" ::"r"(dst), "l"(m), "r"(bar), "r"(c0), "r"(c1) : "memory");
}
__device__ __forceinline__ void tma2d_mc(uint32_t dst, const CUtensorMap* m, int c0, int c1, uint32_t bar) {
  asm volatile("cp.async.bulk.tensor.2d.shared::cluster.global.mbarrier::complete_tx::bytes.multicast::cluster [%0], [%1, {%3,%4}], [%2], %5;" ::"r"(dst), "l"(m), "r"(bar), "r"(c0), "r"(c1), "h"((uint16_t)3) : "memory");
}
__device__ __forceinline__ void cluster_arrive_relaxed() { asm volatile("barrier.cluster.arrive.relaxed.aligned;" ::: "memory"); }
__device__ __forceinline__ void cluster_wait() { asm volatile("barrier.cluster.wait.acquire.aligned;" ::: "memory"); }
__device__ __forceinline__ void wg_fence() { asm volatile("wgmma.fence.sync.aligned;" ::: "memory"); }
__device__ __forceinline__ void wg_commit() { asm volatile("wgmma.commit_group.sync.aligned;" ::: "memory"); }
template <int n> __device__ __forceinline__ void wg_wait() { asm volatile("wgmma.wait_group.sync.aligned %0;" ::"n"(n) : "memory"); }
__device__ __forceinline__ uint32_t ld_acquire(const uint32_t* p) { uint32_t v; asm volatile("ld.acquire.gpu.global.u32 %0, [%1];" : "=r"(v) : "l"(p) : "memory"); return v; }
__device__ __forceinline__ void flag_wait(const uint32_t* p, uint32_t target) {
  int it = 0;
#pragma unroll 1
  while ((int)(ld_acquire(p) - target) < 0 && ++it < (1 << 21)) __nanosleep(40);
}
__device__ __forceinline__ void hint_signal(uint32_t* p) {
  if ((threadIdx.x & 31) == 0) asm volatile("red.relaxed.gpu.global.add.u32 [%0], 1;" ::"l"(p) : "memory");
}
__device__ __forceinline__ void hint_wait(const uint32_t* p, uint32_t target) {
  int it = 0; uint32_t v;
#pragma unroll 1
  do { asm volatile("ld.relaxed.gpu.global.u32 %0, [%1];" : "=r"(v) : "l"(p) : "memory"); if ((int)(v - target) >= 0) break; __nanosleep(32); } while (++it < (1 << 21));
}
__device__ __forceinline__ uint32_t tag(uint32_t x, uint32_t par) { uint32_t r; asm("lop3.b32 %0, %1, 0xfffffffe, %2, 0xea;" : "=r"(r) : "r"(x), "r"(par)); return r; }
__device__ __forceinline__ void st_ll(uint4* p, uint32_t x, uint32_t y, uint32_t z, uint32_t w, uint32_t par) {
  asm volatile("{.reg .b64 a, b; mov.b64 a, {%1,%2}; mov.b64 b, {%3,%4}; st.relaxed.gpu.global.v2.b64 [%0], {a, b};}"
               ::"l"(p), "r"(tag(x, par)), "r"(y), "r"(tag(z, par)), "r"(w) : "memory");
}
__device__ __forceinline__ uint4 ld_ll(const uint4* p) {
  uint4 v;
  asm volatile("{.reg .b64 a, b; ld.relaxed.gpu.global.v2.b64 {a, b}, [%4]; mov.b64 {%0,%1}, a; mov.b64 {%2,%3}, b;}"
               : "=r"(v.x), "=r"(v.y), "=r"(v.z), "=r"(v.w) : "l"(p) : "memory");
  return v;
}
__device__ __forceinline__ uint2 ld_ll64(const uint32_t* p) {
  uint2 v;
  asm volatile("{.reg .b64 a; ld.relaxed.gpu.global.b64 a, [%2]; mov.b64 {%0,%1}, a;}" : "=r"(v.x), "=r"(v.y) : "l"(p) : "memory");
  return v;
}
__device__ __forceinline__ void ll_chk(uint32_t& bad, uint32_t a, uint32_t b, uint32_t par) {
  uint32_t u; asm("lop3.b32 %0, %1, %2, %3, 0x7e;" : "=r"(u) : "r"(a), "r"(b), "r"(par));
  asm("or.b32 %0, %0, %1;" : "+r"(bad) : "r"(u));
}
__device__ __forceinline__ uint32_t hadd2(uint32_t a, uint32_t b) { uint32_t d; asm("add.rn.bf16x2 %0, %1, %2;" : "=r"(d) : "r"(a), "r"(b)); return d; }
__device__ __forceinline__ uint32_t hfma2(uint32_t a, uint32_t b, uint32_t c) { uint32_t d; asm("fma.rn.bf16x2 %0, %1, %2, %3;" : "=r"(d) : "r"(a), "r"(b), "r"(c)); return d; }
__device__ __forceinline__ uint32_t pack_bf16(float lo, float hi) { uint32_t r; asm("cvt.rn.bf16x2.f32 %0, %1, %2;" : "=r"(r) : "f"(hi), "f"(lo)); return r; }
__device__ __forceinline__ float bf_lo(uint32_t v) { return __uint_as_float(v << 16); }
__device__ __forceinline__ float bf_hi(uint32_t v) { return __uint_as_float(v & 0xffff0000u); }
__device__ __forceinline__ float tanh_fast(float x) { float r; asm("tanh.approx.f32 %0, %1;" : "=f"(r) : "f"(x)); return r; }
__device__ __forceinline__ uint32_t movmat(uint32_t a) { uint32_t d; asm volatile("movmatrix.sync.aligned.m8n8.trans.b16 %0, %1;" : "=r"(d) : "r"(a)); return d; }
__device__ __forceinline__ void mma16816(float* c, uint32_t a0, uint32_t a1, uint32_t a2, uint32_t a3, uint32_t b0, uint32_t b1) {
  asm volatile("mma.sync.aligned.m16n8k16.row.col.f32.bf16.bf16.f32 {%0,%1,%2,%3}, {%4,%5,%6,%7}, {%8,%9}, {%0,%1,%2,%3};"
               : "+f"(c[0]), "+f"(c[1]), "+f"(c[2]), "+f"(c[3]) : "r"(a0), "r"(a1), "r"(a2), "r"(a3), "r"(b0), "r"(b1));
}
__device__ __forceinline__ uint4 ldcg128(const void* p) { uint4 v; asm volatile("ld.global.cg.v4.u32 {%0,%1,%2,%3}, [%4];" : "=r"(v.x), "=r"(v.y), "=r"(v.z), "=r"(v.w) : "l"(p) : "memory"); return v; }

template <int N> __device__ __forceinline__ void wgmma_ss(float* d, uint64_t da, uint64_t db, int sc);
template <int N> __device__ __forceinline__ void wgmma_rs(float* d, const uint32_t* a, uint64_t db, int sc);
template <> __device__ __forceinline__ void wgmma_ss<96>(float* d, uint64_t da, uint64_t db, int sc) {
  asm volatile("{.reg .pred p; setp.ne.b32 p, %50, 0; wgmma.mma_async.sync.aligned.m64n96k16.f32.bf16.bf16 {%0, %1, %2, %3, %4, %5, %6, %7, %8, %9, %10, %11, %12, %13, %14, %15, %16, %17, %18, %19, %20, %21, %22, %23, %24, %25, %26, %27, %28, %29, %30, %31, %32, %33, %34, %35, %36, %37, %38, %39, %40, %41, %42, %43, %44, %45, %46, %47}, %48, %49, p, 1, 1, 0, 1;}"
   : "+f"(d[0]), "+f"(d[1]), "+f"(d[2]), "+f"(d[3]), "+f"(d[4]), "+f"(d[5]), "+f"(d[6]), "+f"(d[7]), "+f"(d[8]), "+f"(d[9]), "+f"(d[10]), "+f"(d[11]), "+f"(d[12]), "+f"(d[13]), "+f"(d[14]), "+f"(d[15]), "+f"(d[16]), "+f"(d[17]), "+f"(d[18]), "+f"(d[19]), "+f"(d[20]), "+f"(d[21]), "+f"(d[22]), "+f"(d[23]), "+f"(d[24]), "+f"(d[25]), "+f"(d[26]), "+f"(d[27]), "+f"(d[28]), "+f"(d[29]), "+f"(d[30]), "+f"(d[31]), "+f"(d[32]), "+f"(d[33]), "+f"(d[34]), "+f"(d[35]), "+f"(d[36]), "+f"(d[37]), "+f"(d[38]), "+f"(d[39]), "+f"(d[40]), "+f"(d[41]), "+f"(d[42]), "+f"(d[43]), "+f"(d[44]), "+f"(d[45]), "+f"(d[46]), "+f"(d[47]) : "l"(da), "l"(db), "r"(sc));
}
template <> __device__ __forceinline__ void wgmma_ss<192>(float* d, uint64_t da, uint64_t db, int sc) {
  asm volatile("{.reg .pred p; setp.ne.b32 p, %98, 0; wgmma.mma_async.sync.aligned.m64n192k16.f32.bf16.bf16 {%0, %1, %2, %3, %4, %5, %6, %7, %8, %9, %10, %11, %12, %13, %14, %15, %16, %17, %18, %19, %20, %21, %22, %23, %24, %25, %26, %27, %28, %29, %30, %31, %32, %33, %34, %35, %36, %37, %38, %39, %40, %41, %42, %43, %44, %45, %46, %47, %48, %49, %50, %51, %52, %53, %54, %55, %56, %57, %58, %59, %60, %61, %62, %63, %64, %65, %66, %67, %68, %69, %70, %71, %72, %73, %74, %75, %76, %77, %78, %79, %80, %81, %82, %83, %84, %85, %86, %87, %88, %89, %90, %91, %92, %93, %94, %95}, %96, %97, p, 1, 1, 0, 1;}"
   : "+f"(d[0]), "+f"(d[1]), "+f"(d[2]), "+f"(d[3]), "+f"(d[4]), "+f"(d[5]), "+f"(d[6]), "+f"(d[7]), "+f"(d[8]), "+f"(d[9]), "+f"(d[10]), "+f"(d[11]), "+f"(d[12]), "+f"(d[13]), "+f"(d[14]), "+f"(d[15]), "+f"(d[16]), "+f"(d[17]), "+f"(d[18]), "+f"(d[19]), "+f"(d[20]), "+f"(d[21]), "+f"(d[22]), "+f"(d[23]), "+f"(d[24]), "+f"(d[25]), "+f"(d[26]), "+f"(d[27]), "+f"(d[28]), "+f"(d[29]), "+f"(d[30]), "+f"(d[31]), "+f"(d[32]), "+f"(d[33]), "+f"(d[34]), "+f"(d[35]), "+f"(d[36]), "+f"(d[37]), "+f"(d[38]), "+f"(d[39]), "+f"(d[40]), "+f"(d[41]), "+f"(d[42]), "+f"(d[43]), "+f"(d[44]), "+f"(d[45]), "+f"(d[46]), "+f"(d[47]), "+f"(d[48]), "+f"(d[49]), "+f"(d[50]), "+f"(d[51]), "+f"(d[52]), "+f"(d[53]), "+f"(d[54]), "+f"(d[55]), "+f"(d[56]), "+f"(d[57]), "+f"(d[58]), "+f"(d[59]), "+f"(d[60]), "+f"(d[61]), "+f"(d[62]), "+f"(d[63]), "+f"(d[64]), "+f"(d[65]), "+f"(d[66]), "+f"(d[67]), "+f"(d[68]), "+f"(d[69]), "+f"(d[70]), "+f"(d[71]), "+f"(d[72]), "+f"(d[73]), "+f"(d[74]), "+f"(d[75]), "+f"(d[76]), "+f"(d[77]), "+f"(d[78]), "+f"(d[79]), "+f"(d[80]), "+f"(d[81]), "+f"(d[82]), "+f"(d[83]), "+f"(d[84]), "+f"(d[85]), "+f"(d[86]), "+f"(d[87]), "+f"(d[88]), "+f"(d[89]), "+f"(d[90]), "+f"(d[91]), "+f"(d[92]), "+f"(d[93]), "+f"(d[94]), "+f"(d[95]) : "l"(da), "l"(db), "r"(sc));
}

__device__ __forceinline__ uint64_t desc64(uint32_t lo, uint32_t hi) { uint64_t d; asm("mov.b64 %0, {%1, %2};" : "=l"(d) : "r"(lo), "r"(hi)); return d; }
constexpr uint32_t DESC_HI = (1024u >> 4) | (1u << 30);
constexpr uint32_t DESC_HI64 = (512u >> 4) | (2u << 30);
template <int n> __device__ __forceinline__ void fence_regs(float* a) {
#pragma unroll
  for (int i = 0; i < n; i++) asm volatile("" : "+f"(a[i])::"memory");
}

struct Ctx {
  uint32_t full;
  uint32_t emb;
  bool sig;
  uint32_t stage, phase, prev;
  uint32_t dB, dA;
  __device__ __forceinline__ void release_prev() { if (sig && prev != ~0u) mbar_arrive_cl(emb + prev); }
  __device__ __forceinline__ void wait_full() {
    mbar_wait(full + 8 * stage, phase);
    wg_fence();
  }
};

__device__ __forceinline__ void issue192(float* acc, Ctx& c, int s, bool first = false) {
  c.wait_full();
  const uint32_t db = c.dB + c.stage * (STAGE_BYTES >> 4);
  const uint32_t da = c.dA + (s >> 1) * 1024 + (s & 1) * 4;
  wgmma_ss<192>(acc, desc64(da, DESC_HI), desc64(db, DESC_HI), first ? 0 : 1);
  wgmma_ss<192>(acc, desc64(da + 2, DESC_HI), desc64(db + 128, DESC_HI), 1);
  wg_commit();
}
__device__ __forceinline__ void issue96(float* acc, Ctx& c, int s, bool first) {
  c.wait_full();
  const uint32_t db = c.dB + c.stage * (STAGE_BYTES >> 4);
  const uint32_t da = c.dA + s * 1024;
#pragma unroll
  for (int kk = 0; kk < 4; kk++) wgmma_ss<96>(acc, desc64(da + 2 * kk, DESC_HI), desc64(db + 64 * kk, DESC_HI64), (first && kk == 0) ? 0 : 1);
  wg_commit();
}
__device__ __forceinline__ void retire(Ctx& c) {
  wg_wait<1>();
  c.release_prev();
  c.prev = 8 * c.stage;
  if (++c.stage == NSTAGE) { c.stage = 0; c.phase ^= 1; }
}
__device__ __forceinline__ float gelu2(float x) {
  float u = x * fmaf(x * x, 0.0356774081f, 0.7978845608f);
  return fmaf(x, tanh_fast(u), x);
}
__device__ __forceinline__ uint4 gelu_group(const float* a) {
  return make_uint4(pack_bf16(gelu2(a[0]), gelu2(a[1])), pack_bf16(gelu2(a[2]), gelu2(a[3])), pack_bf16(gelu2(a[4]), gelu2(a[5])), pack_bf16(gelu2(a[6]), gelu2(a[7])));
}
__device__ __forceinline__ void lds_bias(float2* b, uint32_t addr) {
#pragma unroll
  for (int j = 0; j < 4; j++) asm volatile("ld.shared.v2.f32 {%0,%1}, [%2];" : "=f"(b[j].x), "=f"(b[j].y) : "r"(addr + 32 * j));
}
__device__ __forceinline__ int opaque(int v) { asm volatile("" : "+r"(v)); return v; }
__device__ __forceinline__ void stsm4(uint32_t addr, uint4 r) {
  asm volatile("stmatrix.sync.aligned.m8n8.x4.shared.b16 [%0], {%1,%2,%3,%4};" ::"r"(addr), "r"(r.x), "r"(r.y), "r"(r.z), "r"(r.w) : "memory");
}
__device__ __forceinline__ float ex2f(float x) { float r; asm("ex2.approx.ftz.f32 %0, %1;" : "=f"(r) : "f"(x)); return r; }
__device__ __forceinline__ float phi(float t) { float e = ex2f(t * 1.4426950408889634f); if (t > 0.f) e = t + 1.f; return e + 1e-6f; }
__device__ __forceinline__ uint32_t phi2(uint32_t w) { return pack_bf16(phi(bf_lo(w)), phi(bf_hi(w))); }
template <int q0, int q1>
__device__ __forceinline__ void part_groups(const float* a, uint4* p, uint32_t par) {
#pragma unroll
  for (int q = q0; q < q1; q++)
    st_ll(p + q * 32, pack_bf16(a[8 * q], a[8 * q + 1]), pack_bf16(a[8 * q + 2], a[8 * q + 3]), pack_bf16(a[8 * q + 4], a[8 * q + 5]), pack_bf16(a[8 * q + 6], a[8 * q + 7]), par);
}
__device__ __forceinline__ float silu(float y) { return __fdividef(y, 1.f + ex2f(y * -1.4426950408889634f)); }
__device__ __forceinline__ void gate_vec(const uint4* p, uint32_t b0, uint32_t b1, float* gt) {
#pragma unroll
  for (int q = 0; q < 4; q++) {
    float lo = 0.f, hi = 0.f;
#pragma unroll
    for (int i = 0; i < 8; i++) { uint32_t w = reinterpret_cast<const uint32_t*>(&p[i])[q]; lo += bf_lo(w); hi += bf_hi(w); }
    const uint32_t bb = q < 2 ? b0 : b1;
    gt[2 * q] = silu(fmaf(lo, 0.5f, bf_lo(bb)));
    gt[2 * q + 1] = silu(fmaf(hi, 0.5f, bf_hi(bb)));
  }
}
__device__ __forceinline__ int coloff(int c) { return (c >> 4) * 128 + ((c & 7) >> 1) * 4 + ((c >> 3) & 1) * 2; }

struct Params {
  CUtensorMap tm_wqkv, tm_w1, tm_w2, tm_wo, tm_wqkv64, tm_wo64, tm_o;
  const __nv_bfloat16 *x, *b1, *b2, *wqkv, *w1, *w2, *wo;
  __nv_bfloat16* out;
};

__global__ void __cluster_dims__(2, 1, 1) __launch_bounds__(NTHREADS, 1) fused_kernel(const __grid_constant__ Params P) {
  extern __shared__ __align__(1024) uint8_t smem[];
  const uint32_t sbase = smem_u32(smem);
  const int tid = threadIdx.x, lane = tid & 31;
  const int warp = __shfl_sync(0xffffffffu, tid >> 5, 0);
  const int g = lane >> 2, t = lane & 3;
  const uint32_t ep = __shfl_sync(0xffffffffu, g_epoch[blockIdx.x], 0) + 1;
  const uint32_t par = ep & 1;
  STAMPW(0, 0);

  if (blockIdx.x >= 128) {
    const int a = blockIdx.x - 128;
    if (warp >= 8 && lane == 0) {
      const int id = a * 4 + (warp - 8);
      constexpr uint32_t CH = 9216 * 2;
      __nanosleep(1500);
#pragma unroll 1
      for (int i = id; i < 612; i += 16) {
        const char* p = i < 288 ? (const char*)P.w1 + (size_t)i * CH : (i < 576 ? (const char*)P.w2 + (size_t)(i - 288) * CH : (const char*)P.wo + (size_t)(i - 576) * CH);
        asm volatile("cp.async.bulk.prefetch.L2.global [%0], %1;" ::"l"(p), "r"(CH) : "memory");
      }
    }
    __syncwarp();
#pragma unroll 1
    for (int u = a * 12 + warp; u < 160; u += 48) {
      const int head = u / 5;
      if (lane == 0) hint_wait(&g_f_kvp[head], 32 * ep);
      __syncwarp();
      STAMPW(0, 1);
      uint4 v[32];
      int tries = 0;
      uint32_t bad;
#pragma unroll 1
      do {
        bad = 0;
#pragma unroll
        for (int j = 0; j < 32; j++) v[j] = ld_ll(&g_kvp[(u * 32 + j) * 32 + lane]);
#pragma unroll
        for (int j = 0; j < 32; j++) ll_chk(bad, v[j].x, v[j].z, par);
      } while (__any_sync(0xffffffffu, bad & 1) && ++tries < (1 << 20));
      float s0 = 0.f, s1 = 0.f, s2 = 0.f, s3 = 0.f;
#pragma unroll
      for (int j = 0; j < 32; j++) { s0 += __uint_as_float(v[j].x); s1 += __uint_as_float(v[j].y); s2 += __uint_as_float(v[j].z); s3 += __uint_as_float(v[j].w); }
      st_ll(&g_kvt[u * 32 + lane], 0u, pack_bf16(s0, s1), 0u, pack_bf16(s2, s3), par);
      hint_signal(&g_f_kvt[head]);
      STAMPW(0, 2);
    }
    __syncthreads();
    if (tid == 0) g_epoch[blockIdx.x] = ep;
    return;
  }

  const int cl = blockIdx.x >> 1, rank = blockIdx.x & 1;
  const int f = cl & 7, m = (cl >> 3) * 2 + rank;
  const int srole = f >= 6 ? 1 : 0;
  const uint32_t bar_full = sbase + SM_BAR, bar_empty = bar_full + 8 * NSTAGE, bar_xfree = bar_empty + 8 * NSTAGE, bar_ofull = bar_xfree + 72,
                 bar_d = bar_ofull + 72, bar_o = bar_d + 16;

  if (tid == 0) {
#pragma unroll 1
    for (int i = 0; i < NSTAGE; i++) { mbar_init(bar_full + 8 * i, 1); mbar_init(bar_empty + 8 * i, 4); }
#pragma unroll 1
    for (int i = 0; i < 9; i++) { mbar_init(bar_xfree + 8 * i, 2); mbar_init(bar_ofull + 8 * i, 1); }
    mbar_init(bar_d, 1); mbar_init(bar_d + 8, 1); mbar_init(bar_o, 8);
    asm volatile("fence.mbarrier_init.release.cluster;" ::: "memory");
  }
  __syncwarp();
  cluster_arrive_relaxed();

  if (warp >= 8) {
    const int srow = m * 128 + f * 16 + (warp - 8) * 4 + (lane >> 3);
    uint4 xs[9];
#pragma unroll
    for (int kb = 0; kb < 9; kb++) xs[kb] = __ldg(reinterpret_cast<const uint4*>(P.x + srow * D_) + (lane & 7) + kb * 8);
    auto stats = [&]() {
      const uint32_t* w = reinterpret_cast<const uint32_t*>(xs);
      float s0 = 0.f, s1 = 0.f;
#pragma unroll
      for (int i = 0; i < 36; i++) { s0 += bf_lo(w[i]); s1 += bf_hi(w[i]); }
      float sum = s0 + s1;
      sum += __shfl_xor_sync(0xffffffffu, sum, 1); sum += __shfl_xor_sync(0xffffffffu, sum, 2); sum += __shfl_xor_sync(0xffffffffu, sum, 4);
      const float mean = sum * (1.f / 576.f);
      s0 = 0.f; s1 = 0.f;
#pragma unroll
      for (int i = 0; i < 36; i++) { const float a = bf_lo(w[i]) - mean, b = bf_hi(w[i]) - mean; s0 = fmaf(a, a, s0); s1 = fmaf(b, b, s1); }
      float sq = s0 + s1;
      sq += __shfl_xor_sync(0xffffffffu, sq, 1); sq += __shfl_xor_sync(0xffffffffu, sq, 2); sq += __shfl_xor_sync(0xffffffffu, sq, 4);
      const float rstd = rsqrtf(sq * (1.f / 576.f) + 1e-5f);
      if ((lane & 7) == 0)
        asm volatile("{.reg .b64 a; mov.b64 a, {%1,%2}; st.relaxed.gpu.global.b64 [%0], a;}" ::"l"(&g_stat[srow]), "r"((__float_as_uint(rstd) & ~1u) | par), "r"(pack_bf16(-mean, -mean)) : "memory");
    };
    stats();
    asm volatile("setmaxnreg.dec.sync.aligned.u32 56;");
    cluster_wait();
    if (warp == 8) {
      if (lane == 0) {
        uint32_t stage = 0, phase = 1;
        const uint32_t sb = sbase + SM_B;
#pragma unroll 1
        for (int tl = 2 * srole; tl < 8 + 2 * srole; tl++) {
          const CUtensorMap* map = tl == 0 ? &P.tm_wqkv64 : (tl == 1 ? &P.tm_wqkv : (tl < 5 ? &P.tm_w1 : (tl < 8 ? &P.tm_w2 : (tl == 8 ? &P.tm_wo64 : &P.tm_wo))));
          const int col = tl < 2 ? 288 * f + 96 * tl : (tl < 5 ? 576 * f + 192 * (tl - 2) : (tl < 8 ? 192 * (tl - 5) : (tl == 8 ? 384 + 96 * (f - 6) : 192 * (f - 6))));
          const bool perm = tl >= 5 && tl < 8;
          const bool z = (tl & 7) == 0;
          const int cs = z ? 32 : 64, rs = z ? 64 : 32, nst = z ? 9 : 18;
#pragma unroll 1
          for (int st = 0; st < nst; st++) {
            int row = st * rs;
            if (perm) row += 576 * f + (st < 12 ? 192 : -384);
            mbar_wait(bar_empty + 8 * stage, phase);
            mbar_expect(bar_full + 8 * stage, 12288);
            const uint32_t dst = sb + stage * STAGE_BYTES;
            if (((st ^ rank) & 1) == 0) {
              tma2d_mc(dst, map, col, row, bar_full + 8 * stage);
              tma2d_mc(dst + 8192, map, col + 2 * cs, row, bar_full + 8 * stage);
            } else {
              tma2d_mc(dst + 4096, map, col + cs, row, bar_full + 8 * stage);
            }
            if (++stage == NSTAGE) { stage = 0; phase ^= 1; }
          }
        }
      }
      __syncwarp();
    } else {
      const int aw = warp - 9;
      const int hi = f >> 2;
      if (aw == 0) {
        if (lane < 2) hint_wait(&g_f_qkv[m * 8 + 2 + 2 * lane + hi], 16 * ep);
        __syncwarp();
        if (lane == 0) mbar_arrive(bar_d);
        STAMP(20);
        if (lane < 5) hint_wait(lane < 4 ? &g_f_kvt[4 * f + lane] : &g_f_qkv[m * 8 + hi], lane < 4 ? 5 * ep : 16 * ep);
        __syncwarp();
        if (lane == 0) mbar_arrive(bar_d + 8);
        STAMP(22);
        if (lane == 0) {
          mbar_wait(bar_o, 0);
          asm volatile("red.release.gpu.global.add.u32 [%0], 1;" ::"l"(&g_f_o[m]) : "memory");
        }
        __syncwarp();
        STAMP(23);
      }
      if (srole && aw == 2) {
        if (lane == 0) {
          flag_wait(&g_f_o[m], 8 * ep);
          asm volatile("fence.proxy.async.global;" ::: "memory");
#pragma unroll 1
          for (int kb = 0; kb < 9; kb++) {
            mbar_wait(bar_xfree + 8 * kb, 0);
            mbar_expect(bar_ofull + 8 * kb, 16384);
            tma2d(sbase + SM_A + kb * 16384, &P.tm_o, kb * 64, m * 128, bar_ofull + 8 * kb);
          }
        }
        __syncwarp();
      }
      const int rbg = m * 8 + f;
#pragma unroll 1
      for (int ch = 0; ch < 2; ch++) {
        if (lane == 0) hint_wait(&g_f_rb[rbg * 8 + ch], 8 * ep);
        __syncwarp();
        STAMPW(9, 24 + 2 * ch);
#pragma unroll 1
        for (int v = ch * 12 + aw * 4; v < ch * 12 + aw * 4 + 4; v++) {
          const uint32_t b0 = __ldg(reinterpret_cast<const uint32_t*>(P.b2 + 16 * v + 2 * t)), b1 = __ldg(reinterpret_cast<const uint32_t*>(P.b2 + 16 * v + 8 + 2 * t));
          uint4 p[8];
          int tries = 0;
          uint32_t bad;
#pragma unroll 1
          do {
            bad = 0;
#pragma unroll
            for (int i = 0; i < 8; i++) p[i] = ld_ll(&g_part[((rbg * 8 + i) * 36 + v) * 32 + lane]);
#pragma unroll
            for (int i = 0; i < 8; i++) ll_chk(bad, p[i].x, p[i].z, par);
          } while (__any_sync(0xffffffffu, bad & 1) && ++tries < (1 << 20));
          float gt[8];
          gate_vec(p, b0, b1, gt);
          st_ll(&g_g[(rbg * 24 + v) * 32 + lane], pack_bf16(gt[0], gt[1]), pack_bf16(gt[2], gt[3]), pack_bf16(gt[4], gt[5]), pack_bf16(gt[6], gt[7]), par);
        }
        hint_signal(&g_f_rb[rbg * 8 + 4 + ch]);
        STAMPW(9, 25 + 2 * ch);
      }
    }
    cluster_arrive_relaxed();
    cluster_wait();
  } else {
    const int wg = warp >> 2;
    {
      const int rs = lane >> 3, j = lane & 7;
      uint4 xv[4][9];
#pragma unroll
      for (int it = 0; it < 4; it++)
#pragma unroll
        for (int kb = 0; kb < 9; kb++) xv[it][kb] = __ldg(reinterpret_cast<const uint4*>(P.x + (m * 128 + warp * 16 + it * 4 + rs) * D_) + j + kb * 8);
      uint32_t bw0 = __ldg(reinterpret_cast<const uint32_t*>(P.b1 + 576 * f) + tid), bw1 = tid < 32 ? __ldg(reinterpret_cast<const uint32_t*>(P.b1 + 576 * f) + 256 + tid) : 0u;
      uint2 st[4];
      int tries = 0;
      uint32_t bad;
#pragma unroll 1
      do {
        bad = 0;
#pragma unroll
        for (int it = 0; it < 4; it++) st[it] = ld_ll64(reinterpret_cast<const uint32_t*>(&g_stat[m * 128 + warp * 16 + it * 4 + rs]));
        ll_chk(bad, st[0].x, st[1].x, par); ll_chk(bad, st[2].x, st[3].x, par);
      } while (__any_sync(0xffffffffu, bad & 1) && ++tries < (1 << 22));
      STAMPW(0, 19);
#pragma unroll
      for (int it = 0; it < 4; it++) {
        const uint32_t nm = st[it].y;
        uint8_t* dst = smem + SM_A + (warp * 16 + it * 4 + rs) * 128 + ((j ^ ((it * 4 + rs) & 7)) << 4);
#pragma unroll
        for (int kb = 0; kb < 9; kb++) {
          const uint4 w = xv[it][kb];
          *reinterpret_cast<uint4*>(dst + kb * 16384) = make_uint4(hadd2(w.x, nm), hadd2(w.y, nm), hadd2(w.z, nm), hadd2(w.w, nm));
        }
        if (j < 2) reinterpret_cast<uint32_t*>(smem + SM_RSTD)[j * 128 + warp * 16 + it * 4 + rs] = j == 0 ? st[it].x : 0x3f800000u;
      }
      reinterpret_cast<float2*>(smem + SM_BIAS)[tid] = make_float2(bf_lo(bw0), bf_hi(bw0));
      if (tid < 128) reinterpret_cast<float2*>(smem + SM_BIAS)[256 + tid] = make_float2(bf_lo(bw1), bf_hi(bw1));
      asm volatile("fence.proxy.async.shared::cta;" ::: "memory");
    }
    asm volatile("setmaxnreg.inc.sync.aligned.u32 224;");
    cluster_wait();
    asm volatile("bar.sync 1, 256;" ::: "memory");
    STAMPW(0, 1);
    Ctx c;
    c.full = bar_full;
    c.emb = __shfl_sync(0xffffffffu, mapa(bar_empty, (warp & 3) == 0 ? rank : (rank ^ 1)), 0);
    c.sig = lane == 0 && (warp & 3) < 2;
    c.stage = 0; c.phase = 0; c.prev = ~0u;
    c.dB = (((sbase + SM_B) & 0x3FFFF) >> 4) | ((4096u >> 4) << 16);
    c.dA = (((sbase + SM_A + wg * 8192) & 0x3FFFF) >> 4) | (1u << 16);
    const bool leader = (lane == 0) && ((warp & 3) == 0);

    const int rb = m * 8 + warp;
    const uint32_t bias_t = sbase + SM_BIAS + 8 * t;
    const uint32_t hst = sbase + SM_A + (warp * 16 + (lane & 7) + ((lane >> 3) & 1) * 8) * 128 + (((lane >> 4) ^ (lane & 7)) << 4);
    auto wg_sync = [&]() {
      asm volatile("fence.proxy.async.shared::cta;" ::: "memory");
      if (wg == 0) asm volatile("bar.sync 2, 128;" ::: "memory"); else asm volatile("bar.sync 3, 128;" ::: "memory");
    };
    float A[96], B[96];
#pragma unroll
    for (int i = 0; i < 96; i++) A[i] = 0.f;

#define SEL16(E, ACC, OFF, HF) float E[16]; _Pragma("unroll") for (int q = 0; q < 16; q++) E[q] = fmaf((HF) ? ACC[48 + (OFF) + q] : ACC[(OFF) + q], (q & 2) ? r1 : r0, (q & 1) ? bs[q >> 2].y : bs[q >> 2].x);
#define LDS_R(SCALED) float r0, r1; asm volatile("ld.shared.f32 %0, [%1];" : "=f"(r0) : "r"(rst + ((SCALED) ? 0 : 512))); asm volatile("ld.shared.f32 %0, [%1];" : "=f"(r1) : "r"(rst + ((SCALED) ? 32 : 544)));
    const uint32_t rst = sbase + SM_RSTD + (warp * 16 + g) * 4;
#pragma unroll 1
    for (int i = srole; i < 4 + srole; i++) {
      const bool partA = (i == 1 && !srole) || i >= 3;
      {
        const int ln = opaque(lane);
        uint4* dstA = i == 1 ? g_qkvf + (rb * 108 + 18 * f + 6) * 32 + ln : g_part + ((rb * 8 + f) * 36 + (i == 3 ? 0 : 24)) * 32 + ln;
        uint32_t* flgA = i == 1 ? &g_f_qkv[m * 8 + f] : &g_f_rb[rb * 8 + (i == 3 ? 0 : 2)];
        if ((i & 3) == 0) {
          if (i == 4) mbar_wait(bar_ofull, 0);
          issue96(B, c, 0, true);
          retire(c);
          if (i == 4 && leader) mbar_arrive(bar_xfree + 64);
          fence_regs<96>(A);
#pragma unroll 1
          for (int s = 1; s < 8; s++) {
            if (i == 4) mbar_wait(bar_ofull + 8 * s, 0);
            issue96(B, c, s, false);
            if (partA) {
              if (s == 1) part_groups<0, 4>(A, dstA, par);
              if (s == 3) part_groups<4, 8>(A, dstA, par);
              if (s == 5) { part_groups<8, 12>(A, dstA, par); hint_signal(flgA); }
            }
            retire(c);
          }
          if (i == 4) mbar_wait(bar_ofull + 64, 0);
          issue96(B, c, 8, false);
          retire(c);
        } else {
          issue192(B, c, 0, true);
          retire(c);
          fence_regs<96>(A);
          LDS_R(i <= 2)
          int s = 1;
          if (i == 2) {
#pragma unroll 1
            for (; s < 3; s++) { issue192(B, c, s); retire(c); }
          }
#pragma unroll 1
          for (int hf = 0; hf < 2; hf++) {
#pragma unroll
            for (int u = 0; u < 3; u++, s++) {
              float2 bs[4];
              lds_bias(bs, bias_t + ((i == 2 ? 192 : 576) + 96 * hf + 32 * u) * 4);
              issue192(B, c, s);
              SEL16(E, A, 16 * u, hf)
              if (i == 2) {
                const uint4 h0 = gelu_group(E), h1 = gelu_group(E + 8);
                const int q = 6 * hf + 2 * u;
                stsm4((hst ^ ((q & 3) << 5)) + (q >> 2) * 16384, h0);
                stsm4((hst ^ (((q + 1) & 3) << 5)) + (q >> 2) * 16384, h1);
              } else if (partA) {
                part_groups<0, 2>(E, dstA + 2 * u * 32, par);
              }
              if (u == 2) dstA += 6 * 32;
              retire(c);
            }
          }
          if (partA) hint_signal(flgA);
#pragma unroll 1
          for (; s < 9; s++) { issue192(B, c, s); retire(c); }
        }
      }
      if ((i & 3) != 0) {
        const bool d1 = i == 1 + srole, d2 = i == 2 + srole;
        const int rel0 = d1 ? 12 : (d2 ? 9 : 100);
        uint32_t W[61];
#pragma unroll
        for (int q = 0; q < 61; q++) W[q] = 0;
#pragma unroll 1
        for (int s = 9; s < 17; s++) {
          issue192(B, c, s);
          if (s == 10 && i == 2) wg_sync();
          const int rel = s - rel0;
          if (rel == 0 || rel == 2) {
            const int ln = opaque(lane), tt = ln & 3;
            if (rel == 0) mbar_wait(bar_d + (d1 ? 0 : 8), 0);
            int tries = 0;
#pragma unroll 1
            while (true) {
              if (rel == 2) {
                uint32_t bad = W[60];
#pragma unroll
                for (int q = 0; q < 12; q++) if ((q % 3) != 2 || tt == 0) ll_chk(bad, W[2 * q], d1 ? W[24 + 2 * q] : par, par);
                if (!__any_sync(0xffffffffu, bad & 1) || ++tries > (1 << 20)) break;
              }
              const uint32_t* qf = reinterpret_cast<const uint32_t*>(g_qkvf) + (m * 8 + (d1 ? (warp & 1) * 4 : warp)) * 108 * 128 + (ln >> 2) * 16;
              const int col0 = (d1 ? 576 + (4 * f + (warp >> 1)) * 18 : 72 * f) + 2 * tt;
#pragma unroll
              for (int j = 0; j < 4; j++)
#pragma unroll
                for (int b = 0; b < 3; b++) {
                  const uint32_t* p = qf + (d1 ? j * 108 * 128 : 0) + coloff(col0 + (d1 ? 0 : 18 * j) + 8 * b);
                  const uint2 kk = ld_ll64(p);
                  W[6 * j + 2 * b] = kk.x; W[6 * j + 2 * b + 1] = kk.y;
                  if (d1) { const uint2 vv = ld_ll64(p + 36 * 128); W[24 + 6 * j + 2 * b] = vv.x; W[24 + 6 * j + 2 * b + 1] = vv.y; }
                }
              if (!d1) {
                uint32_t bad = 0;
#pragma unroll
                for (int hh = 0; hh < 4; hh++)
#pragma unroll
                  for (int j = 0; j < 5; j++) {
                    const uint4 kv = ld_ll(&g_kvt[((4 * f + hh) * 5 + j) * 32 + ln]);
                    W[24 + 9 * hh + 2 * j] = kv.y;
                    if (j < 4) W[24 + 9 * hh + 2 * j + 1] = kv.w;
                    ll_chk(bad, kv.x, kv.z, par);
                  }
                W[60] = bad;
              }
              if (rel == 0) break;
            }
            if (rel == 2) {
#pragma unroll
              for (int q = 0; q < 24; q++) W[q] = phi2(W[q]);
              if (tt != 0) {
#pragma unroll
                for (int j = 0; j < 4; j++) W[6 * j + 4] = W[6 * j + 5] = 0u;
              }
            }
          }
          if (rel == 3 && d1) {
            if (t != 0) {
#pragma unroll
              for (int j = 0; j < 4; j++) W[24 + 6 * j + 4] = W[24 + 6 * j + 5] = (t == 1 ? 0x00003f80u : 0u);
            }
#pragma unroll
            for (int q = 0; q < 48; q++) W[q] = movmat(W[q]);
          }
          if (rel == 4) {
            wg_wait<0>();
            asm volatile("bar.sync 4, 256;" ::: "memory");
            if (d1) {
              float c0[3][4], c1[3][4];
#pragma unroll
              for (int j = 0; j < 3; j++) { c0[j][0] = c0[j][1] = c0[j][2] = c0[j][3] = 0.f; c1[j][0] = c1[j][1] = c1[j][2] = c1[j][3] = 0.f; }
#pragma unroll
              for (int ks = 0; ks < 4; ks++)
#pragma unroll
                for (int j = 0; j < 3; j++) {
                  mma16816(c0[j], W[24 + 6 * ks], W[24 + 6 * ks + 2], W[24 + 6 * ks + 1], W[24 + 6 * ks + 3], W[6 * ks + 2 * j], W[6 * ks + 2 * j + 1]);
                  mma16816(c1[j], W[24 + 6 * ks + 4], 0u, W[24 + 6 * ks + 5], 0u, W[6 * ks + 2 * j], W[6 * ks + 2 * j + 1]);
                }
              const int head = 4 * f + (warp >> 1);
              uint4* dst = &g_kvp[(head * 160 + m * 2 + (warp & 1)) * 32 + opaque(lane)];
#pragma unroll
              for (int j = 0; j < 3; j++) st_ll(dst + j * 1024, __float_as_uint(c0[j][0]), __float_as_uint(c0[j][1]), __float_as_uint(c0[j][2]), __float_as_uint(c0[j][3]), par);
              st_ll(dst + 3072, __float_as_uint(c1[0][0]), __float_as_uint(c1[0][1]), __float_as_uint(c1[1][0]), __float_as_uint(c1[1][1]), par);
              st_ll(dst + 4096, __float_as_uint(c1[2][0]), __float_as_uint(c1[2][1]), 0u, 0u, par);
              hint_signal(&g_f_kvp[head]);
              STAMPW(0, 21);
            } else {
              float cc[4][3][4];
#pragma unroll
              for (int hh = 0; hh < 4; hh++)
#pragma unroll
                for (int e = 0; e < 3; e++) {
                  cc[hh][e][0] = cc[hh][e][1] = cc[hh][e][2] = cc[hh][e][3] = 0.f;
                  mma16816(cc[hh][e], W[6 * hh], W[6 * hh + 1], W[6 * hh + 2], W[6 * hh + 3], W[24 + 9 * hh + (e < 2 ? e : 6)], W[24 + 9 * hh + (e < 2 ? e + 2 : 7)]);
                  mma16816(cc[hh][e], W[6 * hh + 4], W[6 * hh + 5], 0u, 0u, W[24 + 9 * hh + (e < 2 ? e + 4 : 8)], 0u);
                }
#pragma unroll
              for (int hh = 0; hh < 4; hh++) {
                W[48 + 2 * hh] = __float_as_uint(__shfl_sync(0xffffffffu, cc[hh][2][0], (lane & ~3) | 1));
                W[49 + 2 * hh] = __float_as_uint(__shfl_sync(0xffffffffu, cc[hh][2][2], (lane & ~3) | 1));
              }
#pragma unroll
              for (int q = 0; q < 48; q++) W[q] = __float_as_uint(cc[q / 12][(q % 12) / 4][q % 4]);
            }
            asm volatile("bar.sync 4, 256;" ::: "memory");
          }
          if (rel == 5) {
            const int ln = opaque(lane);
            __nv_bfloat16* po = g_o + (rb * 16 + (ln >> 2)) * D_ + 72 * f + 2 * (ln & 3);
#pragma unroll
            for (int hh = 0; hh < 4; hh++) {
              const float r0 = __fdividef(1.f, __uint_as_float(W[48 + 2 * hh]) + 1e-6f), r1 = __fdividef(1.f, __uint_as_float(W[49 + 2 * hh]) + 1e-6f);
#pragma unroll
              for (int e = 0; e < 3; e++) {
                const uint32_t* w = &W[12 * hh + 4 * e];
                if (e < 2 || (ln & 3) == 0) {
                  *reinterpret_cast<uint32_t*>(po + 18 * hh + 8 * e) = pack_bf16(__uint_as_float(w[0]) * r0, __uint_as_float(w[1]) * r0);
                  *reinterpret_cast<uint32_t*>(po + 8 * D_ + 18 * hh + 8 * e) = pack_bf16(__uint_as_float(w[2]) * r1, __uint_as_float(w[3]) * r1);
                }
              }
            }
            asm volatile("fence.proxy.async.global;" ::: "memory");
            __syncwarp();
            if (ln == 0) mbar_arrive(bar_o);
          }
          retire(c);
        }
        issue192(B, c, 17);
        retire(c);
      }
      STAMPW(0, 2 + 2 * i); WSTAMP(2 + 2 * i);
      {
        const int ln = opaque(lane);
        const bool gel = (i == 1) || (i == 2);
        uint4* dstB = i == 0 ? g_qkvf + (rb * 108 + 18 * f) * 32 + ln
                             : (i == 1 ? g_hsp + (blockIdx.x * 8 + warp) * 12 * 32 + ln : (i == 3 ? g_part + ((rb * 8 + f) * 36 + 12) * 32 + ln : g_s2 + (rb * 12 + 6 * (f - 6)) * 32 + ln));
        uint32_t* flgB = i == 0 ? &g_f_qkv[m * 8 + f] : &g_f_rb[rb * 8 + (i == 3 ? 1 : 3)];
        const bool xf = i == 3 && srole && leader;
        const uint32_t bsa = bias_t + (i == 1 ? 0 : (i == 2 ? 384 * 4 : 576 * 4));
        issue192(A, c, 0, true);
        retire(c);
        fence_regs<96>(B);
        LDS_R(i <= 2)
        int s = 1;
#pragma unroll 1
        for (int hf = 0; hf < 2; hf++) {
#pragma unroll
          for (int u = 0; u < 3; u++, s++) {
            float2 bs[4];
            lds_bias(bs, bsa + (96 * hf + 32 * u) * 4);
            issue192(A, c, s);
            SEL16(E, B, 16 * u, hf)
            if (gel) {
              const uint4 h0 = gelu_group(E), h1 = gelu_group(E + 8);
              if (i == 1) { dstB[2 * u * 32] = h0; dstB[(2 * u + 1) * 32] = h1; }
              else {
                const int q = 6 * hf + 2 * u;
                stsm4((hst ^ ((q & 3) << 5)) + (3 + (q >> 2)) * 16384, h0);
                stsm4((hst ^ (((q + 1) & 3) << 5)) + (3 + (q >> 2)) * 16384, h1);
                if (u == 1 && hf == 1) wg_sync();
              }
            } else if (hf == 0 || i == 3) {
              part_groups<0, 2>(E, dstB + 2 * u * 32, par);
              if (u == 2 && (hf == 1 || i != 3)) hint_signal(flgB);
            }
            if (u == 2) dstB += 6 * 32;
            retire(c);
            if ((s & 1) == 0 && xf) mbar_arrive(bar_xfree + 4 * s - 8);
          }
        }
        uint4 pk[12];
#pragma unroll
        for (int q = 0; q < 12; q++) pk[q] = make_uint4(0, 0, 0, 0);
#pragma unroll 1
        for (; s < 17; s++) {
          issue192(A, c, s);
          if (i == 2) {
            if (s == 7) {
              const uint4* hsp = g_hsp + (blockIdx.x * 8 + warp) * 12 * 32 + opaque(lane);
#pragma unroll
              for (int q = 0; q < 12; q++) pk[q] = ldcg128(hsp + q * 32);
            }
            if (s == 10) {
#pragma unroll
              for (int q = 0; q < 12; q++) stsm4((hst ^ ((q & 3) << 5)) + (6 + (q >> 2)) * 16384, pk[q]);
            }
            if (s == 8 || s == 11) wg_sync();
          }
          retire(c);
          if ((s & 1) == 0 && xf) mbar_arrive(bar_xfree + 4 * s - 8);
        }
        issue192(A, c, 17);
        retire(c);
      }
      STAMPW(0, 3 + 2 * i); WSTAMP(3 + 2 * i);
    }

    const size_t r0 = (size_t)(rb * 16 + g) * D_ + 2 * t;
    if (srole) {
      const int cb = 192 * (f - 6);
      uint32_t xx[48];
      uint4 gg[12];
#pragma unroll
      for (int q = 0; q < 12; q++) {
        xx[4 * q + 0] = __ldg(reinterpret_cast<const uint32_t*>(P.x + r0 + cb + 16 * q));
        xx[4 * q + 1] = __ldg(reinterpret_cast<const uint32_t*>(P.x + r0 + 8 * D_ + cb + 16 * q));
        xx[4 * q + 2] = __ldg(reinterpret_cast<const uint32_t*>(P.x + r0 + cb + 16 * q + 8));
        xx[4 * q + 3] = __ldg(reinterpret_cast<const uint32_t*>(P.x + r0 + 8 * D_ + cb + 16 * q + 8));
      }
      if (lane == 0) hint_wait(&g_f_rb[rb * 8 + 4 + (f - 6)], 3 * ep);
      __syncwarp();
      STAMPW(0, 14);
      int tries = 0;
      uint32_t bad;
#pragma unroll 1
      do {
        bad = 0;
#pragma unroll
        for (int q = 0; q < 12; q++) gg[q] = ld_ll(&g_g[(rb * 24 + 12 * (f - 6) + q) * 32 + lane]);
#pragma unroll
        for (int q = 0; q < 12; q++) ll_chk(bad, gg[q].x, gg[q].z, par);
      } while (__any_sync(0xffffffffu, bad & 1) && ++tries < (1 << 20));
      wg_wait<0>();
      c.release_prev();
      fence_regs<96>(A);
#pragma unroll
      for (int q = 0; q < 12; q++) {
        const uint32_t* gw = reinterpret_cast<const uint32_t*>(&gg[q]);
        uint32_t res[4];
#pragma unroll
        for (int k = 0; k < 4; k++)
          res[k] = hfma2(pack_bf16(A[8 * q + 2 * k], A[8 * q + 2 * k + 1]), gw[k], xx[4 * q + k]);
        *reinterpret_cast<uint32_t*>(P.out + r0 + cb + 16 * q) = res[0];
        *reinterpret_cast<uint32_t*>(P.out + r0 + 8 * D_ + cb + 16 * q) = res[1];
        *reinterpret_cast<uint32_t*>(P.out + r0 + cb + 16 * q + 8) = res[2];
        *reinterpret_cast<uint32_t*>(P.out + r0 + 8 * D_ + cb + 16 * q + 8) = res[3];
      }
    } else {
      wg_wait<0>();
      c.release_prev();
      fence_regs<96>(A);
      part_groups<0, 12>(A, g_part + ((rb * 8 + f) * 36 + 24) * 32 + lane, par);
      hint_signal(&g_f_rb[rb * 8 + 2]);
      STAMPW(0, 12);
      const int cb = 384 + 32 * f;
      uint32_t xx[8], bb[4];
#pragma unroll
      for (int j = 0; j < 2; j++) {
        xx[4 * j + 0] = __ldg(reinterpret_cast<const uint32_t*>(P.x + r0 + cb + 16 * j));
        xx[4 * j + 1] = __ldg(reinterpret_cast<const uint32_t*>(P.x + r0 + 8 * D_ + cb + 16 * j));
        xx[4 * j + 2] = __ldg(reinterpret_cast<const uint32_t*>(P.x + r0 + cb + 16 * j + 8));
        xx[4 * j + 3] = __ldg(reinterpret_cast<const uint32_t*>(P.x + r0 + 8 * D_ + cb + 16 * j + 8));
        bb[2 * j] = __ldg(reinterpret_cast<const uint32_t*>(P.b2 + cb + 16 * j + 2 * t));
        bb[2 * j + 1] = __ldg(reinterpret_cast<const uint32_t*>(P.b2 + cb + 16 * j + 8 + 2 * t));
      }
      if (lane < 2) hint_wait(&g_f_rb[rb * 8 + 2 + lane], (lane == 0 ? 8u : 2u) * ep);
      __syncwarp();
      STAMPW(0, 14);
      uint4 p[2][8], sv[2];
      int tries = 0;
      uint32_t bad;
#pragma unroll 1
      do {
        bad = 0;
#pragma unroll
        for (int j = 0; j < 2; j++) {
#pragma unroll
          for (int i = 0; i < 8; i++) p[j][i] = ld_ll(&g_part[((rb * 8 + i) * 36 + 24 + 2 * f + j) * 32 + lane]);
          sv[j] = ld_ll(&g_s2[(rb * 12 + 2 * f + j) * 32 + lane]);
        }
#pragma unroll
        for (int j = 0; j < 2; j++) {
#pragma unroll
          for (int i = 0; i < 8; i++) ll_chk(bad, p[j][i].x, p[j][i].z, par);
          ll_chk(bad, sv[j].x, sv[j].z, par);
        }
      } while (__any_sync(0xffffffffu, bad & 1) && ++tries < (1 << 20));
#pragma unroll
      for (int j = 0; j < 2; j++) {
        float gt[8];
        gate_vec(p[j], bb[2 * j], bb[2 * j + 1], gt);
        const uint32_t* sw = reinterpret_cast<const uint32_t*>(&sv[j]);
        uint32_t res[4];
#pragma unroll
        for (int k = 0; k < 4; k++) res[k] = hfma2(sw[k], pack_bf16(gt[2 * k], gt[2 * k + 1]), xx[4 * j + k]);
        *reinterpret_cast<uint32_t*>(P.out + r0 + cb + 16 * j) = res[0];
        *reinterpret_cast<uint32_t*>(P.out + r0 + 8 * D_ + cb + 16 * j) = res[1];
        *reinterpret_cast<uint32_t*>(P.out + r0 + cb + 16 * j + 8) = res[2];
        *reinterpret_cast<uint32_t*>(P.out + r0 + 8 * D_ + cb + 16 * j + 8) = res[3];
      }
    }
    STAMPW(0, 15);
    cluster_arrive_relaxed();
    cluster_wait();
    STAMPW(0, 16);
    if (tid == 0) g_epoch[blockIdx.x] = ep;
  }
}

typedef CUresult (*EncFn)(CUtensorMap*, CUtensorMapDataType, cuuint32_t, void*, const cuuint64_t*, const cuuint64_t*, const cuuint32_t*, const cuuint32_t*,
                          CUtensorMapInterleave, CUtensorMapSwizzle, CUtensorMapL2promotion, CUtensorMapFloatOOBfill);

void make_map(EncFn enc, CUtensorMap* tm, const void* ptr, int rows, int cols, int box_rows, bool sw64 = false) {
  cuuint64_t gd[2] = {(cuuint64_t)cols, (cuuint64_t)rows};
  cuuint64_t gs[1] = {(cuuint64_t)cols * 2};
  cuuint32_t bx[2] = {sw64 ? 32u : 64u, (cuuint32_t)box_rows};
  cuuint32_t es[2] = {1, 1};
  enc(tm, CU_TENSOR_MAP_DATA_TYPE_BFLOAT16, 2, const_cast<void*>(ptr), gd, gs, bx, es, CU_TENSOR_MAP_INTERLEAVE_NONE, sw64 ? CU_TENSOR_MAP_SWIZZLE_64B : CU_TENSOR_MAP_SWIZZLE_128B,
      CU_TENSOR_MAP_L2_PROMOTION_L2_256B, CU_TENSOR_MAP_FLOAT_OOB_FILL_NONE);
}

}

extern "C" void kernel_launch(void* const* d_in, const int* in_sizes, int n_in, void* d_out, int out_size) {
  (void)in_sizes; (void)n_in; (void)out_size;
  static EncFn enc = nullptr;
  static void* o_ptr = nullptr;
  if (!enc) {
    void* fn = nullptr; cudaDriverEntryPointQueryResult q;
    cudaGetDriverEntryPoint("cuTensorMapEncodeTiled", &fn, cudaEnableDefault, &q);
    enc = (EncFn)fn;
    cudaFuncSetAttribute(fused_kernel, cudaFuncAttributeMaxDynamicSharedMemorySize, SMEM_BYTES);
    cudaGetSymbolAddress(&o_ptr, g_o);
  }
  Params P;
  P.x = (const __nv_bfloat16*)d_in[0];
  P.wqkv = (const __nv_bfloat16*)d_in[1];
  P.wo = (const __nv_bfloat16*)d_in[2];
  P.w1 = (const __nv_bfloat16*)d_in[4];
  P.b1 = (const __nv_bfloat16*)d_in[5];
  P.w2 = (const __nv_bfloat16*)d_in[6];
  P.b2 = (const __nv_bfloat16*)d_in[7];
  P.out = (__nv_bfloat16*)d_out;
  make_map(enc, &P.tm_wqkv, P.wqkv, D_, Q3_, 32);
  make_map(enc, &P.tm_w1, P.w1, D_, F_, 32);
  make_map(enc, &P.tm_w2, P.w2, F_, D_, 32);
  make_map(enc, &P.tm_wo, P.wo, D_, D_, 32);
  make_map(enc, &P.tm_wqkv64, P.wqkv, D_, Q3_, 64, true);
  make_map(enc, &P.tm_wo64, P.wo, D_, D_, 64, true);
  make_map(enc, &P.tm_o, o_ptr, S_, D_, 128);
  fused_kernel<<<NCTAS, NTHREADS, SMEM_BYTES, cudaStreamPerThread>>>(P);
}
```

```cpp
#include <cuda_runtime.h>
#include <cuda.h>
#include <cuda_bf16.h>
#include <stdint.h>

namespace {

constexpr int S_ = 2048, D_ = 576, F_ = 4608, Q3_ = 1728;
constexpr int NSTAGE = 6, STAGE_BYTES = 12288;
constexpr int SM_A = 0, SM_B = 147456, SM_BIAS = SM_B + NSTAGE * STAGE_BYTES, SM_RSTD = SM_BIAS + 3072, SM_KV = SM_RSTD + 1024, SM_BAR = SM_KV + 4 * 19 * 80;
constexpr int SMEM_BYTES = SM_BAR + 320;
constexpr int NTHREADS = 384;
constexpr int NCTAS = 132;

__device__ uint4 g_qkvf[(128 * 108 + 1) * 32];
__device__ __align__(1024) __nv_bfloat16 g_a[S_ * D_];
__device__ __align__(1024) __nv_bfloat16 g_m[D_ * D_];
__device__ uint4 g_kvp[32 * 5 * 32 * 32];
__device__ uint4 g_kvt[32 * 5 * 32];
__device__ uint4 g_part[128 * 8 * 36 * 32];
__device__ uint4 g_s[128 * 24 * 32];
__device__ uint4 g_g[128 * 24 * 32];
__device__ uint4 g_hsp[128 * 12 * 256];
__device__ uint32_t g_f_qkv[16 * 8];
__device__ uint32_t g_f_kvp[32];
__device__ uint32_t g_f_kvt[32];
__device__ uint32_t g_f_a[16];
__device__ uint32_t g_f_m[1];
__device__ uint32_t g_f_rb[128 * 8];
__device__ uint2 g_stat[S_];
__device__ uint32_t g_epoch[NCTAS];

#define STAMP(i)
#define STAMPW(w, i)
#define WSTAMP(i)
__device__ __forceinline__ uint32_t smem_u32(const void* p) { return (uint32_t)__cvta_generic_to_shared(p); }
__device__ __forceinline__ void mbar_init(uint32_t a, int c) { asm volatile("mbarrier.init.shared::cta.b64 [%0], %1;" ::"r"(a), "r"(c)); }
__device__ __forceinline__ void mbar_expect(uint32_t a, uint32_t b) { asm volatile("mbarrier.arrive.expect_tx.shared::cta.b64 _, [%0], %1;" ::"r"(a), "r"(b) : "memory"); }
__device__ __forceinline__ void mbar_arrive(uint32_t a) { asm volatile("mbarrier.arrive.shared::cta.b64 _, [%0];" ::"r"(a) : "memory"); }
__device__ __forceinline__ void mbar_arrive_cl(uint32_t a) { asm volatile("mbarrier.arrive.shared::cluster.b64 _, [%0];" ::"r"(a) : "memory"); }
__device__ __forceinline__ uint32_t mapa(uint32_t a, uint32_t cta) { uint32_t r; asm volatile("mapa.shared::cluster.u32 %0, %1, %2;" : "=r"(r) : "r"(a), "r"(cta)); return r; }
__device__ __forceinline__ void mbar_wait(uint32_t a, uint32_t ph) {
  uint32_t ok; int it = 0;
#pragma unroll 1
  do {
    asm volatile("{.reg .pred p; mbarrier.try_wait.parity.shared::cta.b64 p, [%1], %2; selp.u32 %0,1,0,p;}" : "=r"(ok) : "r"(a), "r"(ph) : "memory");
  } while (!ok && ++it < (1 << 18));
}
__device__ __forceinline__ void tma2d(uint32_t dst, const CUtensorMap* m, int c0, int c1, uint32_t bar) {
  asm volatile("cp.async.bulk.tensor.2d.shared::cluster.global.mbarrier::complete_tx::bytes [%0], [%1, {%3,%4}], [%2];" ::"r"(dst), "l"(m), "r"(bar), "r"(c0), "r"(c1) : "memory");
}
__device__ __forceinline__ void tma2d_mc(uint32_t dst, const CUtensorMap* m, int c0, int c1, uint32_t bar) {
  asm volatile("cp.async.bulk.tensor.2d.shared::cluster.global.mbarrier::complete_tx::bytes.multicast::cluster [%0], [%1, {%3,%4}], [%2], %5;" ::"r"(dst), "l"(m), "r"(bar), "r"(c0), "r"(c1), "h"((uint16_t)3) : "memory");
}
__device__ __forceinline__ void cluster_arrive_relaxed() { asm volatile("barrier.cluster.arrive.relaxed.aligned;" ::: "memory"); }
__device__ __forceinline__ void cluster_wait() { asm volatile("barrier.cluster.wait.acquire.aligned;" ::: "memory"); }
__device__ __forceinline__ void wg_fence() { asm volatile("wgmma.fence.sync.aligned;" ::: "memory"); }
__device__ __forceinline__ void wg_commit() { asm volatile("wgmma.commit_group.sync.aligned;" ::: "memory"); }
template <int n> __device__ __forceinline__ void wg_wait() { asm volatile("wgmma.wait_group.sync.aligned %0;" ::"n"(n) : "memory"); }
__device__ __forceinline__ uint32_t ld_acquire(const uint32_t* p) { uint32_t v; asm volatile("ld.acquire.gpu.global.u32 %0, [%1];" : "=r"(v) : "l"(p) : "memory"); return v; }
__device__ __forceinline__ void flag_wait(const uint32_t* p, uint32_t target) {
  int it = 0;
#pragma unroll 1
  while ((int)(ld_acquire(p) - target) < 0 && ++it < (1 << 21)) __nanosleep(40);
}
__device__ __forceinline__ void hint_signal(uint32_t* p) {
  if ((threadIdx.x & 31) == 0) asm volatile("red.relaxed.gpu.global.add.u32 [%0], 1;" ::"l"(p) : "memory");
}
__device__ __forceinline__ void hint_wait(const uint32_t* p, uint32_t target) {
  int it = 0; uint32_t v;
#pragma unroll 1
  do { asm volatile("ld.relaxed.gpu.global.u32 %0, [%1];" : "=r"(v) : "l"(p) : "memory"); if ((int)(v - target) >= 0) break; __nanosleep(32); } while (++it < (1 << 21));
}
__device__ __forceinline__ uint32_t tag(uint32_t x, uint32_t par) { uint32_t r; asm("lop3.b32 %0, %1, 0xfffffffe, %2, 0xea;" : "=r"(r) : "r"(x), "r"(par)); return r; }
__device__ __forceinline__ void st_ll(uint4* p, uint32_t x, uint32_t y, uint32_t z, uint32_t w, uint32_t par) {
  asm volatile("{.reg .b64 a, b; mov.b64 a, {%1,%2}; mov.b64 b, {%3,%4}; st.relaxed.gpu.global.v2.b64 [%0], {a, b};}"
               ::"l"(p), "r"(tag(x, par)), "r"(y), "r"(tag(z, par)), "r"(w) : "memory");
}
__device__ __forceinline__ uint4 ld_ll(const uint4* p) {
  uint4 v;
  asm volatile("{.reg .b64 a, b; ld.relaxed.gpu.global.v2.b64 {a, b}, [%4]; mov.b64 {%0,%1}, a; mov.b64 {%2,%3}, b;}"
               : "=r"(v.x), "=r"(v.y), "=r"(v.z), "=r"(v.w) : "l"(p) : "memory");
  return v;
}
__device__ __forceinline__ uint2 ld_ll64(const uint32_t* p) {
  uint2 v;
  asm volatile("{.reg .b64 a; ld.relaxed.gpu.global.b64 a, [%2]; mov.b64 {%0,%1}, a;}" : "=r"(v.x), "=r"(v.y) : "l"(p) : "memory");
  return v;
}
__device__ __forceinline__ void ll_chk(uint32_t& bad, uint32_t a, uint32_t b, uint32_t par) {
  uint32_t u; asm("lop3.b32 %0, %1, %2, %3, 0x7e;" : "=r"(u) : "r"(a), "r"(b), "r"(par));
  asm("or.b32 %0, %0, %1;" : "+r"(bad) : "r"(u));
}
__device__ __forceinline__ uint32_t hadd2(uint32_t a, uint32_t b) { uint32_t d; asm("add.rn.bf16x2 %0, %1, %2;" : "=r"(d) : "r"(a), "r"(b)); return d; }
__device__ __forceinline__ uint32_t hfma2(uint32_t a, uint32_t b, uint32_t c) { uint32_t d; asm("fma.rn.bf16x2 %0, %1, %2, %3;" : "=r"(d) : "r"(a), "r"(b), "r"(c)); return d; }
__device__ __forceinline__ uint32_t pack_bf16(float lo, float hi) { uint32_t r; asm("cvt.rn.bf16x2.f32 %0, %1, %2;" : "=r"(r) : "f"(hi), "f"(lo)); return r; }
__device__ __forceinline__ float bf_lo(uint32_t v) { return __uint_as_float(v << 16); }
__device__ __forceinline__ float bf_hi(uint32_t v) { return __uint_as_float(v & 0xffff0000u); }
__device__ __forceinline__ float tanh_fast(float x) { float r; asm("tanh.approx.f32 %0, %1;" : "=f"(r) : "f"(x)); return r; }
__device__ __forceinline__ uint32_t movmat(uint32_t a) { uint32_t d; asm volatile("movmatrix.sync.aligned.m8n8.trans.b16 %0, %1;" : "=r"(d) : "r"(a)); return d; }
__device__ __forceinline__ void mma16816(float* c, uint32_t a0, uint32_t a1, uint32_t a2, uint32_t a3, uint32_t b0, uint32_t b1) {
  asm volatile("mma.sync.aligned.m16n8k16.row.col.f32.bf16.bf16.f32 {%0,%1,%2,%3}, {%4,%5,%6,%7}, {%8,%9}, {%0,%1,%2,%3};"
               : "+f"(c[0]), "+f"(c[1]), "+f"(c[2]), "+f"(c[3]) : "r"(a0), "r"(a1), "r"(a2), "r"(a3), "r"(b0), "r"(b1));
}
__device__ __forceinline__ uint4 ldcg128(const void* p) { uint4 v; asm volatile("ld.global.cg.v4.u32 {%0,%1,%2,%3}, [%4];" : "=r"(v.x), "=r"(v.y), "=r"(v.z), "=r"(v.w) : "l"(p) : "memory"); return v; }

template <int N> __device__ __forceinline__ void wgmma_ss(float* d, uint64_t da, uint64_t db, int sc);
template <int N> __device__ __forceinline__ void wgmma_rs(float* d, const uint32_t* a, uint64_t db, int sc);
template <> __device__ __forceinline__ void wgmma_ss<96>(float* d, uint64_t da, uint64_t db, int sc) {
  asm volatile("{.reg .pred p; setp.ne.b32 p, %50, 0; wgmma.mma_async.sync.aligned.m64n96k16.f32.bf16.bf16 {%0, %1, %2, %3, %4, %5, %6, %7, %8, %9, %10, %11, %12, %13, %14, %15, %16, %17, %18, %19, %20, %21, %22, %23, %24, %25, %26, %27, %28, %29, %30, %31, %32, %33, %34, %35, %36, %37, %38, %39, %40, %41, %42, %43, %44, %45, %46, %47}, %48, %49, p, 1, 1, 0, 1;}"
   : "+f"(d[0]), "+f"(d[1]), "+f"(d[2]), "+f"(d[3]), "+f"(d[4]), "+f"(d[5]), "+f"(d[6]), "+f"(d[7]), "+f"(d[8]), "+f"(d[9]), "+f"(d[10]), "+f"(d[11]), "+f"(d[12]), "+f"(d[13]), "+f"(d[14]), "+f"(d[15]), "+f"(d[16]), "+f"(d[17]), "+f"(d[18]), "+f"(d[19]), "+f"(d[20]), "+f"(d[21]), "+f"(d[22]), "+f"(d[23]), "+f"(d[24]), "+f"(d[25]), "+f"(d[26]), "+f"(d[27]), "+f"(d[28]), "+f"(d[29]), "+f"(d[30]), "+f"(d[31]), "+f"(d[32]), "+f"(d[33]), "+f"(d[34]), "+f"(d[35]), "+f"(d[36]), "+f"(d[37]), "+f"(d[38]), "+f"(d[39]), "+f"(d[40]), "+f"(d[41]), "+f"(d[42]), "+f"(d[43]), "+f"(d[44]), "+f"(d[45]), "+f"(d[46]), "+f"(d[47]) : "l"(da), "l"(db), "r"(sc));
}
template <> __device__ __forceinline__ void wgmma_ss<192>(float* d, uint64_t da, uint64_t db, int sc) {
  asm volatile("{.reg .pred p; setp.ne.b32 p, %98, 0; wgmma.mma_async.sync.aligned.m64n192k16.f32.bf16.bf16 {%0, %1, %2, %3, %4, %5, %6, %7, %8, %9, %10, %11, %12, %13, %14, %15, %16, %17, %18, %19, %20, %21, %22, %23, %24, %25, %26, %27, %28, %29, %30, %31, %32, %33, %34, %35, %36, %37, %38, %39, %40, %41, %42, %43, %44, %45, %46, %47, %48, %49, %50, %51, %52, %53, %54, %55, %56, %57, %58, %59, %60, %61, %62, %63, %64, %65, %66, %67, %68, %69, %70, %71, %72, %73, %74, %75, %76, %77, %78, %79, %80, %81, %82, %83, %84, %85, %86, %87, %88, %89, %90, %91, %92, %93, %94, %95}, %96, %97, p, 1, 1, 0, 1;}"
   : "+f"(d[0]), "+f"(d[1]), "+f"(d[2]), "+f"(d[3]), "+f"(d[4]), "+f"(d[5]), "+f"(d[6]), "+f"(d[7]), "+f"(d[8]), "+f"(d[9]), "+f"(d[10]), "+f"(d[11]), "+f"(d[12]), "+f"(d[13]), "+f"(d[14]), "+f"(d[15]), "+f"(d[16]), "+f"(d[17]), "+f"(d[18]), "+f"(d[19]), "+f"(d[20]), "+f"(d[21]), "+f"(d[22]), "+f"(d[23]), "+f"(d[24]), "+f"(d[25]), "+f"(d[26]), "+f"(d[27]), "+f"(d[28]), "+f"(d[29]), "+f"(d[30]), "+f"(d[31]), "+f"(d[32]), "+f"(d[33]), "+f"(d[34]), "+f"(d[35]), "+f"(d[36]), "+f"(d[37]), "+f"(d[38]), "+f"(d[39]), "+f"(d[40]), "+f"(d[41]), "+f"(d[42]), "+f"(d[43]), "+f"(d[44]), "+f"(d[45]), "+f"(d[46]), "+f"(d[47]), "+f"(d[48]), "+f"(d[49]), "+f"(d[50]), "+f"(d[51]), "+f"(d[52]), "+f"(d[53]), "+f"(d[54]), "+f"(d[55]), "+f"(d[56]), "+f"(d[57]), "+f"(d[58]), "+f"(d[59]), "+f"(d[60]), "+f"(d[61]), "+f"(d[62]), "+f"(d[63]), "+f"(d[64]), "+f"(d[65]), "+f"(d[66]), "+f"(d[67]), "+f"(d[68]), "+f"(d[69]), "+f"(d[70]), "+f"(d[71]), "+f"(d[72]), "+f"(d[73]), "+f"(d[74]), "+f"(d[75]), "+f"(d[76]), "+f"(d[77]), "+f"(d[78]), "+f"(d[79]), "+f"(d[80]), "+f"(d[81]), "+f"(d[82]), "+f"(d[83]), "+f"(d[84]), "+f"(d[85]), "+f"(d[86]), "+f"(d[87]), "+f"(d[88]), "+f"(d[89]), "+f"(d[90]), "+f"(d[91]), "+f"(d[92]), "+f"(d[93]), "+f"(d[94]), "+f"(d[95]) : "l"(da), "l"(db), "r"(sc));
}

__device__ __forceinline__ uint64_t desc64(uint32_t lo, uint32_t hi) { uint64_t d; asm("mov.b64 %0, {%1, %2};" : "=l"(d) : "r"(lo), "r"(hi)); return d; }
constexpr uint32_t DESC_HI = (1024u >> 4) | (1u << 30);
constexpr uint32_t DESC_HI64 = (512u >> 4) | (2u << 30);
template <int n> __device__ __forceinline__ void fence_regs(float* a) {
#pragma unroll
  for (int i = 0; i < n; i++) asm volatile("" : "+f"(a[i])::"memory");
}

struct Ctx {
  uint32_t full;
  uint32_t emb;
  bool sig;
  uint32_t stage, phase, prev;
  uint32_t dB, dA;
  __device__ __forceinline__ void release_prev() { if (sig && prev != ~0u) mbar_arrive_cl(emb + prev); }
  __device__ __forceinline__ void wait_full() {
    mbar_wait(full + 8 * stage, phase);
    wg_fence();
  }
};

__device__ __forceinline__ void issue192(float* acc, Ctx& c, int s, bool first = false) {
  c.wait_full();
  const uint32_t db = c.dB + c.stage * (STAGE_BYTES >> 4);
  const uint32_t da = c.dA + (s >> 1) * 1024 + (s & 1) * 4;
  wgmma_ss<192>(acc, desc64(da, DESC_HI), desc64(db, DESC_HI), first ? 0 : 1);
  wgmma_ss<192>(acc, desc64(da + 2, DESC_HI), desc64(db + 128, DESC_HI), 1);
  wg_commit();
}
__device__ __forceinline__ void issue96(float* acc, Ctx& c, int s, bool first) {
  c.wait_full();
  const uint32_t db = c.dB + c.stage * (STAGE_BYTES >> 4);
  const uint32_t da = c.dA + s * 1024;
#pragma unroll
  for (int kk = 0; kk < 4; kk++) wgmma_ss<96>(acc, desc64(da + 2 * kk, DESC_HI), desc64(db + 64 * kk, DESC_HI64), (first && kk == 0) ? 0 : 1);
  wg_commit();
}
__device__ __forceinline__ void retire(Ctx& c) {
  wg_wait<1>();
  c.release_prev();
  c.prev = 8 * c.stage;
  if (++c.stage == NSTAGE) { c.stage = 0; c.phase ^= 1; }
}
__device__ __forceinline__ float gelu2(float x) {
  float u = x * fmaf(x * x, 0.0356774081f, 0.7978845608f);
  return fmaf(x, tanh_fast(u), x);
}
__device__ __forceinline__ uint4 gelu_group(const float* a) {
  return make_uint4(pack_bf16(gelu2(a[0]), gelu2(a[1])), pack_bf16(gelu2(a[2]), gelu2(a[3])), pack_bf16(gelu2(a[4]), gelu2(a[5])), pack_bf16(gelu2(a[6]), gelu2(a[7])));
}
__device__ __forceinline__ void lds_bias(float2* b, uint32_t addr) {
#pragma unroll
  for (int j = 0; j < 2; j++) asm volatile("ld.shared.v2.f32 {%0,%1}, [%2];" : "=f"(b[j].x), "=f"(b[j].y) : "r"(addr + 32 * j));
}
__device__ __forceinline__ int opaque(int v) { asm volatile("" : "+r"(v)); return v; }
__device__ __forceinline__ void stsm4(uint32_t addr, uint4 r) {
  asm volatile("stmatrix.sync.aligned.m8n8.x4.shared.b16 [%0], {%1,%2,%3,%4};" ::"r"(addr), "r"(r.x), "r"(r.y), "r"(r.z), "r"(r.w) : "memory");
}
__device__ __forceinline__ float ex2f(float x) { float r; asm("ex2.approx.ftz.f32 %0, %1;" : "=f"(r) : "f"(x)); return r; }
__device__ __forceinline__ float phi(float t) { float e = ex2f(t * 1.4426950408889634f); if (t > 0.f) e = t + 1.f; return e + 1e-6f; }
__device__ __forceinline__ uint32_t phi2(uint32_t w) { return pack_bf16(phi(bf_lo(w)), phi(bf_hi(w))); }
template <int q0, int q1>
__device__ __forceinline__ void part_groups(const float* a, uint4* p, uint32_t par) {
#pragma unroll
  for (int q = q0; q < q1; q++)
    st_ll(p + q * 32, pack_bf16(a[8 * q], a[8 * q + 1]), pack_bf16(a[8 * q + 2], a[8 * q + 3]), pack_bf16(a[8 * q + 4], a[8 * q + 5]), pack_bf16(a[8 * q + 6], a[8 * q + 7]), par);
}
__device__ __forceinline__ float silu(float y) { return __fdividef(y, 1.f + ex2f(y * -1.4426950408889634f)); }
__device__ __forceinline__ void gate_vec(const uint4* p, uint32_t b0, uint32_t b1, float* gt) {
#pragma unroll
  for (int q = 0; q < 4; q++) {
    float lo = 0.f, hi = 0.f;
#pragma unroll
    for (int i = 0; i < 8; i++) { uint32_t w = reinterpret_cast<const uint32_t*>(&p[i])[q]; lo += bf_lo(w); hi += bf_hi(w); }
    const uint32_t bb = q < 2 ? b0 : b1;
    gt[2 * q] = silu(fmaf(lo, 0.5f, bf_lo(bb)));
    gt[2 * q + 1] = silu(fmaf(hi, 0.5f, bf_hi(bb)));
  }
}
__device__ __forceinline__ int coloff(int c) { return (c >> 4) * 128 + ((c & 7) >> 1) * 4 + ((c >> 3) & 1) * 2; }

__device__ __forceinline__ void d1_load(uint32_t* W, int rb0, int head, int ln) {
  const uint32_t* qf = reinterpret_cast<const uint32_t*>(g_qkvf) + rb0 * 108 * 128 + (ln >> 2) * 16;
#pragma unroll
  for (int b = 0; b < 3; b++) {
    const uint32_t* p = qf + coloff(576 + head * 18 + 8 * b + 2 * (ln & 3));
#pragma unroll
    for (int j = 0; j < 4; j++) {
      const uint2 kk = ld_ll64(p + j * 108 * 128), vv = ld_ll64(p + j * 108 * 128 + 36 * 128);
      W[6 * j + 2 * b] = kk.x; W[6 * j + 2 * b + 1] = kk.y; W[24 + 6 * j + 2 * b] = vv.x; W[24 + 6 * j + 2 * b + 1] = vv.y;
    }
  }
}
__device__ __forceinline__ bool d1_bad(const uint32_t* W, int t, uint32_t par) {
  uint32_t bad = 0, bad2 = 0;
#pragma unroll
  for (int q = 0; q < 12; q++) ll_chk((q % 3) != 2 ? bad : bad2, W[2 * q], W[24 + 2 * q], par);
  return __any_sync(0xffffffffu, (bad | (t == 0 ? bad2 : 0u)) & 1);
}
__device__ __forceinline__ void d1_prep(uint32_t* W, int j, int t) {
#pragma unroll
  for (int q = 0; q < 6; q++) W[6 * j + q] = phi2(W[6 * j + q]);
  if (t != 0) { W[6 * j + 4] = W[6 * j + 5] = 0u; W[24 + 6 * j + 4] = W[24 + 6 * j + 5] = (t == 1 ? 0x00003f80u : 0u); }
#pragma unroll
  for (int q = 0; q < 6; q++) { W[6 * j + q] = movmat(W[6 * j + q]); W[24 + 6 * j + q] = movmat(W[24 + 6 * j + q]); }
}
__device__ __forceinline__ void d1_mma_store(const uint32_t* W, int head, int blk, int ln, uint32_t par) {
  float c0[3][4], c1[3][4];
#pragma unroll
  for (int j = 0; j < 3; j++) { c0[j][0] = c0[j][1] = c0[j][2] = c0[j][3] = 0.f; c1[j][0] = c1[j][1] = c1[j][2] = c1[j][3] = 0.f; }
#pragma unroll
  for (int ks = 0; ks < 4; ks++)
#pragma unroll
    for (int j = 0; j < 3; j++) {
      mma16816(c0[j], W[24 + 6 * ks], W[24 + 6 * ks + 2], W[24 + 6 * ks + 1], W[24 + 6 * ks + 3], W[6 * ks + 2 * j], W[6 * ks + 2 * j + 1]);
      mma16816(c1[j], W[24 + 6 * ks + 4], 0u, W[24 + 6 * ks + 5], 0u, W[6 * ks + 2 * j], W[6 * ks + 2 * j + 1]);
    }
  uint4* dst = &g_kvp[(head * 160 + blk) * 32 + ln];
#pragma unroll
  for (int j = 0; j < 3; j++) st_ll(dst + j * 1024, __float_as_uint(c0[j][0]), __float_as_uint(c0[j][1]), __float_as_uint(c0[j][2]), __float_as_uint(c0[j][3]), par);
  st_ll(dst + 3072, __float_as_uint(c1[0][0]), __float_as_uint(c1[0][1]), __float_as_uint(c1[1][0]), __float_as_uint(c1[1][1]), par);
  st_ll(dst + 4096, __float_as_uint(c1[2][0]), __float_as_uint(c1[2][1]), 0u, 0u, par);
  hint_signal(&g_f_kvp[head]);
}

struct Params {
  CUtensorMap tm_wqkv, tm_w1, tm_w2, tm_m, tm_wqkv64, tm_m64, tm_a;
  const __nv_bfloat16 *x, *b1, *b2, *wqkv, *w1, *w2, *wo;
  __nv_bfloat16* out;
};

__global__ void __cluster_dims__(2, 1, 1) __launch_bounds__(NTHREADS, 1) fused_kernel(const __grid_constant__ Params P) {
  extern __shared__ __align__(1024) uint8_t smem[];
  const uint32_t sbase = smem_u32(smem);
  const int tid = threadIdx.x, lane = tid & 31;
  const int warp = __shfl_sync(0xffffffffu, tid >> 5, 0);
  const int g = lane >> 2, t = lane & 3;
  const uint32_t ep = __shfl_sync(0xffffffffu, g_epoch[blockIdx.x], 0) + 1;
  const uint32_t par = ep & 1;
  STAMPW(0, 0);

  if (blockIdx.x >= 128) {
    const int a = blockIdx.x - 128;
    if (warp >= 8 && lane == 0) {
      const int id = a * 4 + (warp - 8);
      constexpr uint32_t CH = 9216 * 2;
      __nanosleep(1500);
#pragma unroll 1
      for (int i = id; i < 576; i += 16) {
        const char* p = i < 288 ? (const char*)P.w1 + (size_t)i * CH : (const char*)P.w2 + (size_t)(i - 288) * CH;
        asm volatile("cp.async.bulk.prefetch.L2.global [%0], %1;" ::"l"(p), "r"(CH) : "memory");
      }
    }
    __syncwarp();
#pragma unroll 1
    for (int u = a * 12 + warp; u < 256; u += 48) {
      const int head = 24 + (u & 7), blk = u >> 3;
      if (lane < 2) hint_wait(&g_f_qkv[(blk >> 1) * 8 + 3 + 2 * lane], 16 * ep);
      __syncwarp();
      uint32_t W[48];
      int tries = 0;
#pragma unroll 1
      do { d1_load(W, blk * 4, head, lane); } while (d1_bad(W, t, par) && ++tries < (1 << 20));
#pragma unroll
      for (int j = 0; j < 4; j++) d1_prep(W, j, t);
      d1_mma_store(W, head, blk, lane, par);
    }
    STAMPW(0, 3);
#pragma unroll 1
    for (int u = a * 12 + warp; u < 160; u += 48) {
      const int head = u / 5;
      if (lane == 0) hint_wait(&g_f_kvp[head], 32 * ep);
      __syncwarp();
      STAMPW(0, 1);
      uint4 v[32];
      int tries = 0;
      uint32_t bad;
#pragma unroll 1
      do {
        bad = 0;
#pragma unroll
        for (int j = 0; j < 32; j++) v[j] = ld_ll(&g_kvp[(u * 32 + j) * 32 + lane]);
#pragma unroll
        for (int j = 0; j < 32; j++) ll_chk(bad, v[j].x, v[j].z, par);
      } while (__any_sync(0xffffffffu, bad & 1) && ++tries < (1 << 20));
      float s0 = 0.f, s1 = 0.f, s2 = 0.f, s3 = 0.f;
#pragma unroll
      for (int j = 0; j < 32; j++) { s0 += __uint_as_float(v[j].x); s1 += __uint_as_float(v[j].y); s2 += __uint_as_float(v[j].z); s3 += __uint_as_float(v[j].w); }
      st_ll(&g_kvt[u * 32 + lane], __float_as_uint(s0), __float_as_uint(s1), __float_as_uint(s2), __float_as_uint(s3), par);
      hint_signal(&g_f_kvt[head]);
      STAMPW(0, 2);
    }
    __syncthreads();
    if (tid == 0) g_epoch[blockIdx.x] = ep;
    return;
  }

  const int cl = blockIdx.x >> 1, rank = blockIdx.x & 1;
  const int f = cl & 7, m = (cl >> 3) * 2 + rank;
  const int srole = f >= 6 ? 1 : 0;
  const uint32_t bar_full = sbase + SM_BAR, bar_empty = bar_full + 8 * NSTAGE, bar_xfree = bar_empty + 8 * NSTAGE, bar_ofull = bar_xfree + 72,
                 bar_d = bar_ofull + 72;

  if (tid == 0) {
#pragma unroll 1
    for (int i = 0; i < NSTAGE; i++) { mbar_init(bar_full + 8 * i, 1); mbar_init(bar_empty + 8 * i, 4); }
#pragma unroll 1
    for (int i = 0; i < 9; i++) { mbar_init(bar_xfree + 8 * i, 2); mbar_init(bar_ofull + 8 * i, 1); }
    mbar_init(bar_d, 1);
    asm volatile("fence.mbarrier_init.release.cluster;" ::: "memory");
  }
  __syncwarp();
  cluster_arrive_relaxed();

  if (warp >= 8) {
    const int srow = m * 128 + f * 16 + (warp - 8) * 4 + (lane >> 3);
    uint4 xs[9];
#pragma unroll
    for (int kb = 0; kb < 9; kb++) xs[kb] = __ldg(reinterpret_cast<const uint4*>(P.x + srow * D_) + (lane & 7) + kb * 8);
    auto stats = [&]() {
      const uint32_t* w = reinterpret_cast<const uint32_t*>(xs);
      float s0 = 0.f, s1 = 0.f;
#pragma unroll
      for (int i = 0; i < 36; i++) { s0 += bf_lo(w[i]); s1 += bf_hi(w[i]); }
      float sum = s0 + s1;
      sum += __shfl_xor_sync(0xffffffffu, sum, 1); sum += __shfl_xor_sync(0xffffffffu, sum, 2); sum += __shfl_xor_sync(0xffffffffu, sum, 4);
      const float mean = sum * (1.f / 576.f);
      s0 = 0.f; s1 = 0.f;
#pragma unroll
      for (int i = 0; i < 36; i++) { const float a = bf_lo(w[i]) - mean, b = bf_hi(w[i]) - mean; s0 = fmaf(a, a, s0); s1 = fmaf(b, b, s1); }
      float sq = s0 + s1;
      sq += __shfl_xor_sync(0xffffffffu, sq, 1); sq += __shfl_xor_sync(0xffffffffu, sq, 2); sq += __shfl_xor_sync(0xffffffffu, sq, 4);
      const float rstd = rsqrtf(sq * (1.f / 576.f) + 1e-5f);
      if ((lane & 7) == 0)
        asm volatile("{.reg .b64 a; mov.b64 a, {%1,%2}; st.relaxed.gpu.global.b64 [%0], a;}" ::"l"(&g_stat[srow]), "r"((__float_as_uint(rstd) & ~1u) | par), "r"(pack_bf16(-mean, -mean)) : "memory");
    };
    stats();
    asm volatile("setmaxnreg.dec.sync.aligned.u32 56;");
    cluster_wait();
    if (warp == 8) {
      if (lane == 0) {
        uint32_t stage = 0, phase = 1;
        const uint32_t sb = sbase + SM_B;
#pragma unroll 1
        for (int tl = 2 * srole; tl < 8 + 2 * srole; tl++) {
          const CUtensorMap* map = tl == 0 ? &P.tm_wqkv : (tl == 1 ? &P.tm_wqkv64 : (tl < 5 ? &P.tm_w1 : (tl < 8 ? &P.tm_w2 : (tl == 8 ? &P.tm_m : &P.tm_m64))));
          const int col = tl < 2 ? 288 * f + 192 * tl : (tl < 5 ? 576 * f + 192 * (tl - 2) : (tl < 8 ? 192 * (tl - 5) : (tl == 8 ? 192 * (f - 5) : 96 * (f - 6))));
          const bool perm = tl >= 5 && tl < 8;
          const bool z = (tl & 7) == 1;
          if (tl == 8) { flag_wait(g_f_m, 128 * ep); asm volatile("fence.proxy.async.global;" ::: "memory"); }
          const int cs = z ? 32 : 64, rs = z ? 64 : 32, nst = z ? 9 : 18;
#pragma unroll 1
          for (int st = 0; st < nst; st++) {
            int row = st * rs;
            if (perm) row += 576 * f + ((st < 6) ? 192 : (st < 12 ? -192 : 0));
            mbar_wait(bar_empty + 8 * stage, phase);
            mbar_expect(bar_full + 8 * stage, 12288);
            const uint32_t dst = sb + stage * STAGE_BYTES;
            if (((st ^ rank) & 1) == 0) {
              tma2d_mc(dst, map, col, row, bar_full + 8 * stage);
              tma2d_mc(dst + 8192, map, col + 2 * cs, row, bar_full + 8 * stage);
            } else {
              tma2d_mc(dst + 4096, map, col + cs, row, bar_full + 8 * stage);
            }
            if (++stage == NSTAGE) { stage = 0; phase ^= 1; }
          }
        }
      }
      __syncwarp();
    } else {
      const int aw = warp - 9, ta = tid - 288;
      const int hi = f >> 2;
      float* skv = reinterpret_cast<float*>(smem + SM_KV);
      const int hM = 4 * f + (m >> 2), nM = 144 * (m & 3) + 2 * (ta < 72 ? ta : 0);
      uint32_t wo[18];
#pragma unroll
      for (int e = 0; e < 18; e++) wo[e] = __ldg(reinterpret_cast<const uint32_t*>(P.wo + (hM * 18 + e) * D_ + nM));
      if (aw == 0 && !srole) {
        if (lane < 2) hint_wait(&g_f_qkv[m * 8 + 2 + 2 * lane + hi], 16 * ep);
        __syncwarp();
        if (lane == 0) mbar_arrive(bar_d);
        STAMP(20);
      }
#pragma unroll 1
      for (int hh = aw; hh < 4; hh += 3) {
        if (lane == 0) hint_wait(&g_f_kvt[4 * f + hh], 5 * ep);
        __syncwarp();
        uint4 kv[5];
        int tries = 0;
        uint32_t bad;
#pragma unroll 1
        do {
          bad = 0;
#pragma unroll
          for (int j = 0; j < 5; j++) kv[j] = ld_ll(&g_kvt[((4 * f + hh) * 5 + j) * 32 + lane]);
#pragma unroll
          for (int j = 0; j < 5; j++) ll_chk(bad, kv[j].x, kv[j].z, par);
        } while (__any_sync(0xffffffffu, bad & 1) && ++tries < (1 << 20));
        uint2* row = reinterpret_cast<uint2*>(skv + (hh * 19 + g) * 20 + 2 * t);
#pragma unroll
        for (int j = 0; j < 3; j++)
          if (j < 2 || t < 2) { row[4 * j] = make_uint2(kv[j].x, kv[j].y); row[80 + 4 * j] = make_uint2(kv[j].z, kv[j].w); }
        if (g < 3) {
          row[160] = make_uint2(kv[3].x, kv[3].y); row[164] = make_uint2(kv[3].z, kv[3].w);
          if (t < 2) row[168] = make_uint2(kv[4].x, kv[4].y);
        }
      }
      asm volatile("bar.sync 5, 96;" ::: "memory");
      STAMPW(9, 22);
      if (ta < 72) {
#pragma unroll 1
        for (int d0 = 0; d0 < 20; d0 += 4) {
          float ac[8];
#pragma unroll
          for (int q = 0; q < 8; q++) ac[q] = 0.f;
#pragma unroll
          for (int e = 0; e < 18; e++) {
            const float4 k4 = *reinterpret_cast<const float4*>(skv + ((m >> 2) * 19 + e) * 20 + d0);
            const float w0 = bf_lo(wo[e]), w1 = bf_hi(wo[e]);
            ac[0] = fmaf(k4.x, w0, ac[0]); ac[1] = fmaf(k4.x, w1, ac[1]); ac[2] = fmaf(k4.y, w0, ac[2]); ac[3] = fmaf(k4.y, w1, ac[3]);
            ac[4] = fmaf(k4.z, w0, ac[4]); ac[5] = fmaf(k4.z, w1, ac[5]); ac[6] = fmaf(k4.w, w0, ac[6]); ac[7] = fmaf(k4.w, w1, ac[7]);
          }
#pragma unroll
          for (int q = 0; q < 4; q++)
            if (d0 + q < 18) *reinterpret_cast<uint32_t*>(g_m + (hM * 18 + d0 + q) * D_ + nM) = pack_bf16(ac[2 * q], ac[2 * q + 1]);
        }
      }
      __syncwarp();
      if (lane == 0) hint_wait(&g_f_qkv[m * 8 + hi], 16 * ep);
      __syncwarp();
      {
        const uint32_t* qf = reinterpret_cast<const uint32_t*>(g_qkvf) + m * 8 * 108 * 128 + g * 16;
        uint2 nx[3];
        auto ldq = [&](int it) {
#pragma unroll
          for (int b = 0; b < 3; b++) nx[b] = ld_ll64(qf + (it >> 2) * 108 * 128 + coloff(72 * f + (it & 3) * 18 + 8 * b + 2 * t));
        };
        ldq(aw);
#pragma unroll 1
        for (int it = aw; it < 32; it += 3) {
          int tries = 0;
#pragma unroll 1
          while (true) {
            uint32_t bad = 0;
            ll_chk(bad, nx[0].x, nx[1].x, par); ll_chk(bad, t == 0 ? nx[2].x : par, par, par);
            if (!__any_sync(0xffffffffu, bad & 1) || ++tries > (1 << 20)) break;
            ldq(it);
          }
          const uint2 q0 = nx[0], q1 = nx[1], q2 = nx[2];
          if (it + 3 < 32) ldq(it + 3);
          float p[12] = {phi(bf_lo(q0.x)), phi(bf_hi(q0.x)), phi(bf_lo(q1.x)), phi(bf_hi(q1.x)), phi(bf_lo(q2.x)), phi(bf_hi(q2.x)),
                         phi(bf_lo(q0.y)), phi(bf_hi(q0.y)), phi(bf_lo(q1.y)), phi(bf_hi(q1.y)), phi(bf_lo(q2.y)), phi(bf_hi(q2.y))};
          const float2* zp = reinterpret_cast<const float2*>(skv + ((it & 3) * 19 + 18) * 20 + 2 * t);
          const float2 z0 = zp[0], z1 = zp[4], z2 = *reinterpret_cast<const float2*>(skv + ((it & 3) * 19 + 18) * 20 + 16);
          float d0 = p[0] * z0.x + p[1] * z0.y + p[2] * z1.x + p[3] * z1.y, d1 = p[6] * z0.x + p[7] * z0.y + p[8] * z1.x + p[9] * z1.y;
          if (t == 0) { d0 += p[4] * z2.x + p[5] * z2.y; d1 += p[10] * z2.x + p[11] * z2.y; }
          d0 += __shfl_xor_sync(0xffffffffu, d0, 1); d1 += __shfl_xor_sync(0xffffffffu, d1, 1);
          d0 += __shfl_xor_sync(0xffffffffu, d0, 2); d1 += __shfl_xor_sync(0xffffffffu, d1, 2);
          const float r0 = __fdividef(1.f, d0 + 1e-6f), r1 = __fdividef(1.f, d1 + 1e-6f);
          __nv_bfloat16* po = g_a + (m * 128 + (it >> 2) * 16 + g) * D_ + 72 * f + (it & 3) * 18 + 2 * t;
#pragma unroll
          for (int b = 0; b < 3; b++)
            if (b < 2 || t == 0) {
              *reinterpret_cast<uint32_t*>(po + 8 * b) = pack_bf16(p[2 * b] * r0, p[2 * b + 1] * r0);
              *reinterpret_cast<uint32_t*>(po + 8 * D_ + 8 * b) = pack_bf16(p[6 + 2 * b] * r1, p[7 + 2 * b] * r1);
            }
        }
      }
      asm volatile("fence.proxy.async.global;" ::: "memory");
      asm volatile("bar.sync 5, 96;" ::: "memory");
      if (ta == 0) {
        asm volatile("fence.acq_rel.gpu;" ::: "memory");
        asm volatile("red.relaxed.gpu.global.add.u32 [%0], 1;" ::"l"(&g_f_a[m]) : "memory");
        asm volatile("red.relaxed.gpu.global.add.u32 [%0], 1;" ::"l"(g_f_m) : "memory");
      }
      __syncwarp();
      STAMPW(9, 23);
      if (srole && aw == 2) {
        if (lane == 0) {
          flag_wait(&g_f_a[m], 8 * ep);
          asm volatile("fence.proxy.async.global;" ::: "memory");
#pragma unroll 1
          for (int kb = 0; kb < 9; kb++) {
            mbar_wait(bar_xfree + 8 * kb, 0);
            mbar_expect(bar_ofull + 8 * kb, 16384);
            tma2d(sbase + SM_A + kb * 16384, &P.tm_a, kb * 64, m * 128, bar_ofull + 8 * kb);
          }
        }
        __syncwarp();
      }
      const int rbg = m * 8 + f;
#pragma unroll 1
      for (int ch = 0; ch < 2; ch++) {
        if (lane == 0) hint_wait(&g_f_rb[rbg * 8 + ch], 8 * ep);
        __syncwarp();
        STAMPW(9, 24 + 2 * ch);
#pragma unroll 1
        for (int v = ch * 12 + aw * 4; v < ch * 12 + aw * 4 + 4; v++) {
          const uint32_t b0 = __ldg(reinterpret_cast<const uint32_t*>(P.b2 + 16 * v + 2 * t)), b1 = __ldg(reinterpret_cast<const uint32_t*>(P.b2 + 16 * v + 8 + 2 * t));
          uint4 p[8];
          int tries = 0;
          uint32_t bad;
#pragma unroll 1
          do {
            bad = 0;
#pragma unroll
            for (int i = 0; i < 8; i++) p[i] = ld_ll(&g_part[((rbg * 8 + i) * 36 + v) * 32 + lane]);
#pragma unroll
            for (int i = 0; i < 8; i++) ll_chk(bad, p[i].x, p[i].z, par);
          } while (__any_sync(0xffffffffu, bad & 1) && ++tries < (1 << 20));
          float gt[8];
          gate_vec(p, b0, b1, gt);
          st_ll(&g_g[(rbg * 24 + v) * 32 + lane], pack_bf16(gt[0], gt[1]), pack_bf16(gt[2], gt[3]), pack_bf16(gt[4], gt[5]), pack_bf16(gt[6], gt[7]), par);
        }
        hint_signal(&g_f_rb[rbg * 8 + 5 + ch]);
        STAMPW(9, 25 + 2 * ch);
      }
    }
    cluster_arrive_relaxed();
    cluster_wait();
  } else {
    const int wg = warp >> 2;
    {
      const int rs = lane >> 3, j = lane & 7;
      uint4 xv[4][9];
#pragma unroll
      for (int it = 0; it < 4; it++)
#pragma unroll
        for (int kb = 0; kb < 9; kb++) xv[it][kb] = __ldg(reinterpret_cast<const uint4*>(P.x + (m * 128 + warp * 16 + it * 4 + rs) * D_) + j + kb * 8);
      uint32_t bw0 = __ldg(reinterpret_cast<const uint32_t*>(P.b1 + 576 * f) + tid), bw1 = tid < 32 ? __ldg(reinterpret_cast<const uint32_t*>(P.b1 + 576 * f) + 256 + tid) : 0u;
      uint2 st[4];
      int tries = 0;
      uint32_t bad;
#pragma unroll 1
      do {
        bad = 0;
#pragma unroll
        for (int it = 0; it < 4; it++) st[it] = ld_ll64(reinterpret_cast<const uint32_t*>(&g_stat[m * 128 + warp * 16 + it * 4 + rs]));
        ll_chk(bad, st[0].x, st[1].x, par); ll_chk(bad, st[2].x, st[3].x, par);
      } while (__any_sync(0xffffffffu, bad & 1) && ++tries < (1 << 22));
      STAMPW(0, 19);
#pragma unroll
      for (int it = 0; it < 4; it++) {
        const uint32_t nm = st[it].y;
        uint8_t* dst = smem + SM_A + (warp * 16 + it * 4 + rs) * 128 + ((j ^ ((it * 4 + rs) & 7)) << 4);
#pragma unroll
        for (int kb = 0; kb < 9; kb++) {
          const uint4 w = xv[it][kb];
          *reinterpret_cast<uint4*>(dst + kb * 16384) = make_uint4(hadd2(w.x, nm), hadd2(w.y, nm), hadd2(w.z, nm), hadd2(w.w, nm));
        }
        if (j < 2) reinterpret_cast<uint32_t*>(smem + SM_RSTD)[j * 128 + warp * 16 + it * 4 + rs] = j == 0 ? st[it].x : 0x3f800000u;
      }
      reinterpret_cast<float2*>(smem + SM_BIAS)[tid] = make_float2(bf_lo(bw0), bf_hi(bw0));
      if (tid < 128) reinterpret_cast<float2*>(smem + SM_BIAS)[256 + tid] = make_float2(bf_lo(bw1), bf_hi(bw1));
      asm volatile("fence.proxy.async.shared::cta;" ::: "memory");
    }
    asm volatile("setmaxnreg.inc.sync.aligned.u32 224;");
    cluster_wait();
    asm volatile("bar.sync 1, 256;" ::: "memory");
    STAMPW(0, 1);
    Ctx c;
    c.full = bar_full;
    c.emb = __shfl_sync(0xffffffffu, mapa(bar_empty, (warp & 3) == 0 ? rank : (rank ^ 1)), 0);
    c.sig = lane == 0 && (warp & 3) < 2;
    c.stage = 0; c.phase = 0; c.prev = ~0u;
    c.dB = (((sbase + SM_B) & 0x3FFFF) >> 4) | ((4096u >> 4) << 16);
    c.dA = (((sbase + SM_A + wg * 8192) & 0x3FFFF) >> 4) | (1u << 16);
    const bool leader = (lane == 0) && ((warp & 3) == 0);

    const int rb = m * 8 + warp;
    const uint32_t bias_t = sbase + SM_BIAS + 8 * t;
    const uint32_t hst = sbase + SM_A + (warp * 16 + (lane & 7) + ((lane >> 3) & 1) * 8) * 128 + (((lane >> 4) ^ (lane & 7)) << 4);
    auto wg_sync = [&]() {
      asm volatile("fence.proxy.async.shared::cta;" ::: "memory");
      if (wg == 0) asm volatile("bar.sync 2, 128;" ::: "memory"); else asm volatile("bar.sync 3, 128;" ::: "memory");
    };
    float A[96], B[96];
#pragma unroll
    for (int i = 0; i < 96; i++) B[i] = 0.f;
#define SEL8(E, ACC, OFF, HF) float E[8]; _Pragma("unroll") for (int q = 0; q < 8; q++) E[q] = fmaf((HF) ? ACC[48 + (OFF) + q] : ACC[(OFF) + q], (q & 2) ? r1 : r0, (q & 1) ? bs[q >> 2].y : bs[q >> 2].x);
#define LDS_R(SCALED) float r0, r1; asm volatile("ld.shared.f32 %0, [%1];" : "=f"(r0) : "r"(rst + ((SCALED) ? 0 : 512))); asm volatile("ld.shared.f32 %0, [%1];" : "=f"(r1) : "r"(rst + ((SCALED) ? 32 : 544)));
    const uint32_t rst = sbase + SM_RSTD + (warp * 16 + g) * 4;
#pragma unroll 1
    for (int i = srole; i < 4 + srole; i++) {
      {
        const uint32_t ow = i == 4 ? bar_ofull : 0u;
        if (ow) mbar_wait(ow, 0);
        issue192(A, c, 0, true);
        const int ln = opaque(lane);
        uint4* dst = i == 1 ? g_qkvf + (rb * 108 + 18 * f + 12) * 32 + ln : g_part + ((rb * 8 + f) * 36 + (i == 3 ? 0 : 24)) * 32 + ln;
        const int nhf = i == 0 ? 0 : (i == 1 ? 1 - srole : 2);
        const uint32_t bsa = bias_t + (i == 2 ? 192 : 576) * 4;
        LDS_R(i <= 2)
        retire(c);
        if (ow && leader) mbar_arrive(bar_xfree + 64);
        fence_regs<96>(B);
        int s = 1;
        if (i == 2) {
#pragma unroll 1
          for (; s < 3; s++) { issue192(A, c, s); retire(c); }
        }
#pragma unroll 1
        for (int hf = 0; hf < nhf; hf++) {
#pragma unroll
          for (int u = 0; u < 6; u++, s++) {
            float2 bs[2];
            lds_bias(bs, bsa + (96 * hf + 16 * u) * 4);
            if ((u & 1) && ow) mbar_wait(ow + 4 * s, 0);
            issue192(A, c, s);
            SEL8(E, B, 8 * u, hf)
            if (i == 2) {
              const int q = 6 * hf + u;
              stsm4((hst ^ ((q & 3) << 5)) + (q >> 2) * 16384, gelu_group(E));
            } else part_groups<0, 1>(E, dst + u * 32, par);
            retire(c);
          }
          dst += 6 * 32;
        }
        if (nhf != 0 && i != 2) hint_signal(i == 1 ? &g_f_qkv[m * 8 + f] : &g_f_rb[rb * 8 + (i == 3 ? 0 : 2)]);
        const bool d1 = i == 1 && !srole;
        uint32_t W[48];
#pragma unroll
        for (int q = 0; q < 48; q++) W[q] = 0;
#pragma unroll 1
        for (; s < 17; s++) {
          if (ow && !(s & 1)) mbar_wait(ow + 4 * s, 0);
          issue192(A, c, s);
          if (d1) {
            if (s == 10 || s == 12) {
              if (s == 10) mbar_wait(bar_d, 0);
              int tries = 0;
#pragma unroll 1
              while (s == 10 || (d1_bad(W, t, par) && ++tries < (1 << 20))) {
                d1_load(W, m * 8 + (warp & 1) * 4, 4 * f + (warp >> 1), opaque(lane));
                if (s == 10) break;
              }
            }
            if (s == 12) d1_prep(W, 0, t);
            if (s == 13) d1_prep(W, 1, t);
            if (s == 14) d1_prep(W, 2, t);
            if (s == 15) d1_prep(W, 3, t);
            if (s == 16) {
              wg_wait<0>();
              asm volatile("bar.sync 4, 256;" ::: "memory");
              d1_mma_store(W, 4 * f + (warp >> 1), m * 2 + (warp & 1), opaque(lane), par);
              asm volatile("bar.sync 4, 256;" ::: "memory");
              STAMPW(0, 21);
            }
          } else if (i == 2) {
            if (s == 15) {
              const uint4* hsp = g_hsp + (blockIdx.x * 8 + warp) * 12 * 32 + opaque(lane);
#pragma unroll
              for (int q = 0; q < 12; q++) { const uint4 v = ldcg128(hsp + q * 32); W[4 * q] = v.x; W[4 * q + 1] = v.y; W[4 * q + 2] = v.z; W[4 * q + 3] = v.w; }
            }
            if (s == 16) wg_sync();
          }
          retire(c);
        }
        issue192(A, c, 17);
        if (i == 2) {
#pragma unroll
          for (int q = 0; q < 12; q++) stsm4((hst ^ ((q & 3) << 5)) + (3 + (q >> 2)) * 16384, make_uint4(W[4 * q], W[4 * q + 1], W[4 * q + 2], W[4 * q + 3]));
        }
        retire(c);
      }
      STAMPW(0, 2 + 2 * i);
      if ((i & 3) == 0) {
        issue96(B, c, 0, true);
        const int ln = opaque(lane);
        uint4* dst = i == 0 ? g_qkvf + (rb * 108 + 18 * f) * 32 + ln : g_s + (rb * 24 + 12 * (f - 6)) * 32 + ln;
        LDS_R(i == 0)
        retire(c);
        fence_regs<96>(A);
#pragma unroll 1
        for (int s = 1; s < 8; s++) {
          issue96(B, c, s, false);
#pragma unroll
          for (int u = 0; u < 6; u++)
            if (s == u + 1) {
              float E[16];
#pragma unroll
              for (int q = 0; q < 16; q++) E[q] = A[16 * u + q] * ((q & 2) ? r1 : r0);
              part_groups<0, 2>(E, dst + 2 * u * 32, par);
            }
          if (s == 6) hint_signal(i == 0 ? &g_f_qkv[m * 8 + f] : &g_f_rb[rb * 8 + f - 3]);
          retire(c);
        }
        issue96(B, c, 8, false);
        retire(c);
      } else {
        issue192(B, c, 0, true);
        const int ln = opaque(lane);
        uint4* dst = i == 1 ? g_hsp + (blockIdx.x * 8 + warp) * 12 * 32 + ln : g_part + ((rb * 8 + f) * 36 + 12) * 32 + ln;
        const bool xf = i == 3 && srole && leader;
        const uint32_t bsa = bias_t + (i == 1 ? 0 : (i == 2 ? 384 : 576)) * 4;
        LDS_R(i <= 2)
        retire(c);
        fence_regs<96>(A);
        int s = 1;
#pragma unroll 1
        for (int hf = 0; hf < 2; hf++) {
#pragma unroll
          for (int u = 0; u < 6; u++, s++) {
            float2 bs[2];
            lds_bias(bs, bsa + (96 * hf + 16 * u) * 4);
            issue192(B, c, s);
            SEL8(E, A, 8 * u, hf)
            if (i != 3) {
              const uint4 h = gelu_group(E);
              if (i == 1) dst[u * 32] = h;
              else {
                const int q = 6 * hf + u;
                stsm4((hst ^ ((q & 3) << 5)) + (6 + (q >> 2)) * 16384, h);
                if (u == 3) wg_sync();
              }
            } else part_groups<0, 1>(E, dst + u * 32, par);
            retire(c);
            if ((u & 1) && xf) mbar_arrive(bar_xfree + 4 * s - 8);
          }
          dst += 6 * 32;
        }
        if (i == 3) hint_signal(&g_f_rb[rb * 8 + 1]);
#pragma unroll 1
        for (; s < 17; s++) {
          issue192(B, c, s);
          if (s == 14 && i == 2) wg_sync();
          retire(c);
          if ((s & 1) == 0 && xf) mbar_arrive(bar_xfree + 4 * s - 8);
        }
        issue192(B, c, 17);
        retire(c);
      }
      STAMPW(0, 3 + 2 * i);
    }

    const int ln = opaque(lane);
    const __nv_bfloat16* xp = P.x + (rb * 16 + (ln >> 2)) * D_ + 2 * (ln & 3);
    __nv_bfloat16* op = P.out + (rb * 16 + (ln >> 2)) * D_ + 2 * (ln & 3);
    auto ldx = [&](uint32_t* xx, int col) {
      xx[0] = __ldg(reinterpret_cast<const uint32_t*>(xp + col)); xx[1] = __ldg(reinterpret_cast<const uint32_t*>(xp + 8 * D_ + col));
      xx[2] = __ldg(reinterpret_cast<const uint32_t*>(xp + col + 8)); xx[3] = __ldg(reinterpret_cast<const uint32_t*>(xp + 8 * D_ + col + 8));
    };
    auto stout = [&](int col, uint4 sv, uint4 gv, const uint32_t* xx) {
      *reinterpret_cast<uint32_t*>(op + col) = hfma2(sv.x, gv.x, xx[0]); *reinterpret_cast<uint32_t*>(op + 8 * D_ + col) = hfma2(sv.y, gv.y, xx[1]);
      *reinterpret_cast<uint32_t*>(op + col + 8) = hfma2(sv.z, gv.z, xx[2]); *reinterpret_cast<uint32_t*>(op + 8 * D_ + col + 8) = hfma2(sv.w, gv.w, xx[3]);
    };
    if (srole) {
      const int cb = 96 * (f - 6);
      uint32_t xx[24];
      uint4 gg[6];
#pragma unroll
      for (int q = 0; q < 6; q++) ldx(&xx[4 * q], cb + 16 * q);
      int tries = 0;
      uint32_t bad;
#pragma unroll 1
      do {
        bad = 0;
#pragma unroll
        for (int q = 0; q < 6; q++) gg[q] = ld_ll(&g_g[(rb * 24 + 6 * (f - 6) + q) * 32 + ln]);
#pragma unroll
        for (int q = 0; q < 6; q++) ll_chk(bad, gg[q].x, gg[q].z, par);
      } while (__any_sync(0xffffffffu, bad & 1) && ++tries < (1 << 20));
      STAMPW(0, 14);
      wg_wait<0>();
      c.release_prev();
      fence_regs<48>(B);
#pragma unroll
      for (int q = 0; q < 6; q++)
        stout(cb + 16 * q, make_uint4(pack_bf16(B[8 * q], B[8 * q + 1]), pack_bf16(B[8 * q + 2], B[8 * q + 3]), pack_bf16(B[8 * q + 4], B[8 * q + 5]), pack_bf16(B[8 * q + 6], B[8 * q + 7])), gg[q], &xx[4 * q]);
    } else {
      wg_wait<0>();
      c.release_prev();
      fence_regs<96>(B);
      part_groups<0, 12>(B, g_part + ((rb * 8 + f) * 36 + 24) * 32 + ln, par);
      hint_signal(&g_f_rb[rb * 8 + 2]);
      STAMPW(0, 12);
      uint32_t xx[16], bb[4];
#pragma unroll
      for (int j = 0; j < 4; j++) ldx(&xx[4 * j], 192 + 192 * (j >> 1) + 32 * f + 16 * (j & 1));
#pragma unroll
      for (int j = 0; j < 4; j++) bb[j] = __ldg(reinterpret_cast<const uint32_t*>(P.b2 + 384 + 32 * f + 8 * j + 2 * (ln & 3)));
      uint4 sv[4], gg[2];
      int tries = 0;
      uint32_t bad;
#pragma unroll 1
      do {
        bad = 0;
#pragma unroll
        for (int j = 0; j < 4; j++) sv[j] = ld_ll(&g_s[(rb * 24 + 12 * (j >> 1) + 2 * f + (j & 1)) * 32 + ln]);
#pragma unroll
        for (int j = 0; j < 2; j++) gg[j] = ld_ll(&g_g[(rb * 24 + 12 + 2 * f + j) * 32 + ln]);
#pragma unroll
        for (int j = 0; j < 4; j++) ll_chk(bad, sv[j].x, sv[j].z, par);
#pragma unroll
        for (int j = 0; j < 2; j++) ll_chk(bad, gg[j].x, gg[j].z, par);
      } while (__any_sync(0xffffffffu, bad & 1) && ++tries < (1 << 20));
#pragma unroll
      for (int j = 0; j < 2; j++) stout(192 + 32 * f + 16 * j, sv[j], gg[j], &xx[4 * j]);
      STAMPW(0, 13);
      if (ln == 0) hint_wait(&g_f_rb[rb * 8 + 2], 8u * ep);
      __syncwarp();
      STAMPW(0, 14);
      uint4 p[2][8];
      tries = 0;
#pragma unroll 1
      do {
        bad = 0;
#pragma unroll
        for (int j = 0; j < 2; j++)
#pragma unroll
          for (int k = 0; k < 8; k++) p[j][k] = ld_ll(&g_part[((rb * 8 + k) * 36 + 24 + 2 * f + j) * 32 + ln]);
#pragma unroll
        for (int j = 0; j < 2; j++)
#pragma unroll
          for (int k = 0; k < 8; k++) ll_chk(bad, p[j][k].x, p[j][k].z, par);
      } while (__any_sync(0xffffffffu, bad & 1) && ++tries < (1 << 20));
#pragma unroll
      for (int j = 0; j < 2; j++) {
        float gt[8];
        gate_vec(p[j], bb[2 * j], bb[2 * j + 1], gt);
        stout(384 + 32 * f + 16 * j, sv[2 + j], make_uint4(pack_bf16(gt[0], gt[1]), pack_bf16(gt[2], gt[3]), pack_bf16(gt[4], gt[5]), pack_bf16(gt[6], gt[7])), &xx[8 + 4 * j]);
      }
    }
    STAMPW(0, 15);
    cluster_arrive_relaxed();
    cluster_wait();
    STAMPW(0, 16);
    if (tid == 0) g_epoch[blockIdx.x] = ep;
  }
}

typedef CUresult (*EncFn)(CUtensorMap*, CUtensorMapDataType, cuuint32_t, void*, const cuuint64_t*, const cuuint64_t*, const cuuint32_t*, const cuuint32_t*,
                          CUtensorMapInterleave, CUtensorMapSwizzle, CUtensorMapL2promotion, CUtensorMapFloatOOBfill);

void make_map(EncFn enc, CUtensorMap* tm, const void* ptr, int rows, int cols, int box_rows, bool sw64 = false) {
  cuuint64_t gd[2] = {(cuuint64_t)cols, (cuuint64_t)rows};
  cuuint64_t gs[1] = {(cuuint64_t)cols * 2};
  cuuint32_t bx[2] = {sw64 ? 32u : 64u, (cuuint32_t)box_rows};
  cuuint32_t es[2] = {1, 1};
  enc(tm, CU_TENSOR_MAP_DATA_TYPE_BFLOAT16, 2, const_cast<void*>(ptr), gd, gs, bx, es, CU_TENSOR_MAP_INTERLEAVE_NONE, sw64 ? CU_TENSOR_MAP_SWIZZLE_64B : CU_TENSOR_MAP_SWIZZLE_128B,
      CU_TENSOR_MAP_L2_PROMOTION_L2_256B, CU_TENSOR_MAP_FLOAT_OOB_FILL_NONE);
}

}

extern "C" void kernel_launch(void* const* d_in, const int* in_sizes, int n_in, void* d_out, int out_size) {
  (void)in_sizes; (void)n_in; (void)out_size;
  static EncFn enc = nullptr;
  static void *a_ptr = nullptr, *m_ptr = nullptr;
  if (!enc) {
    void* fn = nullptr; cudaDriverEntryPointQueryResult q;
    cudaGetDriverEntryPoint("cuTensorMapEncodeTiled", &fn, cudaEnableDefault, &q);
    enc = (EncFn)fn;
    cudaFuncSetAttribute(fused_kernel, cudaFuncAttributeMaxDynamicSharedMemorySize, SMEM_BYTES);
    cudaGetSymbolAddress(&a_ptr, g_a);
    cudaGetSymbolAddress(&m_ptr, g_m);
  }
  Params P;
  P.x = (const __nv_bfloat16*)d_in[0];
  P.wqkv = (const __nv_bfloat16*)d_in[1];
  P.wo = (const __nv_bfloat16*)d_in[2];
  P.w1 = (const __nv_bfloat16*)d_in[4];
  P.b1 = (const __nv_bfloat16*)d_in[5];
  P.w2 = (const __nv_bfloat16*)d_in[6];
  P.b2 = (const __nv_bfloat16*)d_in[7];
  P.out = (__nv_bfloat16*)d_out;
  make_map(enc, &P.tm_wqkv, P.wqkv, D_, Q3_, 32);
  make_map(enc, &P.tm_w1, P.w1, D_, F_, 32);
  make_map(enc, &P.tm_w2, P.w2, F_, D_, 32);
  make_map(enc, &P.tm_m, m_ptr, D_, D_, 32);
  make_map(enc, &P.tm_wqkv64, P.wqkv, D_, Q3_, 64, true);
  make_map(enc, &P.tm_m64, m_ptr, D_, D_, 64, true);
  make_map(enc, &P.tm_a, a_ptr, S_, D_, 128);
  fused_kernel<<<NCTAS, NTHREADS, SMEM_BYTES, cudaStreamPerThread>>>(P);
}
```

```cpp
#include <cuda_runtime.h>
#include <cuda.h>
#include <cuda_bf16.h>
#include <stdint.h>

namespace {

constexpr int S_ = 2048, D_ = 576, F_ = 4608, Q3_ = 1728;
constexpr int NSTAGE = 6, STAGE_BYTES = 12288;
constexpr int SM_A = 0, SM_B = 147456, SM_BIAS = SM_B + NSTAGE * STAGE_BYTES, SM_RSTD = SM_BIAS + 2304, SM_KV = SM_RSTD + 512, SM_BAR = SM_KV + 4 * 19 * 80;
constexpr int SMEM_BYTES = SM_BAR + 320;
constexpr int NTHREADS = 384;
constexpr int NCTAS = 132;

__device__ uint4 g_qkvf[(128 * 108 + 1) * 32];
__device__ __align__(1024) __nv_bfloat16 g_a[S_ * D_];
__device__ __align__(1024) __nv_bfloat16 g_m[D_ * D_];
__device__ uint4 g_kvp[32 * 5 * 32 * 32];
__device__ uint4 g_kvt[32 * 5 * 32];
__device__ uint4 g_part[128 * 8 * 36 * 32];
__device__ uint4 g_s[128 * 24 * 32];
__device__ uint4 g_g[128 * 24 * 32];
__device__ uint4 g_hsp[128 * 12 * 256];
__device__ uint32_t g_f_qkv[16 * 8];
__device__ uint32_t g_f_kvp[32];
__device__ uint32_t g_f_kvt[32];
__device__ uint32_t g_f_a[16];
__device__ uint32_t g_f_m[1];
__device__ uint32_t g_f_rb[128 * 8];
__device__ uint2 g_stat[S_];
__device__ uint32_t g_epoch[NCTAS];

#define STAMP(i)
#define STAMPW(w, i)
#define WSTAMP(i)
__device__ __forceinline__ uint32_t smem_u32(const void* p) { return (uint32_t)__cvta_generic_to_shared(p); }
__device__ __forceinline__ void mbar_init(uint32_t a, int c) { asm volatile("mbarrier.init.shared::cta.b64 [%0], %1;" ::"r"(a), "r"(c)); }
__device__ __forceinline__ void mbar_expect(uint32_t a, uint32_t b) { asm volatile("mbarrier.arrive.expect_tx.shared::cta.b64 _, [%0], %1;" ::"r"(a), "r"(b) : "memory"); }
__device__ __forceinline__ void mbar_arrive(uint32_t a) { asm volatile("mbarrier.arrive.shared::cta.b64 _, [%0];" ::"r"(a) : "memory"); }
__device__ __forceinline__ void mbar_arrive_cl(uint32_t a) { asm volatile("mbarrier.arrive.shared::cluster.b64 _, [%0];" ::"r"(a) : "memory"); }
__device__ __forceinline__ uint32_t mapa(uint32_t a, uint32_t cta) { uint32_t r; asm volatile("mapa.shared::cluster.u32 %0, %1, %2;" : "=r"(r) : "r"(a), "r"(cta)); return r; }
__device__ __forceinline__ void mbar_wait(uint32_t a, uint32_t ph) {
  uint32_t ok; int it = 0;
#pragma unroll 1
  do {
    asm volatile("{.reg .pred p; mbarrier.try_wait.parity.shared::cta.b64 p, [%1], %2; selp.u32 %0,1,0,p;}" : "=r"(ok) : "r"(a), "r"(ph) : "memory");
  } while (!ok && ++it < (1 << 18));
}
__device__ __forceinline__ void tma2d(uint32_t dst, const CUtensorMap* m, int c0, int c1, uint32_t bar) {
  asm volatile("cp.async.bulk.tensor.2d.shared::cluster.global.mbarrier::complete_tx::bytes [%0], [%1, {%3,%4}], [%2];" ::"r"(dst), "l"(m), "r"(bar), "r"(c0), "r"(c1) : "memory");
}
__device__ __forceinline__ void tma2d_mc(uint32_t dst, const CUtensorMap* m, int c0, int c1, uint32_t bar) {
  asm volatile("cp.async.bulk.tensor.2d.shared::cluster.global.mbarrier::complete_tx::bytes.multicast::cluster [%0], [%1, {%3,%4}], [%2], %5;" ::"r"(dst), "l"(m), "r"(bar), "r"(c0), "r"(c1), "h"((uint16_t)3) : "memory");
}
__device__ __forceinline__ void cluster_arrive_relaxed() { asm volatile("barrier.cluster.arrive.relaxed.aligned;" ::: "memory"); }
__device__ __forceinline__ void cluster_wait() { asm volatile("barrier.cluster.wait.acquire.aligned;" ::: "memory"); }
__device__ __forceinline__ void wg_fence() { asm volatile("wgmma.fence.sync.aligned;" ::: "memory"); }
__device__ __forceinline__ void wg_commit() { asm volatile("wgmma.commit_group.sync.aligned;" ::: "memory"); }
template <int n> __device__ __forceinline__ void wg_wait() { asm volatile("wgmma.wait_group.sync.aligned %0;" ::"n"(n) : "memory"); }
__device__ __forceinline__ uint32_t ld_acquire(const uint32_t* p) { uint32_t v; asm volatile("ld.acquire.gpu.global.u32 %0, [%1];" : "=r"(v) : "l"(p) : "memory"); return v; }
__device__ __forceinline__ void flag_wait(const uint32_t* p, uint32_t target) {
  int it = 0;
#pragma unroll 1
  while ((int)(ld_acquire(p) - target) < 0 && ++it < (1 << 20)) __nanosleep(300);
}
__device__ __forceinline__ void hint_signal(uint32_t* p) {
  if ((threadIdx.x & 31) == 0) asm volatile("red.relaxed.gpu.global.add.u32 [%0], 1;" ::"l"(p) : "memory");
}
__device__ __forceinline__ void hint_wait(const uint32_t* p, uint32_t target, uint32_t ns = 400) {
  int it = 0; uint32_t v;
#pragma unroll 1
  do { asm volatile("ld.relaxed.gpu.global.u32 %0, [%1];" : "=r"(v) : "l"(p) : "memory"); if ((int)(v - target) >= 0) break; __nanosleep(ns); } while (++it < (1 << 20));
}
__device__ __forceinline__ uint32_t tag(uint32_t x, uint32_t par) { uint32_t r; asm("lop3.b32 %0, %1, 0xfffffffe, %2, 0xea;" : "=r"(r) : "r"(x), "r"(par)); return r; }
__device__ __forceinline__ void st_ll(uint4* p, uint32_t x, uint32_t y, uint32_t z, uint32_t w, uint32_t par) {
  asm volatile("{.reg .b64 a, b; mov.b64 a, {%1,%2}; mov.b64 b, {%3,%4}; st.relaxed.gpu.global.v2.b64 [%0], {a, b};}"
               ::"l"(p), "r"(tag(x, par)), "r"(y), "r"(tag(z, par)), "r"(w) : "memory");
}
__device__ __forceinline__ uint4 ld_ll(const uint4* p) {
  uint4 v;
  asm volatile("{.reg .b64 a, b; ld.relaxed.gpu.global.v2.b64 {a, b}, [%4]; mov.b64 {%0,%1}, a; mov.b64 {%2,%3}, b;}"
               : "=r"(v.x), "=r"(v.y), "=r"(v.z), "=r"(v.w) : "l"(p) : "memory");
  return v;
}
__device__ __forceinline__ uint2 ld_ll64(const uint32_t* p) {
  uint2 v;
  asm volatile("{.reg .b64 a; ld.relaxed.gpu.global.b64 a, [%2]; mov.b64 {%0,%1}, a;}" : "=r"(v.x), "=r"(v.y) : "l"(p) : "memory");
  return v;
}
__device__ __forceinline__ void ll_chk(uint32_t& bad, uint32_t a, uint32_t b, uint32_t par) {
  uint32_t u; asm("lop3.b32 %0, %1, %2, %3, 0x7e;" : "=r"(u) : "r"(a), "r"(b), "r"(par));
  asm("or.b32 %0, %0, %1;" : "+r"(bad) : "r"(u));
}
__device__ __forceinline__ uint32_t hadd2(uint32_t a, uint32_t b) { uint32_t d; asm("add.rn.bf16x2 %0, %1, %2;" : "=r"(d) : "r"(a), "r"(b)); return d; }
__device__ __forceinline__ uint32_t hfma2(uint32_t a, uint32_t b, uint32_t c) { uint32_t d; asm("fma.rn.bf16x2 %0, %1, %2, %3;" : "=r"(d) : "r"(a), "r"(b), "r"(c)); return d; }
__device__ __forceinline__ uint32_t pack_bf16(float lo, float hi) { uint32_t r; asm("cvt.rn.bf16x2.f32 %0, %1, %2;" : "=r"(r) : "f"(hi), "f"(lo)); return r; }
__device__ __forceinline__ float bf_lo(uint32_t v) { return __uint_as_float(v << 16); }
__device__ __forceinline__ float bf_hi(uint32_t v) { return __uint_as_float(v & 0xffff0000u); }
__device__ __forceinline__ uint32_t movmat(uint32_t a) { uint32_t d; asm volatile("movmatrix.sync.aligned.m8n8.trans.b16 %0, %1;" : "=r"(d) : "r"(a)); return d; }
__device__ __forceinline__ void mma16816(float* c, uint32_t a0, uint32_t a1, uint32_t a2, uint32_t a3, uint32_t b0, uint32_t b1) {
  asm volatile("mma.sync.aligned.m16n8k16.row.col.f32.bf16.bf16.f32 {%0,%1,%2,%3}, {%4,%5,%6,%7}, {%8,%9}, {%0,%1,%2,%3};"
               : "+f"(c[0]), "+f"(c[1]), "+f"(c[2]), "+f"(c[3]) : "r"(a0), "r"(a1), "r"(a2), "r"(a3), "r"(b0), "r"(b1));
}
__device__ __forceinline__ uint4 ldcg128(const void* p) { uint4 v; asm volatile("ld.global.cg.v4.u32 {%0,%1,%2,%3}, [%4];" : "=r"(v.x), "=r"(v.y), "=r"(v.z), "=r"(v.w) : "l"(p) : "memory"); return v; }

template <int N> __device__ __forceinline__ void wgmma_ss(float* d, uint64_t da, uint64_t db, int sc);
template <int N> __device__ __forceinline__ void wgmma_rs(float* d, const uint32_t* a, uint64_t db, int sc);
template <> __device__ __forceinline__ void wgmma_ss<96>(float* d, uint64_t da, uint64_t db, int sc) {
  asm volatile("{.reg .pred p; setp.ne.b32 p, %50, 0; wgmma.mma_async.sync.aligned.m64n96k16.f32.bf16.bf16 {%0, %1, %2, %3, %4, %5, %6, %7, %8, %9, %10, %11, %12, %13, %14, %15, %16, %17, %18, %19, %20, %21, %22, %23, %24, %25, %26, %27, %28, %29, %30, %31, %32, %33, %34, %35, %36, %37, %38, %39, %40, %41, %42, %43, %44, %45, %46, %47}, %48, %49, p, 1, 1, 0, 1;}"
   : "+f"(d[0]), "+f"(d[1]), "+f"(d[2]), "+f"(d[3]), "+f"(d[4]), "+f"(d[5]), "+f"(d[6]), "+f"(d[7]), "+f"(d[8]), "+f"(d[9]), "+f"(d[10]), "+f"(d[11]), "+f"(d[12]), "+f"(d[13]), "+f"(d[14]), "+f"(d[15]), "+f"(d[16]), "+f"(d[17]), "+f"(d[18]), "+f"(d[19]), "+f"(d[20]), "+f"(d[21]), "+f"(d[22]), "+f"(d[23]), "+f"(d[24]), "+f"(d[25]), "+f"(d[26]), "+f"(d[27]), "+f"(d[28]), "+f"(d[29]), "+f"(d[30]), "+f"(d[31]), "+f"(d[32]), "+f"(d[33]), "+f"(d[34]), "+f"(d[35]), "+f"(d[36]), "+f"(d[37]), "+f"(d[38]), "+f"(d[39]), "+f"(d[40]), "+f"(d[41]), "+f"(d[42]), "+f"(d[43]), "+f"(d[44]), "+f"(d[45]), "+f"(d[46]), "+f"(d[47]) : "l"(da), "l"(db), "r"(sc));
}
template <> __device__ __forceinline__ void wgmma_ss<192>(float* d, uint64_t da, uint64_t db, int sc) {
  asm volatile("{.reg .pred p; setp.ne.b32 p, %98, 0; wgmma.mma_async.sync.aligned.m64n192k16.f32.bf16.bf16 {%0, %1, %2, %3, %4, %5, %6, %7, %8, %9, %10, %11, %12, %13, %14, %15, %16, %17, %18, %19, %20, %21, %22, %23, %24, %25, %26, %27, %28, %29, %30, %31, %32, %33, %34, %35, %36, %37, %38, %39, %40, %41, %42, %43, %44, %45, %46, %47, %48, %49, %50, %51, %52, %53, %54, %55, %56, %57, %58, %59, %60, %61, %62, %63, %64, %65, %66, %67, %68, %69, %70, %71, %72, %73, %74, %75, %76, %77, %78, %79, %80, %81, %82, %83, %84, %85, %86, %87, %88, %89, %90, %91, %92, %93, %94, %95}, %96, %97, p, 1, 1, 0, 1;}"
   : "+f"(d[0]), "+f"(d[1]), "+f"(d[2]), "+f"(d[3]), "+f"(d[4]), "+f"(d[5]), "+f"(d[6]), "+f"(d[7]), "+f"(d[8]), "+f"(d[9]), "+f"(d[10]), "+f"(d[11]), "+f"(d[12]), "+f"(d[13]), "+f"(d[14]), "+f"(d[15]), "+f"(d[16]), "+f"(d[17]), "+f"(d[18]), "+f"(d[19]), "+f"(d[20]), "+f"(d[21]), "+f"(d[22]), "+f"(d[23]), "+f"(d[24]), "+f"(d[25]), "+f"(d[26]), "+f"(d[27]), "+f"(d[28]), "+f"(d[29]), "+f"(d[30]), "+f"(d[31]), "+f"(d[32]), "+f"(d[33]), "+f"(d[34]), "+f"(d[35]), "+f"(d[36]), "+f"(d[37]), "+f"(d[38]), "+f"(d[39]), "+f"(d[40]), "+f"(d[41]), "+f"(d[42]), "+f"(d[43]), "+f"(d[44]), "+f"(d[45]), "+f"(d[46]), "+f"(d[47]), "+f"(d[48]), "+f"(d[49]), "+f"(d[50]), "+f"(d[51]), "+f"(d[52]), "+f"(d[53]), "+f"(d[54]), "+f"(d[55]), "+f"(d[56]), "+f"(d[57]), "+f"(d[58]), "+f"(d[59]), "+f"(d[60]), "+f"(d[61]), "+f"(d[62]), "+f"(d[63]), "+f"(d[64]), "+f"(d[65]), "+f"(d[66]), "+f"(d[67]), "+f"(d[68]), "+f"(d[69]), "+f"(d[70]), "+f"(d[71]), "+f"(d[72]), "+f"(d[73]), "+f"(d[74]), "+f"(d[75]), "+f"(d[76]), "+f"(d[77]), "+f"(d[78]), "+f"(d[79]), "+f"(d[80]), "+f"(d[81]), "+f"(d[82]), "+f"(d[83]), "+f"(d[84]), "+f"(d[85]), "+f"(d[86]), "+f"(d[87]), "+f"(d[88]), "+f"(d[89]), "+f"(d[90]), "+f"(d[91]), "+f"(d[92]), "+f"(d[93]), "+f"(d[94]), "+f"(d[95]) : "l"(da), "l"(db), "r"(sc));
}

__device__ __forceinline__ uint64_t desc64(uint32_t lo, uint32_t hi) { uint64_t d; asm("mov.b64 %0, {%1, %2};" : "=l"(d) : "r"(lo), "r"(hi)); return d; }
constexpr uint32_t DESC_HI = (1024u >> 4) | (1u << 30);
constexpr uint32_t DESC_HI64 = (512u >> 4) | (2u << 30);
template <int n> __device__ __forceinline__ void fence_regs(float* a) {
#pragma unroll
  for (int i = 0; i < n; i++) asm volatile("" : "+f"(a[i])::"memory");
}

struct Ctx {
  uint32_t full;
  uint32_t emb;
  bool sig;
  uint32_t stage, phase, prev;
  uint32_t dB, dA;
  __device__ __forceinline__ void release_prev() { if (sig && prev != ~0u) mbar_arrive_cl(emb + prev); }
  __device__ __forceinline__ void wait_full() {
    mbar_wait(full + 8 * stage, phase);
    wg_fence();
  }
};

__device__ __forceinline__ void issue192(float* acc, Ctx& c, int s, bool first = false) {
  c.wait_full();
  const uint32_t db = c.dB + c.stage * (STAGE_BYTES >> 4);
  const uint32_t da = c.dA + (s >> 1) * 1024 + (s & 1) * 4;
  wgmma_ss<192>(acc, desc64(da, DESC_HI), desc64(db, DESC_HI), first ? 0 : 1);
  wgmma_ss<192>(acc, desc64(da + 2, DESC_HI), desc64(db + 128, DESC_HI), 1);
  wg_commit();
}
__device__ __forceinline__ void issue96(float* acc, Ctx& c, int s, bool first) {
  c.wait_full();
  const uint32_t db = c.dB + c.stage * (STAGE_BYTES >> 4);
  const uint32_t da = c.dA + s * 1024;
#pragma unroll
  for (int kk = 0; kk < 4; kk++) wgmma_ss<96>(acc, desc64(da + 2 * kk, DESC_HI), desc64(db + 64 * kk, DESC_HI64), (first && kk == 0) ? 0 : 1);
  wg_commit();
}
__device__ __forceinline__ void retire(Ctx& c) {
  wg_wait<1>();
  c.release_prev();
  c.prev = 8 * c.stage;
  if (++c.stage == NSTAGE) { c.stage = 0; c.phase ^= 1; }
}
constexpr float GK = 0.32920349f;
__device__ __forceinline__ uint32_t gelu_pair(uint32_t y) {
  uint32_t u, th;
  asm("mul.rn.bf16x2 %0, %1, %2;" : "=r"(u) : "r"(hfma2(y, y, 0x401b401bu)), "r"(y));
  asm("tanh.approx.bf16x2 %0, %1;" : "=r"(th) : "r"(u));
  return hfma2(y, th, y);
}
__device__ __forceinline__ uint4 gelu_group(const uint32_t* a) { return make_uint4(gelu_pair(a[0]), gelu_pair(a[1]), gelu_pair(a[2]), gelu_pair(a[3])); }
__device__ __forceinline__ uint32_t fma_pack_v(const float* a, float r, float2 b) {
  uint32_t e; asm volatile("{.reg .f32 x, y; fma.rn.f32 x, %1, %3, %4; fma.rn.f32 y, %2, %3, %5; cvt.rn.bf16x2.f32 %0, y, x;}" : "=r"(e) : "f"(a[0]), "f"(a[1]), "f"(r), "f"(b.x), "f"(b.y)); return e;
}
__device__ __forceinline__ uint32_t mul_pack_v(const float* a, float r) {
  uint32_t e; asm volatile("{.reg .f32 x, y; mul.rn.f32 x, %1, %3; mul.rn.f32 y, %2, %3; cvt.rn.bf16x2.f32 %0, y, x;}" : "=r"(e) : "f"(a[0]), "f"(a[1]), "f"(r)); return e;
}
__device__ __forceinline__ uint32_t pack_v(float lo, float hi) { uint32_t r; asm volatile("cvt.rn.bf16x2.f32 %0, %1, %2;" : "=r"(r) : "f"(hi), "f"(lo)); return r; }
__device__ __forceinline__ void lds_bias(float2* b, uint32_t addr) {
#pragma unroll
  for (int j = 0; j < 4; j++) asm volatile("ld.shared.v2.f32 {%0,%1}, [%2];" : "=f"(b[j].x), "=f"(b[j].y) : "r"(addr + 32 * j));
}
__device__ __forceinline__ int opaque(int v) { asm volatile("" : "+r"(v)); return v; }
__device__ __forceinline__ void stsm4(uint32_t addr, uint4 r) {
  asm volatile("stmatrix.sync.aligned.m8n8.x4.shared.b16 [%0], {%1,%2,%3,%4};" ::"r"(addr), "r"(r.x), "r"(r.y), "r"(r.z), "r"(r.w) : "memory");
}
__device__ __forceinline__ float ex2f(float x) { float r; asm("ex2.approx.ftz.f32 %0, %1;" : "=f"(r) : "f"(x)); return r; }
__device__ __forceinline__ float phi(float t) { float e = ex2f(t * 1.4426950408889634f); if (t > 0.f) e = t + 1.f; return e + 1e-6f; }
__device__ __forceinline__ uint32_t phi2(uint32_t w) { return pack_bf16(phi(bf_lo(w)), phi(bf_hi(w))); }
template <int q0, int q1>
__device__ __forceinline__ void part_groups(const float* a, uint4* p, uint32_t par) {
#pragma unroll
  for (int q = q0; q < q1; q++)
    st_ll(p + q * 32, pack_bf16(a[8 * q], a[8 * q + 1]), pack_bf16(a[8 * q + 2], a[8 * q + 3]), pack_bf16(a[8 * q + 4], a[8 * q + 5]), pack_bf16(a[8 * q + 6], a[8 * q + 7]), par);
}
__device__ __forceinline__ float silu(float y) { return __fdividef(y, 1.f + ex2f(y * -1.4426950408889634f)); }
__device__ __forceinline__ uint4 gate_vec(const uint4* p, uint32_t b0, uint32_t b1) {
  uint32_t o[4];
#pragma unroll
  for (int q = 0; q < 4; q++) {
    uint32_t w[8];
#pragma unroll
    for (int i = 0; i < 8; i++) w[i] = reinterpret_cast<const uint32_t*>(&p[i])[q];
    const uint32_t u0 = hadd2(hadd2(w[0], w[1]), hadd2(w[2], w[3])), u1 = hadd2(hadd2(w[4], w[5]), hadd2(w[6], w[7]));
    const uint32_t bb = q < 2 ? b0 : b1;
    o[q] = pack_bf16(silu(fmaf(bf_lo(u0) + bf_lo(u1), 0.5f / GK, bf_lo(bb))), silu(fmaf(bf_hi(u0) + bf_hi(u1), 0.5f / GK, bf_hi(bb))));
  }
  return make_uint4(o[0], o[1], o[2], o[3]);
}
__device__ __forceinline__ int coloff(int c) { return (c >> 4) * 128 + ((c & 7) >> 1) * 4 + ((c >> 3) & 1) * 2; }

__device__ __forceinline__ void d1_load(uint32_t* W, int rb0, int head, int ln) {
  const uint32_t* qf = reinterpret_cast<const uint32_t*>(g_qkvf) + rb0 * 108 * 128 + (ln >> 2) * 16;
#pragma unroll
  for (int b = 0; b < 3; b++) {
    const uint32_t* p = qf + coloff(576 + head * 18 + 8 * b + 2 * (ln & 3));
#pragma unroll
    for (int j = 0; j < 4; j++) {
      const uint2 kk = ld_ll64(p + j * 108 * 128), vv = ld_ll64(p + j * 108 * 128 + 36 * 128);
      W[6 * j + 2 * b] = kk.x; W[6 * j + 2 * b + 1] = kk.y; W[24 + 6 * j + 2 * b] = vv.x; W[24 + 6 * j + 2 * b + 1] = vv.y;
    }
  }
}
__device__ __forceinline__ bool d1_bad(const uint32_t* W, int t, uint32_t par) {
  uint32_t bad = 0, bad2 = 0;
#pragma unroll
  for (int q = 0; q < 12; q++) ll_chk((q % 3) != 2 ? bad : bad2, W[2 * q], W[24 + 2 * q], par);
  return __any_sync(0xffffffffu, (bad | (t == 0 ? bad2 : 0u)) & 1);
}
__device__ __forceinline__ void d1_prep(uint32_t* W, int j, int t) {
#pragma unroll
  for (int q = 0; q < 6; q++) W[6 * j + q] = phi2(W[6 * j + q]);
  if (t != 0) { W[6 * j + 4] = W[6 * j + 5] = 0u; W[24 + 6 * j + 4] = W[24 + 6 * j + 5] = (t == 1 ? 0x00003f80u : 0u); }
#pragma unroll
  for (int q = 0; q < 6; q++) { W[6 * j + q] = movmat(W[6 * j + q]); W[24 + 6 * j + q] = movmat(W[24 + 6 * j + q]); }
}
__device__ __forceinline__ void d1_mma_store(const uint32_t* W, int head, int blk, int ln, uint32_t par) {
  float c0[3][4], c1[3][4];
#pragma unroll
  for (int j = 0; j < 3; j++) { c0[j][0] = c0[j][1] = c0[j][2] = c0[j][3] = 0.f; c1[j][0] = c1[j][1] = c1[j][2] = c1[j][3] = 0.f; }
#pragma unroll
  for (int ks = 0; ks < 4; ks++)
#pragma unroll
    for (int j = 0; j < 3; j++) {
      mma16816(c0[j], W[24 + 6 * ks], W[24 + 6 * ks + 2], W[24 + 6 * ks + 1], W[24 + 6 * ks + 3], W[6 * ks + 2 * j], W[6 * ks + 2 * j + 1]);
      mma16816(c1[j], W[24 + 6 * ks + 4], 0u, W[24 + 6 * ks + 5], 0u, W[6 * ks + 2 * j], W[6 * ks + 2 * j + 1]);
    }
  uint4* dst = &g_kvp[(head * 160 + blk) * 32 + ln];
#pragma unroll
  for (int j = 0; j < 3; j++) st_ll(dst + j * 1024, __float_as_uint(c0[j][0]), __float_as_uint(c0[j][1]), __float_as_uint(c0[j][2]), __float_as_uint(c0[j][3]), par);
  st_ll(dst + 3072, __float_as_uint(c1[0][0]), __float_as_uint(c1[0][1]), __float_as_uint(c1[1][0]), __float_as_uint(c1[1][1]), par);
  st_ll(dst + 4096, __float_as_uint(c1[2][0]), __float_as_uint(c1[2][1]), 0u, 0u, par);
  hint_signal(&g_f_kvp[head]);
}

struct Params {
  CUtensorMap tm_wqkv, tm_w1, tm_w2, tm_m, tm_wqkv64, tm_m64, tm_a;
  const __nv_bfloat16 *x, *b1, *b2, *wqkv, *w1, *w2, *wo;
  __nv_bfloat16* out;
};

__global__ void __cluster_dims__(2, 1, 1) __launch_bounds__(NTHREADS, 1) fused_kernel(const __grid_constant__ Params P) {
  extern __shared__ __align__(1024) uint8_t smem[];
  const uint32_t sbase = smem_u32(smem);
  const int tid = threadIdx.x, lane = tid & 31;
  const int warp = __shfl_sync(0xffffffffu, tid >> 5, 0);
  const int g = lane >> 2, t = lane & 3;
  const uint32_t ep = __shfl_sync(0xffffffffu, g_epoch[blockIdx.x], 0) + 1;
  const uint32_t par = ep & 1;
  STAMPW(0, 0);

  if (blockIdx.x >= 128) {
    const int a = blockIdx.x - 128;
    if (warp >= 8 && lane == 0) {
      const int id = a * 4 + (warp - 8);
      constexpr uint32_t CH = 9216 * 2;
      __nanosleep(1500);
#pragma unroll 1
      for (int i = id; i < 576; i += 16) {
        const char* p = i < 288 ? (const char*)P.w1 + (size_t)i * CH : (const char*)P.w2 + (size_t)(i - 288) * CH;
        asm volatile("cp.async.bulk.prefetch.L2.global [%0], %1;" ::"l"(p), "r"(CH) : "memory");
      }
    }
    __syncwarp();
#pragma unroll 1
    for (int u0 = a * 12 + warp; u0 < 160; u0 += 48) {
      const int head = u0 / 5, u = u0;
      if (lane == 0) hint_wait(&g_f_kvp[head], 32 * ep, 50);
      __syncwarp();
      STAMPW(0, 1);
      uint4 v[32];
      int tries = 0;
      uint32_t bad;
#pragma unroll 1
      do {
        bad = 0;
#pragma unroll
        for (int j = 0; j < 32; j++) v[j] = ld_ll(&g_kvp[(u * 32 + j) * 32 + lane]);
#pragma unroll
        for (int j = 0; j < 32; j++) ll_chk(bad, v[j].x, v[j].z, par);
      } while (__any_sync(0xffffffffu, bad & 1) && ++tries < (1 << 20));
      float s0 = 0.f, s1 = 0.f, s2 = 0.f, s3 = 0.f;
#pragma unroll
      for (int j = 0; j < 32; j++) { s0 += __uint_as_float(v[j].x); s1 += __uint_as_float(v[j].y); s2 += __uint_as_float(v[j].z); s3 += __uint_as_float(v[j].w); }
      st_ll(&g_kvt[u * 32 + lane], __float_as_uint(s0), __float_as_uint(s1), __float_as_uint(s2), __float_as_uint(s3), par);
      hint_signal(&g_f_kvt[head]);
      STAMPW(0, 2);
    }
    __syncthreads();
    if (tid == 0) g_epoch[blockIdx.x] = ep;
    return;
  }

  const int cl = blockIdx.x >> 1, rank = blockIdx.x & 1;
  const int f = cl & 7, m = (cl >> 3) * 2 + rank;
  const int srole = f >= 6 ? 1 : 0;
  const uint32_t bar_full = sbase + SM_BAR, bar_empty = bar_full + 8 * NSTAGE, bar_xfree = bar_empty + 8 * NSTAGE, bar_ofull = bar_xfree + 72,
                 bar_d = bar_ofull + 72;

  if (tid == 0) {
#pragma unroll 1
    for (int i = 0; i < NSTAGE; i++) { mbar_init(bar_full + 8 * i, 1); mbar_init(bar_empty + 8 * i, 4); }
#pragma unroll 1
    for (int i = 0; i < 9; i++) { mbar_init(bar_xfree + 8 * i, 2); mbar_init(bar_ofull + 8 * i, 1); }
    mbar_init(bar_d, 1);
    asm volatile("fence.mbarrier_init.release.cluster;" ::: "memory");
  }
  __syncwarp();
  cluster_arrive_relaxed();

  if (warp >= 8) {
    const int srow = m * 128 + f * 16 + (warp - 8) * 4 + (lane >> 3);
    uint4 xs[9];
#pragma unroll
    for (int kb = 0; kb < 9; kb++) xs[kb] = __ldg(reinterpret_cast<const uint4*>(P.x + srow * D_) + (lane & 7) + kb * 8);
    auto stats = [&]() {
      const uint32_t* w = reinterpret_cast<const uint32_t*>(xs);
      float s0 = 0.f, s1 = 0.f;
#pragma unroll
      for (int i = 0; i < 36; i++) { s0 += bf_lo(w[i]); s1 += bf_hi(w[i]); }
      float sum = s0 + s1;
      sum += __shfl_xor_sync(0xffffffffu, sum, 1); sum += __shfl_xor_sync(0xffffffffu, sum, 2); sum += __shfl_xor_sync(0xffffffffu, sum, 4);
      const float mean = sum * (1.f / 576.f);
      s0 = 0.f; s1 = 0.f;
#pragma unroll
      for (int i = 0; i < 36; i++) { const float a = bf_lo(w[i]) - mean, b = bf_hi(w[i]) - mean; s0 = fmaf(a, a, s0); s1 = fmaf(b, b, s1); }
      float sq = s0 + s1;
      sq += __shfl_xor_sync(0xffffffffu, sq, 1); sq += __shfl_xor_sync(0xffffffffu, sq, 2); sq += __shfl_xor_sync(0xffffffffu, sq, 4);
      const float rstd = rsqrtf(sq * (1.f / 576.f) + 1e-5f);
      if ((lane & 7) == 0)
        asm volatile("{.reg .b64 a; mov.b64 a, {%1,%2}; st.relaxed.gpu.global.b64 [%0], a;}" ::"l"(&g_stat[srow]), "r"((__float_as_uint(rstd) & ~1u) | par), "r"(pack_bf16(-mean, -mean)) : "memory");
    };
    stats();
    asm volatile("setmaxnreg.dec.sync.aligned.u32 56;");
    cluster_wait();
    if (warp == 8) {
      if (lane == 0) {
        uint32_t stage = 0, phase = 1;
        const uint32_t sb = sbase + SM_B;
#pragma unroll 1
        for (int tl = 2 * srole; tl < 8 + 2 * srole; tl++) {
          const CUtensorMap* map = tl == 0 ? &P.tm_wqkv : (tl == 1 ? &P.tm_wqkv64 : (tl < 5 ? &P.tm_w1 : (tl < 8 ? &P.tm_w2 : (tl == 8 ? &P.tm_m : &P.tm_m64))));
          const int col = tl < 2 ? 288 * f + 192 * tl : (tl < 5 ? 576 * f + 192 * (tl - 2) : (tl < 8 ? 192 * (tl - 5) : (tl == 8 ? 192 * (f - 5) : 96 * (f - 6))));
          const bool perm = tl >= 5 && tl < 8;
          const bool z = (tl & 7) == 1;
          if (tl == 8) { flag_wait(g_f_m, 128 * ep); asm volatile("fence.proxy.async.global;" ::: "memory"); }
          const int cs = z ? 32 : 64, rs = z ? 64 : 32, nst = z ? 9 : 18;
#pragma unroll 1
          for (int st = 0; st < nst; st++) {
            int row = st * rs;
            if (perm) row += 576 * f + ((st < 6) ? 192 : (st < 12 ? -192 : 0));
            mbar_wait(bar_empty + 8 * stage, phase);
            mbar_expect(bar_full + 8 * stage, 12288);
            const uint32_t dst = sb + stage * STAGE_BYTES;
            if (((st ^ rank) & 1) == 0) {
              tma2d_mc(dst, map, col, row, bar_full + 8 * stage);
              tma2d_mc(dst + 8192, map, col + 2 * cs, row, bar_full + 8 * stage);
            } else {
              tma2d_mc(dst + 4096, map, col + cs, row, bar_full + 8 * stage);
            }
            if (++stage == NSTAGE) { stage = 0; phase ^= 1; }
          }
        }
      }
      __syncwarp();
    } else {
      const int aw = warp - 9, ta = tid - 288;
      const int hi = f >> 2;
      float* skv = reinterpret_cast<float*>(smem + SM_KV);
      const int hM = 4 * f + (m >> 2), nM = 144 * (m & 3) + 2 * (ta < 72 ? ta : 0);
      uint32_t wo[18];
#pragma unroll
      for (int e = 0; e < 18; e++) wo[e] = __ldg(reinterpret_cast<const uint32_t*>(P.wo + (hM * 18 + e) * D_ + nM));
      if (aw == 0) {
        if (lane < 2) hint_wait(&g_f_qkv[m * 8 + 2 + 2 * lane + hi], 16 * ep);
        __syncwarp();
        if (lane == 0) mbar_arrive(bar_d);
        STAMP(20);
      }
#pragma unroll 1
      for (int hh = aw; hh < 4; hh += 3) {
        if (lane == 0) hint_wait(&g_f_kvt[4 * f + hh], 5 * ep);
        __syncwarp();
        uint4 kv[5];
        int tries = 0;
        uint32_t bad;
#pragma unroll 1
        do {
          bad = 0;
#pragma unroll
          for (int j = 0; j < 5; j++) kv[j] = ld_ll(&g_kvt[((4 * f + hh) * 5 + j) * 32 + lane]);
#pragma unroll
          for (int j = 0; j < 5; j++) ll_chk(bad, kv[j].x, kv[j].z, par);
        } while (__any_sync(0xffffffffu, bad & 1) && ++tries < (1 << 20));
        uint2* row = reinterpret_cast<uint2*>(skv + (hh * 19 + g) * 20 + 2 * t);
#pragma unroll
        for (int j = 0; j < 3; j++)
          if (j < 2 || t < 2) { row[4 * j] = make_uint2(kv[j].x, kv[j].y); row[80 + 4 * j] = make_uint2(kv[j].z, kv[j].w); }
        if (g < 3) {
          row[160] = make_uint2(kv[3].x, kv[3].y); row[164] = make_uint2(kv[3].z, kv[3].w);
          if (t < 2) row[168] = make_uint2(kv[4].x, kv[4].y);
        }
      }
      asm volatile("bar.sync 5, 96;" ::: "memory");
      STAMPW(9, 22);
      if (ta < 72) {
#pragma unroll 1
        for (int d0 = 0; d0 < 20; d0 += 4) {
          float ac[8];
#pragma unroll
          for (int q = 0; q < 8; q++) ac[q] = 0.f;
#pragma unroll
          for (int e = 0; e < 18; e++) {
            const float4 k4 = *reinterpret_cast<const float4*>(skv + ((m >> 2) * 19 + e) * 20 + d0);
            const float w0 = bf_lo(wo[e]), w1 = bf_hi(wo[e]);
            ac[0] = fmaf(k4.x, w0, ac[0]); ac[1] = fmaf(k4.x, w1, ac[1]); ac[2] = fmaf(k4.y, w0, ac[2]); ac[3] = fmaf(k4.y, w1, ac[3]);
            ac[4] = fmaf(k4.z, w0, ac[4]); ac[5] = fmaf(k4.z, w1, ac[5]); ac[6] = fmaf(k4.w, w0, ac[6]); ac[7] = fmaf(k4.w, w1, ac[7]);
          }
#pragma unroll
          for (int q = 0; q < 4; q++)
            if (d0 + q < 18) *reinterpret_cast<uint32_t*>(g_m + (hM * 18 + d0 + q) * D_ + nM) = pack_bf16(ac[2 * q], ac[2 * q + 1]);
        }
      }
      __syncwarp();
      if (lane == 0) hint_wait(&g_f_qkv[m * 8 + hi], 16 * ep);
      __syncwarp();
      {
        const uint32_t* qf = reinterpret_cast<const uint32_t*>(g_qkvf) + m * 8 * 108 * 128 + g * 16;
        uint2 nx[3];
        auto ldq = [&](int it) {
#pragma unroll
          for (int b = 0; b < 3; b++) nx[b] = ld_ll64(qf + (it >> 2) * 108 * 128 + coloff(72 * f + (it & 3) * 18 + 8 * b + 2 * t));
        };
        ldq(aw);
#pragma unroll 1
        for (int it = aw; it < 32; it += 3) {
          int tries = 0;
#pragma unroll 1
          while (true) {
            uint32_t bad = 0;
            ll_chk(bad, nx[0].x, nx[1].x, par); ll_chk(bad, t == 0 ? nx[2].x : par, par, par);
            if (!__any_sync(0xffffffffu, bad & 1) || ++tries > (1 << 20)) break;
            ldq(it);
          }
          const uint2 q0 = nx[0], q1 = nx[1], q2 = nx[2];
          if (it + 3 < 32) ldq(it + 3);
          float p[12] = {phi(bf_lo(q0.x)), phi(bf_hi(q0.x)), phi(bf_lo(q1.x)), phi(bf_hi(q1.x)), phi(bf_lo(q2.x)), phi(bf_hi(q2.x)),
                         phi(bf_lo(q0.y)), phi(bf_hi(q0.y)), phi(bf_lo(q1.y)), phi(bf_hi(q1.y)), phi(bf_lo(q2.y)), phi(bf_hi(q2.y))};
          const float2* zp = reinterpret_cast<const float2*>(skv + ((it & 3) * 19 + 18) * 20 + 2 * t);
          const float2 z0 = zp[0], z1 = zp[4], z2 = *reinterpret_cast<const float2*>(skv + ((it & 3) * 19 + 18) * 20 + 16);
          float d0 = p[0] * z0.x + p[1] * z0.y + p[2] * z1.x + p[3] * z1.y, d1 = p[6] * z0.x + p[7] * z0.y + p[8] * z1.x + p[9] * z1.y;
          if (t == 0) { d0 += p[4] * z2.x + p[5] * z2.y; d1 += p[10] * z2.x + p[11] * z2.y; }
          d0 += __shfl_xor_sync(0xffffffffu, d0, 1); d1 += __shfl_xor_sync(0xffffffffu, d1, 1);
          d0 += __shfl_xor_sync(0xffffffffu, d0, 2); d1 += __shfl_xor_sync(0xffffffffu, d1, 2);
          const float r0 = __fdividef(1.f, d0 + 1e-6f), r1 = __fdividef(1.f, d1 + 1e-6f);
          __nv_bfloat16* po = g_a + (m * 128 + (it >> 2) * 16 + g) * D_ + 72 * f + (it & 3) * 18 + 2 * t;
#pragma unroll
          for (int b = 0; b < 3; b++)
            if (b < 2 || t == 0) {
              *reinterpret_cast<uint32_t*>(po + 8 * b) = pack_bf16(p[2 * b] * r0, p[2 * b + 1] * r0);
              *reinterpret_cast<uint32_t*>(po + 8 * D_ + 8 * b) = pack_bf16(p[6 + 2 * b] * r1, p[7 + 2 * b] * r1);
            }
        }
      }
      asm volatile("fence.proxy.async.global;" ::: "memory");
      asm volatile("bar.sync 5, 96;" ::: "memory");
      if (ta == 0) {
        asm volatile("fence.acq_rel.gpu;" ::: "memory");
        asm volatile("red.relaxed.gpu.global.add.u32 [%0], 1;" ::"l"(&g_f_a[m]) : "memory");
        asm volatile("red.relaxed.gpu.global.add.u32 [%0], 1;" ::"l"(g_f_m) : "memory");
      }
      __syncwarp();
      STAMPW(9, 23);
      if (srole && aw == 2) {
        if (lane == 0) {
          flag_wait(&g_f_a[m], 8 * ep);
          asm volatile("fence.proxy.async.global;" ::: "memory");
#pragma unroll 1
          for (int kb = 0; kb < 9; kb++) {
            mbar_wait(bar_xfree + 8 * kb, 0);
            mbar_expect(bar_ofull + 8 * kb, 16384);
            tma2d(sbase + SM_A + kb * 16384, &P.tm_a, kb * 64, m * 128, bar_ofull + 8 * kb);
          }
        }
        __syncwarp();
      }
      const int rbg = m * 8 + f;
#pragma unroll 1
      for (int ch = 0; ch < 2; ch++) {
        if (lane == 0) hint_wait(&g_f_rb[rbg * 8 + ch], 8 * ep);
        __syncwarp();
        STAMPW(9, 24 + 2 * ch);
#pragma unroll 1
        for (int v = ch * 12 + aw * 4; v < ch * 12 + aw * 4 + 4; v++) {
          const uint32_t b0 = __ldg(reinterpret_cast<const uint32_t*>(P.b2 + 16 * v + 2 * t)), b1 = __ldg(reinterpret_cast<const uint32_t*>(P.b2 + 16 * v + 8 + 2 * t));
          uint4 p[8];
          int tries = 0;
          uint32_t bad;
#pragma unroll 1
          do {
            bad = 0;
#pragma unroll
            for (int i = 0; i < 8; i++) p[i] = ld_ll(&g_part[((rbg * 8 + i) * 36 + v) * 32 + lane]);
#pragma unroll
            for (int i = 0; i < 8; i++) ll_chk(bad, p[i].x, p[i].z, par);
          } while (__any_sync(0xffffffffu, bad & 1) && ++tries < (1 << 20));
          const uint4 gt = gate_vec(p, b0, b1);
          st_ll(&g_g[(rbg * 24 + v) * 32 + lane], gt.x, gt.y, gt.z, gt.w, par);
        }
        hint_signal(&g_f_rb[rbg * 8 + 5 + ch]);
        STAMPW(9, 25 + 2 * ch);
      }
    }
    cluster_arrive_relaxed();
    cluster_wait();
  } else {
    const int wg = warp >> 2;
    {
      const int rs = lane >> 3, j = lane & 7;
      uint4 xv[4][9];
#pragma unroll
      for (int it = 0; it < 4; it++)
#pragma unroll
        for (int kb = 0; kb < 9; kb++) xv[it][kb] = __ldg(reinterpret_cast<const uint4*>(P.x + (m * 128 + warp * 16 + it * 4 + rs) * D_) + j + kb * 8);
      uint32_t bw0 = __ldg(reinterpret_cast<const uint32_t*>(P.b1 + 576 * f) + tid), bw1 = tid < 32 ? __ldg(reinterpret_cast<const uint32_t*>(P.b1 + 576 * f) + 256 + tid) : 0u;
      uint2 st[4];
      int tries = 0;
      uint32_t bad;
#pragma unroll 1
      do {
        bad = 0;
#pragma unroll
        for (int it = 0; it < 4; it++) st[it] = ld_ll64(reinterpret_cast<const uint32_t*>(&g_stat[m * 128 + warp * 16 + it * 4 + rs]));
        ll_chk(bad, st[0].x, st[1].x, par); ll_chk(bad, st[2].x, st[3].x, par);
      } while (__any_sync(0xffffffffu, bad & 1) && ++tries < (1 << 22));
      STAMPW(0, 19);
#pragma unroll
      for (int it = 0; it < 4; it++) {
        const uint32_t nm = st[it].y;
        uint8_t* dst = smem + SM_A + (warp * 16 + it * 4 + rs) * 128 + ((j ^ ((it * 4 + rs) & 7)) << 4);
#pragma unroll
        for (int kb = 0; kb < 9; kb++) {
          const uint4 w = xv[it][kb];
          *reinterpret_cast<uint4*>(dst + kb * 16384) = make_uint4(hadd2(w.x, nm), hadd2(w.y, nm), hadd2(w.z, nm), hadd2(w.w, nm));
        }
        if (j == 0) reinterpret_cast<uint32_t*>(smem + SM_RSTD)[warp * 16 + it * 4 + rs] = st[it].x;
      }
      reinterpret_cast<float2*>(smem + SM_BIAS)[tid] = make_float2(bf_lo(bw0) * GK, bf_hi(bw0) * GK);
      if (tid < 32) reinterpret_cast<float2*>(smem + SM_BIAS)[256 + tid] = make_float2(bf_lo(bw1) * GK, bf_hi(bw1) * GK);
      asm volatile("fence.proxy.async.shared::cta;" ::: "memory");
    }
    asm volatile("setmaxnreg.inc.sync.aligned.u32 224;");
    cluster_wait();
    asm volatile("bar.sync 1, 256;" ::: "memory");
    STAMPW(0, 1);
    Ctx c;
    c.full = bar_full;
    c.emb = __shfl_sync(0xffffffffu, mapa(bar_empty, (warp & 3) == 0 ? rank : (rank ^ 1)), 0);
    c.sig = lane == 0 && (warp & 3) < 2;
    c.stage = 0; c.phase = 0; c.prev = ~0u;
    c.dB = (((sbase + SM_B) & 0x3FFFF) >> 4) | ((4096u >> 4) << 16);
    c.dA = (((sbase + SM_A + wg * 8192) & 0x3FFFF) >> 4) | (1u << 16);
    const bool leader = (lane == 0) && ((warp & 3) == 0);

    const int rb = m * 8 + warp;
    const uint32_t bias_t = sbase + SM_BIAS + 8 * t;
    const uint32_t hst = sbase + SM_A + (warp * 16 + (lane & 7) + ((lane >> 3) & 1) * 8) * 128 + (((lane >> 4) ^ (lane & 7)) << 4);
    auto wg_sync = [&]() {
      asm volatile("fence.proxy.async.shared::cta;" ::: "memory");
      if (wg == 0) asm volatile("bar.sync 2, 128;" ::: "memory"); else asm volatile("bar.sync 3, 128;" ::: "memory");
    };
    float A[96], B[96];
#pragma unroll
    for (int i = 0; i < 96; i++) B[i] = 0.f;
#define GELU16(H0, H1, ACC, OFF, HF) uint32_t E[8]; \
    if (HF) { _Pragma("unroll") for (int q = 0; q < 8; q++) E[q] = fma_pack_v(&ACC[48 + (OFF) + 2 * q], (q & 1) ? r1 : r0, bs[q >> 1]); } \
    else { _Pragma("unroll") for (int q = 0; q < 8; q++) E[q] = fma_pack_v(&ACC[(OFF) + 2 * q], (q & 1) ? r1 : r0, bs[q >> 1]); } \
    const uint4 H0 = gelu_group(E), H1 = gelu_group(E + 4);
#define PART16(DST, ACC, OFF, HF) uint32_t E[8]; \
    if (HF) { _Pragma("unroll") for (int q = 0; q < 8; q++) E[q] = pack_v(ACC[48 + (OFF) + 2 * q], ACC[49 + (OFF) + 2 * q]); } \
    else { _Pragma("unroll") for (int q = 0; q < 8; q++) E[q] = pack_v(ACC[(OFF) + 2 * q], ACC[1 + (OFF) + 2 * q]); } \
    st_ll(DST, E[0], E[1], E[2], E[3], par); st_ll(DST + 32, E[4], E[5], E[6], E[7], par);
#define SPART16(DST, ACC, OFF) { uint32_t E[8]; _Pragma("unroll") for (int q = 0; q < 8; q++) E[q] = mul_pack_v(&ACC[(OFF) + 2 * q], (q & 1) ? r1 : r0); \
    st_ll(DST, E[0], E[1], E[2], E[3], par); st_ll(DST + 32, E[4], E[5], E[6], E[7], par); }
#define LDS_R(SC) float r0, r1; asm volatile("ld.shared.f32 %0, [%1];" : "=f"(r0) : "r"(rst)); asm volatile("ld.shared.f32 %0, [%1];" : "=f"(r1) : "r"(rst + 32)); r0 *= (SC); r1 *= (SC);
    const uint32_t rst = sbase + SM_RSTD + (warp * 16 + g) * 4;
#pragma unroll 1
    for (int i = srole; i < 4 + srole; i++) {
      {
        const uint32_t ow = i == 4 ? bar_ofull : 0u;
        if (ow) mbar_wait(ow, 0);
        issue192(A, c, 0, true);
        const int ln = opaque(lane);
        uint4* dst = i == 1 ? g_qkvf + (rb * 108 + 18 * f + 12) * 32 + ln : g_part + ((rb * 8 + f) * 36 + (i == 3 ? 0 : 24)) * 32 + ln;
        const int nhf = i == 0 ? 0 : (i == 1 ? 1 - srole : 2);
        LDS_R(i == 2 ? GK : 1.f)
        retire(c);
        if (ow && leader) mbar_arrive(bar_xfree + 64);
        fence_regs<96>(B);
        int s = 1;
        if (i == 2) {
#pragma unroll 1
          for (; s < 3; s++) { issue192(A, c, s); retire(c); }
        }
#pragma unroll 1
        for (int hf = 0; hf < nhf; hf++) {
#pragma unroll
          for (int u = 0; u < 3; u++, s++) {
            float2 bs[4];
            lds_bias(bs, bias_t + (192 + 96 * hf + 32 * u) * 4);
            if (ow && !(s & 1)) mbar_wait(ow + 4 * s, 0);
            issue192(A, c, s);
            if (i == 2) {
              GELU16(h0, h1, B, 16 * u, hf)
              const int q = 6 * hf + 2 * u;
              stsm4((hst ^ ((q & 3) << 5)) + (q >> 2) * 16384, h0);
              stsm4((hst ^ (((q + 1) & 3) << 5)) + (q >> 2) * 16384, h1);
            } else if (i == 1) { SPART16(dst + 2 * u * 32, B, 16 * u) }
            else { PART16(dst + 2 * u * 32, B, 16 * u, hf) }
            retire(c);
          }
          dst += 6 * 32;
        }
        if (nhf != 0 && i != 2) hint_signal(i == 1 ? &g_f_qkv[m * 8 + f] : &g_f_rb[rb * 8 + (i == 3 ? 0 : 2)]);
        const bool d1 = i == 1 + srole;
        uint32_t W[48];
#pragma unroll
        for (int q = 0; q < 48; q++) W[q] = 0;
#pragma unroll 1
        for (; s < 17; s++) {
          if (ow && !(s & 1)) mbar_wait(ow + 4 * s, 0);
          issue192(A, c, s);
          if (d1) {
            if (s == 9 || s == 11) {
              if (s == 9) mbar_wait(bar_d, 0);
              int tries = 0;
#pragma unroll 1
              while (s == 9 || (d1_bad(W, t, par) && ++tries < (1 << 20))) {
                d1_load(W, m * 8 + (warp & 1) * 4, 4 * f + (warp >> 1), opaque(lane));
                if (s == 9) break;
              }
            }
            if (s == 11) d1_prep(W, 0, t);
            if (s == 12) d1_prep(W, 1, t);
            if (s == 13) d1_prep(W, 2, t);
            if (s == 14) d1_prep(W, 3, t);
            if (s == 15) {
              wg_wait<0>();
              asm volatile("bar.sync 4, 256;" ::: "memory");
              d1_mma_store(W, 4 * f + (warp >> 1), m * 2 + (warp & 1), opaque(lane), par);
              asm volatile("bar.sync 4, 256;" ::: "memory");
              STAMPW(0, 21);
            }
          }
          if (i == 2) {
            if (s == 15) {
              const uint4* hsp = g_hsp + (blockIdx.x * 8 + warp) * 12 * 32 + opaque(lane);
#pragma unroll
              for (int q = 0; q < 12; q++) { const uint4 v = ldcg128(hsp + q * 32); W[4 * q] = v.x; W[4 * q + 1] = v.y; W[4 * q + 2] = v.z; W[4 * q + 3] = v.w; }
            }
            if (s == 10) wg_sync();
          }
          retire(c);
        }
        issue192(A, c, 17);
        if (i == 2) {
#pragma unroll
          for (int q = 0; q < 12; q++) stsm4((hst ^ ((q & 3) << 5)) + (3 + (q >> 2)) * 16384, make_uint4(W[4 * q], W[4 * q + 1], W[4 * q + 2], W[4 * q + 3]));
        }
        retire(c);
      }
      STAMPW(0, 2 + 2 * i);
      if ((i & 3) == 0) {
        issue96(B, c, 0, true);
        const int ln = opaque(lane);
        uint4* dst = i == 0 ? g_qkvf + (rb * 108 + 18 * f) * 32 + ln : g_s + (rb * 24 + 12 * (f - 6)) * 32 + ln;
        LDS_R(1.f)
        if (i != 0) { r0 = 1.f; r1 = 1.f; }
        retire(c);
        fence_regs<96>(A);
#pragma unroll 1
        for (int s = 1; s < 8; s++) {
          issue96(B, c, s, false);
#pragma unroll
          for (int u = 0; u < 6; u++)
            if (s == u + 1) SPART16(dst + 2 * u * 32, A, 16 * u)
          if (s == 6) hint_signal(i == 0 ? &g_f_qkv[m * 8 + f] : &g_f_rb[rb * 8 + f - 3]);
          retire(c);
        }
        issue96(B, c, 8, false);
        retire(c);
      } else {
        issue192(B, c, 0, true);
        const int ln = opaque(lane);
        uint4* dst = i == 1 ? g_hsp + (blockIdx.x * 8 + warp) * 12 * 32 + ln : g_part + ((rb * 8 + f) * 36 + 12) * 32 + ln;
        const bool xf = i == 3 && srole && leader;
        const uint32_t bsa = bias_t + (i == 1 ? 0 : 384) * 4;
        LDS_R(GK)
        retire(c);
        fence_regs<96>(A);
        int s = 1;
#pragma unroll 1
        for (int hf = 0; hf < 2; hf++) {
#pragma unroll
          for (int u = 0; u < 3; u++, s++) {
            float2 bs[4];
            lds_bias(bs, bsa + (96 * hf + 32 * u) * 4);
            issue192(B, c, s);
            if (i != 3) {
              GELU16(h0, h1, A, 16 * u, hf)
              if (i == 1) { dst[2 * u * 32] = h0; dst[(2 * u + 1) * 32] = h1; }
              else {
                const int q = 6 * hf + 2 * u;
                stsm4((hst ^ ((q & 3) << 5)) + (6 + (q >> 2)) * 16384, h0);
                stsm4((hst ^ (((q + 1) & 3) << 5)) + (6 + (q >> 2)) * 16384, h1);
                if (u == 2 && hf == 0) wg_sync();
              }
            } else { PART16(dst + 2 * u * 32, A, 16 * u, hf) }
            retire(c);
            if ((s & 1) == 0 && xf) mbar_arrive(bar_xfree + 4 * s - 8);
          }
          dst += 6 * 32;
        }
        if (i == 3) hint_signal(&g_f_rb[rb * 8 + 1]);
#pragma unroll 1
        for (; s < 17; s++) {
          issue192(B, c, s);
          if (s == 9 && i == 2) wg_sync();
          retire(c);
          if ((s & 1) == 0 && xf) mbar_arrive(bar_xfree + 4 * s - 8);
        }
        issue192(B, c, 17);
        retire(c);
      }
      STAMPW(0, 3 + 2 * i);
    }

    const int ln = opaque(lane);
    const __nv_bfloat16* xp = P.x + (rb * 16 + (ln >> 2)) * D_ + 2 * (ln & 3);
    __nv_bfloat16* op = P.out + (rb * 16 + (ln >> 2)) * D_ + 2 * (ln & 3);
    auto ldx = [&](uint32_t* xx, int col) {
      xx[0] = __ldg(reinterpret_cast<const uint32_t*>(xp + col)); xx[1] = __ldg(reinterpret_cast<const uint32_t*>(xp + 8 * D_ + col));
      xx[2] = __ldg(reinterpret_cast<const uint32_t*>(xp + col + 8)); xx[3] = __ldg(reinterpret_cast<const uint32_t*>(xp + 8 * D_ + col + 8));
    };
    auto stout = [&](int col, uint4 sv, uint4 gv, const uint32_t* xx) {
      *reinterpret_cast<uint32_t*>(op + col) = hfma2(sv.x, gv.x, xx[0]); *reinterpret_cast<uint32_t*>(op + 8 * D_ + col) = hfma2(sv.y, gv.y, xx[1]);
      *reinterpret_cast<uint32_t*>(op + col + 8) = hfma2(sv.z, gv.z, xx[2]); *reinterpret_cast<uint32_t*>(op + 8 * D_ + col + 8) = hfma2(sv.w, gv.w, xx[3]);
    };
    if (srole) {
      const int cb = 96 * (f - 6);
      uint32_t xx[24];
      uint4 gg[6];
#pragma unroll
      for (int q = 0; q < 6; q++) ldx(&xx[4 * q], cb + 16 * q);
      int tries = 0;
      uint32_t bad;
#pragma unroll 1
      do {
        bad = 0;
#pragma unroll
        for (int q = 0; q < 6; q++) gg[q] = ld_ll(&g_g[(rb * 24 + 6 * (f - 6) + q) * 32 + ln]);
#pragma unroll
        for (int q = 0; q < 6; q++) ll_chk(bad, gg[q].x, gg[q].z, par);
      } while (__any_sync(0xffffffffu, bad & 1) && ++tries < (1 << 20));
      STAMPW(0, 14);
      wg_wait<0>();
      c.release_prev();
      fence_regs<48>(B);
#pragma unroll
      for (int q = 0; q < 6; q++)
        stout(cb + 16 * q, make_uint4(pack_bf16(B[8 * q], B[8 * q + 1]), pack_bf16(B[8 * q + 2], B[8 * q + 3]), pack_bf16(B[8 * q + 4], B[8 * q + 5]), pack_bf16(B[8 * q + 6], B[8 * q + 7])), gg[q], &xx[4 * q]);
    } else {
      wg_wait<0>();
      c.release_prev();
      fence_regs<96>(B);
      part_groups<0, 12>(B, g_part + ((rb * 8 + f) * 36 + 24) * 32 + ln, par);
      hint_signal(&g_f_rb[rb * 8 + 2]);
      STAMPW(0, 12);
      uint32_t xx[16], bb[4];
#pragma unroll
      for (int j = 0; j < 4; j++) ldx(&xx[4 * j], 192 + 192 * (j >> 1) + 32 * f + 16 * (j & 1));
#pragma unroll
      for (int j = 0; j < 4; j++) bb[j] = __ldg(reinterpret_cast<const uint32_t*>(P.b2 + 384 + 32 * f + 8 * j + 2 * (ln & 3)));
      uint4 sv[4], gg[2];
      int tries = 0;
      uint32_t bad;
#pragma unroll 1
      do {
        bad = 0;
#pragma unroll
        for (int j = 0; j < 4; j++) sv[j] = ld_ll(&g_s[(rb * 24 + 12 * (j >> 1) + 2 * f + (j & 1)) * 32 + ln]);
#pragma unroll
        for (int j = 0; j < 2; j++) gg[j] = ld_ll(&g_g[(rb * 24 + 12 + 2 * f + j) * 32 + ln]);
#pragma unroll
        for (int j = 0; j < 4; j++) ll_chk(bad, sv[j].x, sv[j].z, par);
#pragma unroll
        for (int j = 0; j < 2; j++) ll_chk(bad, gg[j].x, gg[j].z, par);
      } while (__any_sync(0xffffffffu, bad & 1) && ++tries < (1 << 20));
#pragma unroll
      for (int j = 0; j < 2; j++) stout(192 + 32 * f + 16 * j, sv[j], gg[j], &xx[4 * j]);
      STAMPW(0, 13);
      if (ln == 0) hint_wait(&g_f_rb[rb * 8 + 2], 8u * ep, 20);
      __syncwarp();
      STAMPW(0, 14);
      uint4 p[2][8];
      tries = 0;
#pragma unroll 1
      do {
        bad = 0;
#pragma unroll
        for (int j = 0; j < 2; j++)
#pragma unroll
          for (int k = 0; k < 8; k++) p[j][k] = ld_ll(&g_part[((rb * 8 + k) * 36 + 24 + 2 * f + j) * 32 + ln]);
#pragma unroll
        for (int j = 0; j < 2; j++)
#pragma unroll
          for (int k = 0; k < 8; k++) ll_chk(bad, p[j][k].x, p[j][k].z, par);
      } while (__any_sync(0xffffffffu, bad & 1) && ++tries < (1 << 20));
#pragma unroll
      for (int j = 0; j < 2; j++) {
        stout(384 + 32 * f + 16 * j, sv[2 + j], gate_vec(p[j], bb[2 * j], bb[2 * j + 1]), &xx[8 + 4 * j]);
      }
    }
    STAMPW(0, 15);
    cluster_arrive_relaxed();
    cluster_wait();
    STAMPW(0, 16);
    if (tid == 0) g_epoch[blockIdx.x] = ep;
  }
}

typedef CUresult (*EncFn)(CUtensorMap*, CUtensorMapDataType, cuuint32_t, void*, const cuuint64_t*, const cuuint64_t*, const cuuint32_t*, const cuuint32_t*,
                          CUtensorMapInterleave, CUtensorMapSwizzle, CUtensorMapL2promotion, CUtensorMapFloatOOBfill);

void make_map(EncFn enc, CUtensorMap* tm, const void* ptr, int rows, int cols, int box_rows, bool sw64 = false) {
  cuuint64_t gd[2] = {(cuuint64_t)cols, (cuuint64_t)rows};
  cuuint64_t gs[1] = {(cuuint64_t)cols * 2};
  cuuint32_t bx[2] = {sw64 ? 32u : 64u, (cuuint32_t)box_rows};
  cuuint32_t es[2] = {1, 1};
  enc(tm, CU_TENSOR_MAP_DATA_TYPE_BFLOAT16, 2, const_cast<void*>(ptr), gd, gs, bx, es, CU_TENSOR_MAP_INTERLEAVE_NONE, sw64 ? CU_TENSOR_MAP_SWIZZLE_64B : CU_TENSOR_MAP_SWIZZLE_128B,
      CU_TENSOR_MAP_L2_PROMOTION_L2_256B, CU_TENSOR_MAP_FLOAT_OOB_FILL_NONE);
}

}

extern "C" void kernel_launch(void* const* d_in, const int* in_sizes, int n_in, void* d_out, int out_size) {
  (void)in_sizes; (void)n_in; (void)out_size;
  static EncFn enc = nullptr;
  static void *a_ptr = nullptr, *m_ptr = nullptr;
  if (!enc) {
    void* fn = nullptr; cudaDriverEntryPointQueryResult q;
    cudaGetDriverEntryPoint("cuTensorMapEncodeTiled", &fn, cudaEnableDefault, &q);
    enc = (EncFn)fn;
    cudaFuncSetAttribute(fused_kernel, cudaFuncAttributeMaxDynamicSharedMemorySize, SMEM_BYTES);
    cudaGetSymbolAddress(&a_ptr, g_a);
    cudaGetSymbolAddress(&m_ptr, g_m);
  }
  Params P;
  P.x = (const __nv_bfloat16*)d_in[0];
  P.wqkv = (const __nv_bfloat16*)d_in[1];
  P.wo = (const __nv_bfloat16*)d_in[2];
  P.w1 = (const __nv_bfloat16*)d_in[4];
  P.b1 = (const __nv_bfloat16*)d_in[5];
  P.w2 = (const __nv_bfloat16*)d_in[6];
  P.b2 = (const __nv_bfloat16*)d_in[7];
  P.out = (__nv_bfloat16*)d_out;
  make_map(enc, &P.tm_wqkv, P.wqkv, D_, Q3_, 32);
  make_map(enc, &P.tm_w1, P.w1, D_, F_, 32);
  make_map(enc, &P.tm_w2, P.w2, F_, D_, 32);
  make_map(enc, &P.tm_m, m_ptr, D_, D_, 32);
  make_map(enc, &P.tm_wqkv64, P.wqkv, D_, Q3_, 64, true);
  make_map(enc, &P.tm_m64, m_ptr, D_, D_, 64, true);
  make_map(enc, &P.tm_a, a_ptr, S_, D_, 128);
  fused_kernel<<<NCTAS, NTHREADS, SMEM_BYTES, cudaStreamPerThread>>>(P);
}
```

```cpp
#include <cuda_runtime.h>
#include <cuda.h>
#include <cuda_bf16.h>
#include <stdint.h>

namespace {

constexpr int S_ = 2048, D_ = 576, F_ = 4608, Q3_ = 1728;
constexpr int NSTAGE = 6, STAGE_BYTES = 12288;
constexpr int SM_A = 0, SM_B = 147456, SM_BIAS = SM_B + NSTAGE * STAGE_BYTES, SM_RSTD = SM_BIAS + 2304, SM_KV = SM_RSTD + 512, SM_BAR = SM_KV + 4 * 19 * 80;
constexpr int SMEM_BYTES = SM_BAR + 320;
constexpr int NTHREADS = 384;
constexpr int NCTAS = 132;

__device__ uint4 g_qkvf[(128 * 108 + 1) * 32];
__device__ __align__(1024) __nv_bfloat16 g_a[S_ * D_];
__device__ __align__(1024) __nv_bfloat16 g_m[D_ * D_];
__device__ uint4 g_kvp[32 * 5 * 32 * 32];
__device__ uint4 g_kvt[32 * 5 * 32];
__device__ uint4 g_part[128 * 8 * 36 * 32];
__device__ uint4 g_s[128 * 24 * 32];
__device__ uint4 g_g[128 * 24 * 32];
__device__ uint4 g_hsp[128 * 12 * 256];
__device__ uint32_t g_f_qkv[16 * 8];
__device__ uint32_t g_f_kvp[32];
__device__ uint32_t g_f_kvt[32];
__device__ uint32_t g_f_a[16];
__device__ uint32_t g_f_m[1];
__device__ uint32_t g_f_rb[128 * 8];
__device__ uint2 g_stat[S_];
__device__ uint32_t g_epoch[NCTAS];

#define STAMP(i)
#define STAMPW(w, i)
#define WSTAMP(i)
__device__ __forceinline__ uint32_t smem_u32(const void* p) { return (uint32_t)__cvta_generic_to_shared(p); }
__device__ __forceinline__ void mbar_init(uint32_t a, int c) { asm volatile("mbarrier.init.shared::cta.b64 [%0], %1;" ::"r"(a), "r"(c)); }
__device__ __forceinline__ void mbar_expect(uint32_t a, uint32_t b) { asm volatile("mbarrier.arrive.expect_tx.shared::cta.b64 _, [%0], %1;" ::"r"(a), "r"(b) : "memory"); }
__device__ __forceinline__ void mbar_arrive(uint32_t a) { asm volatile("mbarrier.arrive.shared::cta.b64 _, [%0];" ::"r"(a) : "memory"); }
__device__ __forceinline__ void mbar_arrive_cl(uint32_t a) { asm volatile("mbarrier.arrive.shared::cluster.b64 _, [%0];" ::"r"(a) : "memory"); }
__device__ __forceinline__ uint32_t mapa(uint32_t a, uint32_t cta) { uint32_t r; asm volatile("mapa.shared::cluster.u32 %0, %1, %2;" : "=r"(r) : "r"(a), "r"(cta)); return r; }
__device__ __forceinline__ void mbar_wait(uint32_t a, uint32_t ph) {
  uint32_t ok; int it = 0;
#pragma unroll 1
  do {
    asm volatile("{.reg .pred p; mbarrier.try_wait.parity.shared::cta.b64 p, [%1], %2; selp.u32 %0,1,0,p;}" : "=r"(ok) : "r"(a), "r"(ph) : "memory");
  } while (!ok && ++it < (1 << 18));
}
__device__ __forceinline__ void tma2d(uint32_t dst, const CUtensorMap* m, int c0, int c1, uint32_t bar) {
  asm volatile("cp.async.bulk.tensor.2d.shared::cluster.global.mbarrier::complete_tx::bytes [%0], [%1, {%3,%4}], [%2];" ::"r"(dst), "l"(m), "r"(bar), "r"(c0), "r"(c1) : "memory");
}
__device__ __forceinline__ void tma2d_mc(uint32_t dst, const CUtensorMap* m, int c0, int c1, uint32_t bar) {
  asm volatile("cp.async.bulk.tensor.2d.shared::cluster.global.mbarrier::complete_tx::bytes.multicast::cluster [%0], [%1, {%3,%4}], [%2], %5;" ::"r"(dst), "l"(m), "r"(bar), "r"(c0), "r"(c1), "h"((uint16_t)3) : "memory");
}
__device__ __forceinline__ void cluster_arrive_relaxed() { asm volatile("barrier.cluster.arrive.relaxed.aligned;" ::: "memory"); }
__device__ __forceinline__ void cluster_wait() { asm volatile("barrier.cluster.wait.acquire.aligned;" ::: "memory"); }
__device__ __forceinline__ void wg_fence() { asm volatile("wgmma.fence.sync.aligned;" ::: "memory"); }
__device__ __forceinline__ void wg_commit() { asm volatile("wgmma.commit_group.sync.aligned;" ::: "memory"); }
template <int n> __device__ __forceinline__ void wg_wait() { asm volatile("wgmma.wait_group.sync.aligned %0;" ::"n"(n) : "memory"); }
__device__ __forceinline__ uint32_t ld_acquire(const uint32_t* p) { uint32_t v; asm volatile("ld.acquire.gpu.global.u32 %0, [%1];" : "=r"(v) : "l"(p) : "memory"); return v; }
__device__ __forceinline__ void flag_wait(const uint32_t* p, uint32_t target) {
  int it = 0;
#pragma unroll 1
  while ((int)(ld_acquire(p) - target) < 0 && ++it < (1 << 20)) __nanosleep(300);
}
__device__ __forceinline__ void hint_signal(uint32_t* p) {
  if ((threadIdx.x & 31) == 0) asm volatile("red.relaxed.gpu.global.add.u32 [%0], 1;" ::"l"(p) : "memory");
}
__device__ __forceinline__ void hint_wait(const uint32_t* p, uint32_t target, uint32_t ns = 400) {
  int it = 0; uint32_t v;
#pragma unroll 1
  do { asm volatile("ld.relaxed.gpu.global.u32 %0, [%1];" : "=r"(v) : "l"(p) : "memory"); if ((int)(v - target) >= 0) break; __nanosleep(ns); } while (++it < (1 << 20));
}
__device__ __forceinline__ uint32_t tag(uint32_t x, uint32_t par) { uint32_t r; asm("lop3.b32 %0, %1, 0xfffffffe, %2, 0xea;" : "=r"(r) : "r"(x), "r"(par)); return r; }
__device__ __forceinline__ void st_ll(uint4* p, uint32_t x, uint32_t y, uint32_t z, uint32_t w, uint32_t par) {
  asm volatile("{.reg .b64 a, b; mov.b64 a, {%1,%2}; mov.b64 b, {%3,%4}; st.relaxed.gpu.global.v2.b64 [%0], {a, b};}"
               ::"l"(p), "r"(tag(x, par)), "r"(y), "r"(tag(z, par)), "r"(w) : "memory");
}
__device__ __forceinline__ uint4 ld_ll(const uint4* p) {
  uint4 v;
  asm volatile("{.reg .b64 a, b; ld.relaxed.gpu.global.v2.b64 {a, b}, [%4]; mov.b64 {%0,%1}, a; mov.b64 {%2,%3}, b;}"
               : "=r"(v.x), "=r"(v.y), "=r"(v.z), "=r"(v.w) : "l"(p) : "memory");
  return v;
}
__device__ __forceinline__ uint2 ld_ll64(const uint32_t* p) {
  uint2 v;
  asm volatile("{.reg .b64 a; ld.relaxed.gpu.global.b64 a, [%2]; mov.b64 {%0,%1}, a;}" : "=r"(v.x), "=r"(v.y) : "l"(p) : "memory");
  return v;
}
__device__ __forceinline__ void ll_chk(uint32_t& bad, uint32_t a, uint32_t b, uint32_t par) {
  uint32_t u; asm("lop3.b32 %0, %1, %2, %3, 0x7e;" : "=r"(u) : "r"(a), "r"(b), "r"(par));
  asm("or.b32 %0, %0, %1;" : "+r"(bad) : "r"(u));
}
__device__ __forceinline__ uint32_t hadd2(uint32_t a, uint32_t b) { uint32_t d; asm("add.rn.bf16x2 %0, %1, %2;" : "=r"(d) : "r"(a), "r"(b)); return d; }
__device__ __forceinline__ uint32_t hfma2(uint32_t a, uint32_t b, uint32_t c) { uint32_t d; asm("fma.rn.bf16x2 %0, %1, %2, %3;" : "=r"(d) : "r"(a), "r"(b), "r"(c)); return d; }
__device__ __forceinline__ uint32_t pack_bf16(float lo, float hi) { uint32_t r; asm("cvt.rn.bf16x2.f32 %0, %1, %2;" : "=r"(r) : "f"(hi), "f"(lo)); return r; }
__device__ __forceinline__ float bf_lo(uint32_t v) { return __uint_as_float(v << 16); }
__device__ __forceinline__ float bf_hi(uint32_t v) { return __uint_as_float(v & 0xffff0000u); }
__device__ __forceinline__ uint32_t movmat(uint32_t a) { uint32_t d; asm volatile("movmatrix.sync.aligned.m8n8.trans.b16 %0, %1;" : "=r"(d) : "r"(a)); return d; }
__device__ __forceinline__ void mma16816(float* c, uint32_t a0, uint32_t a1, uint32_t a2, uint32_t a3, uint32_t b0, uint32_t b1) {
  asm volatile("mma.sync.aligned.m16n8k16.row.col.f32.bf16.bf16.f32 {%0,%1,%2,%3}, {%4,%5,%6,%7}, {%8,%9}, {%0,%1,%2,%3};"
               : "+f"(c[0]), "+f"(c[1]), "+f"(c[2]), "+f"(c[3]) : "r"(a0), "r"(a1), "r"(a2), "r"(a3), "r"(b0), "r"(b1));
}
__device__ __forceinline__ uint4 ldcg128(const void* p) { uint4 v; asm volatile("ld.global.cg.v4.u32 {%0,%1,%2,%3}, [%4];" : "=r"(v.x), "=r"(v.y), "=r"(v.z), "=r"(v.w) : "l"(p) : "memory"); return v; }

template <int N> __device__ __forceinline__ void wgmma_ss(float* d, uint64_t da, uint64_t db, int sc);
template <int N> __device__ __forceinline__ void wgmma_rs(float* d, const uint32_t* a, uint64_t db, int sc);
template <> __device__ __forceinline__ void wgmma_ss<96>(float* d, uint64_t da, uint64_t db, int sc) {
  asm volatile("{.reg .pred p; setp.ne.b32 p, %50, 0; wgmma.mma_async.sync.aligned.m64n96k16.f32.bf16.bf16 {%0, %1, %2, %3, %4, %5, %6, %7, %8, %9, %10, %11, %12, %13, %14, %15, %16, %17, %18, %19, %20, %21, %22, %23, %24, %25, %26, %27, %28, %29, %30, %31, %32, %33, %34, %35, %36, %37, %38, %39, %40, %41, %42, %43, %44, %45, %46, %47}, %48, %49, p, 1, 1, 0, 1;}"
   : "+f"(d[0]), "+f"(d[1]), "+f"(d[2]), "+f"(d[3]), "+f"(d[4]), "+f"(d[5]), "+f"(d[6]), "+f"(d[7]), "+f"(d[8]), "+f"(d[9]), "+f"(d[10]), "+f"(d[11]), "+f"(d[12]), "+f"(d[13]), "+f"(d[14]), "+f"(d[15]), "+f"(d[16]), "+f"(d[17]), "+f"(d[18]), "+f"(d[19]), "+f"(d[20]), "+f"(d[21]), "+f"(d[22]), "+f"(d[23]), "+f"(d[24]), "+f"(d[25]), "+f"(d[26]), "+f"(d[27]), "+f"(d[28]), "+f"(d[29]), "+f"(d[30]), "+f"(d[31]), "+f"(d[32]), "+f"(d[33]), "+f"(d[34]), "+f"(d[35]), "+f"(d[36]), "+f"(d[37]), "+f"(d[38]), "+f"(d[39]), "+f"(d[40]), "+f"(d[41]), "+f"(d[42]), "+f"(d[43]), "+f"(d[44]), "+f"(d[45]), "+f"(d[46]), "+f"(d[47]) : "l"(da), "l"(db), "r"(sc));
}
template <> __device__ __forceinline__ void wgmma_ss<192>(float* d, uint64_t da, uint64_t db, int sc) {
  asm volatile("{.reg .pred p; setp.ne.b32 p, %98, 0; wgmma.mma_async.sync.aligned.m64n192k16.f32.bf16.bf16 {%0, %1, %2, %3, %4, %5, %6, %7, %8, %9, %10, %11, %12, %13, %14, %15, %16, %17, %18, %19, %20, %21, %22, %23, %24, %25, %26, %27, %28, %29, %30, %31, %32, %33, %34, %35, %36, %37, %38, %39, %40, %41, %42, %43, %44, %45, %46, %47, %48, %49, %50, %51, %52, %53, %54, %55, %56, %57, %58, %59, %60, %61, %62, %63, %64, %65, %66, %67, %68, %69, %70, %71, %72, %73, %74, %75, %76, %77, %78, %79, %80, %81, %82, %83, %84, %85, %86, %87, %88, %89, %90, %91, %92, %93, %94, %95}, %96, %97, p, 1, 1, 0, 1;}"
   : "+f"(d[0]), "+f"(d[1]), "+f"(d[2]), "+f"(d[3]), "+f"(d[4]), "+f"(d[5]), "+f"(d[6]), "+f"(d[7]), "+f"(d[8]), "+f"(d[9]), "+f"(d[10]), "+f"(d[11]), "+f"(d[12]), "+f"(d[13]), "+f"(d[14]), "+f"(d[15]), "+f"(d[16]), "+f"(d[17]), "+f"(d[18]), "+f"(d[19]), "+f"(d[20]), "+f"(d[21]), "+f"(d[22]), "+f"(d[23]), "+f"(d[24]), "+f"(d[25]), "+f"(d[26]), "+f"(d[27]), "+f"(d[28]), "+f"(d[29]), "+f"(d[30]), "+f"(d[31]), "+f"(d[32]), "+f"(d[33]), "+f"(d[34]), "+f"(d[35]), "+f"(d[36]), "+f"(d[37]), "+f"(d[38]), "+f"(d[39]), "+f"(d[40]), "+f"(d[41]), "+f"(d[42]), "+f"(d[43]), "+f"(d[44]), "+f"(d[45]), "+f"(d[46]), "+f"(d[47]), "+f"(d[48]), "+f"(d[49]), "+f"(d[50]), "+f"(d[51]), "+f"(d[52]), "+f"(d[53]), "+f"(d[54]), "+f"(d[55]), "+f"(d[56]), "+f"(d[57]), "+f"(d[58]), "+f"(d[59]), "+f"(d[60]), "+f"(d[61]), "+f"(d[62]), "+f"(d[63]), "+f"(d[64]), "+f"(d[65]), "+f"(d[66]), "+f"(d[67]), "+f"(d[68]), "+f"(d[69]), "+f"(d[70]), "+f"(d[71]), "+f"(d[72]), "+f"(d[73]), "+f"(d[74]), "+f"(d[75]), "+f"(d[76]), "+f"(d[77]), "+f"(d[78]), "+f"(d[79]), "+f"(d[80]), "+f"(d[81]), "+f"(d[82]), "+f"(d[83]), "+f"(d[84]), "+f"(d[85]), "+f"(d[86]), "+f"(d[87]), "+f"(d[88]), "+f"(d[89]), "+f"(d[90]), "+f"(d[91]), "+f"(d[92]), "+f"(d[93]), "+f"(d[94]), "+f"(d[95]) : "l"(da), "l"(db), "r"(sc));
}

__device__ __forceinline__ uint64_t desc64(uint32_t lo, uint32_t hi) { uint64_t d; asm("mov.b64 %0, {%1, %2};" : "=l"(d) : "r"(lo), "r"(hi)); return d; }
constexpr uint32_t DESC_HI = (1024u >> 4) | (1u << 30);
constexpr uint32_t DESC_HI64 = (512u >> 4) | (2u << 30);
template <int n> __device__ __forceinline__ void fence_regs(float* a) {
#pragma unroll
  for (int i = 0; i < n; i++) asm volatile("" : "+f"(a[i])::"memory");
}

struct Ctx {
  uint32_t full;
  uint32_t emb;
  bool sig;
  uint32_t stage, phase, prev;
  uint32_t dB, dA;
  __device__ __forceinline__ void release_prev() { if (sig && prev != ~0u) mbar_arrive_cl(emb + prev); }
  __device__ __forceinline__ void wait_full() {
    mbar_wait(full + 8 * stage, phase);
    wg_fence();
  }
};

__device__ __forceinline__ void issue192(float* acc, Ctx& c, int s, bool first = false) {
  c.wait_full();
  const uint32_t db = c.dB + c.stage * (STAGE_BYTES >> 4);
  const uint32_t da = c.dA + (s >> 1) * 1024 + (s & 1) * 4;
  wgmma_ss<192>(acc, desc64(da, DESC_HI), desc64(db, DESC_HI), first ? 0 : 1);
  wgmma_ss<192>(acc, desc64(da + 2, DESC_HI), desc64(db + 128, DESC_HI), 1);
  wg_commit();
}
__device__ __forceinline__ void issue96(float* acc, Ctx& c, int s, bool first) {
  c.wait_full();
  const uint32_t db = c.dB + c.stage * (STAGE_BYTES >> 4);
  const uint32_t da = c.dA + s * 1024;
  if (first) { wgmma_ss<192>(acc, desc64(da, DESC_HI), desc64(db, DESC_HI64), 0); wg_fence(); }
#pragma unroll
  for (int kk = first ? 1 : 0; kk < 4; kk++) wgmma_ss<96>(acc, desc64(da + 2 * kk, DESC_HI), desc64(db + 64 * kk, DESC_HI64), 1);
  wg_commit();
}
__device__ __forceinline__ void retire(Ctx& c) {
  wg_wait<1>();
  c.release_prev();
  c.prev = 8 * c.stage;
  if (++c.stage == NSTAGE) { c.stage = 0; c.phase ^= 1; }
}
constexpr float GK = 0.32920349f;
__device__ __forceinline__ uint32_t gelu_pair(uint32_t y) {
  uint32_t u, th;
  asm("mul.rn.bf16x2 %0, %1, %2;" : "=r"(u) : "r"(hfma2(y, y, 0x401b401bu)), "r"(y));
  asm("tanh.approx.bf16x2 %0, %1;" : "=r"(th) : "r"(u));
  return hfma2(y, th, y);
}
__device__ __forceinline__ uint4 gelu_group(const uint32_t* a) { return make_uint4(gelu_pair(a[0]), gelu_pair(a[1]), gelu_pair(a[2]), gelu_pair(a[3])); }
__device__ __forceinline__ void lds_bias(float2* b, uint32_t addr) {
#pragma unroll
  for (int j = 0; j < 4; j++) asm volatile("ld.shared.v2.f32 {%0,%1}, [%2];" : "=f"(b[j].x), "=f"(b[j].y) : "r"(addr + 32 * j));
}
__device__ __forceinline__ int opaque(int v) { asm volatile("" : "+r"(v)); return v; }
__device__ __forceinline__ void stsm4(uint32_t addr, uint4 r) {
  asm volatile("stmatrix.sync.aligned.m8n8.x4.shared.b16 [%0], {%1,%2,%3,%4};" ::"r"(addr), "r"(r.x), "r"(r.y), "r"(r.z), "r"(r.w) : "memory");
}
__device__ __forceinline__ float ex2f(float x) { float r; asm("ex2.approx.ftz.f32 %0, %1;" : "=f"(r) : "f"(x)); return r; }
__device__ __forceinline__ float phi(float t) { float e = ex2f(t * 1.4426950408889634f); if (t > 0.f) e = t + 1.f; return e + 1e-6f; }
__device__ __forceinline__ uint32_t phi2(uint32_t w) { return pack_bf16(phi(bf_lo(w)), phi(bf_hi(w))); }
template <int q0, int q1>
__device__ __forceinline__ void part_groups(const float* a, uint4* p, uint32_t par) {
#pragma unroll
  for (int q = q0; q < q1; q++)
    st_ll(p + q * 32, pack_bf16(a[8 * q], a[8 * q + 1]), pack_bf16(a[8 * q + 2], a[8 * q + 3]), pack_bf16(a[8 * q + 4], a[8 * q + 5]), pack_bf16(a[8 * q + 6], a[8 * q + 7]), par);
}
__device__ __forceinline__ float silu(float y) { return __fdividef(y, 1.f + ex2f(y * -1.4426950408889634f)); }
__device__ __forceinline__ uint4 gate_vec(const uint4* p, uint32_t b0, uint32_t b1) {
  uint32_t o[4];
#pragma unroll
  for (int q = 0; q < 4; q++) {
    uint32_t w[8];
#pragma unroll
    for (int i = 0; i < 8; i++) w[i] = reinterpret_cast<const uint32_t*>(&p[i])[q];
    const uint32_t u0 = hadd2(hadd2(w[0], w[1]), hadd2(w[2], w[3])), u1 = hadd2(hadd2(w[4], w[5]), hadd2(w[6], w[7]));
    const uint32_t bb = q < 2 ? b0 : b1;
    o[q] = pack_bf16(silu(fmaf(bf_lo(u0) + bf_lo(u1), 0.5f / GK, bf_lo(bb))), silu(fmaf(bf_hi(u0) + bf_hi(u1), 0.5f / GK, bf_hi(bb))));
  }
  return make_uint4(o[0], o[1], o[2], o[3]);
}
__device__ __forceinline__ int coloff(int c) { return (c >> 4) * 128 + ((c & 7) >> 1) * 4 + ((c >> 3) & 1) * 2; }

__device__ __forceinline__ void d1_load(uint32_t* W, int rb0, int head, int ln) {
  const uint32_t* qf = reinterpret_cast<const uint32_t*>(g_qkvf) + rb0 * 108 * 128 + (ln >> 2) * 16;
#pragma unroll
  for (int b = 0; b < 3; b++) {
    const uint32_t* p = qf + coloff(576 + head * 18 + 8 * b + 2 * (ln & 3));
#pragma unroll
    for (int j = 0; j < 4; j++) {
      const uint2 kk = ld_ll64(p + j * 108 * 128), vv = ld_ll64(p + j * 108 * 128 + 36 * 128);
      W[6 * j + 2 * b] = kk.x; W[6 * j + 2 * b + 1] = kk.y; W[24 + 6 * j + 2 * b] = vv.x; W[24 + 6 * j + 2 * b + 1] = vv.y;
    }
  }
}
__device__ __forceinline__ bool d1_bad(const uint32_t* W, int t, uint32_t par) {
  uint32_t bad = 0, bad2 = 0;
#pragma unroll
  for (int q = 0; q < 12; q++) ll_chk((q % 3) != 2 ? bad : bad2, W[2 * q], W[24 + 2 * q], par);
  return __any_sync(0xffffffffu, (bad | (t == 0 ? bad2 : 0u)) & 1);
}
__device__ __forceinline__ void d1_phi(uint32_t* W, int j, int t) {
#pragma unroll
  for (int q = 0; q < 6; q++) W[6 * j + q] = phi2(W[6 * j + q]);
  if (t != 0) { W[6 * j + 4] = W[6 * j + 5] = 0u; W[24 + 6 * j + 4] = W[24 + 6 * j + 5] = (t == 1 ? 0x00003f80u : 0u); }
}
__device__ __forceinline__ void d1_mov(uint32_t* W, int j) {
#pragma unroll
  for (int q = 0; q < 6; q++) { W[6 * j + q] = movmat(W[6 * j + q]); W[24 + 6 * j + q] = movmat(W[24 + 6 * j + q]); }
}
__device__ __forceinline__ void d1_mma_store(const uint32_t* W, int head, int blk, int ln, uint32_t par) {
  float c0[3][4], c1[3][4];
#pragma unroll
  for (int j = 0; j < 3; j++) { c0[j][0] = c0[j][1] = c0[j][2] = c0[j][3] = 0.f; c1[j][0] = c1[j][1] = c1[j][2] = c1[j][3] = 0.f; }
#pragma unroll
  for (int ks = 0; ks < 4; ks++)
#pragma unroll
    for (int j = 0; j < 3; j++) {
      mma16816(c0[j], W[24 + 6 * ks], W[24 + 6 * ks + 2], W[24 + 6 * ks + 1], W[24 + 6 * ks + 3], W[6 * ks + 2 * j], W[6 * ks + 2 * j + 1]);
      mma16816(c1[j], W[24 + 6 * ks + 4], 0u, W[24 + 6 * ks + 5], 0u, W[6 * ks + 2 * j], W[6 * ks + 2 * j + 1]);
    }
  uint4* dst = &g_kvp[(head * 160 + blk) * 32 + ln];
#pragma unroll
  for (int j = 0; j < 3; j++) st_ll(dst + j * 1024, __float_as_uint(c0[j][0]), __float_as_uint(c0[j][1]), __float_as_uint(c0[j][2]), __float_as_uint(c0[j][3]), par);
  st_ll(dst + 3072, __float_as_uint(c1[0][0]), __float_as_uint(c1[0][1]), __float_as_uint(c1[1][0]), __float_as_uint(c1[1][1]), par);
  st_ll(dst + 4096, __float_as_uint(c1[2][0]), __float_as_uint(c1[2][1]), 0u, 0u, par);
  hint_signal(&g_f_kvp[head]);
}

struct Params {
  CUtensorMap tm_wqkv, tm_w1, tm_w2, tm_m, tm_wqkv64, tm_m64, tm_a;
  const __nv_bfloat16 *x, *b1, *b2, *wqkv, *w1, *w2, *wo;
  __nv_bfloat16* out;
};

__global__ void __cluster_dims__(2, 1, 1) __launch_bounds__(NTHREADS, 1) fused_kernel(const __grid_constant__ Params P) {
  extern __shared__ __align__(1024) uint8_t smem[];
  const uint32_t sbase = smem_u32(smem);
  const int tid = threadIdx.x, lane = tid & 31;
  const int warp = __shfl_sync(0xffffffffu, tid >> 5, 0);
  const int g = lane >> 2, t = lane & 3;
  const uint32_t ep = __shfl_sync(0xffffffffu, g_epoch[blockIdx.x], 0) + 1;
  const uint32_t par = ep & 1;
  STAMPW(0, 0);

  if (blockIdx.x >= 128) {
    const int a = blockIdx.x - 128;
    if (warp >= 8 && lane == 0) {
      const int id = a * 4 + (warp - 8);
      constexpr uint32_t CH = 9216 * 2;
      __nanosleep(1500);
#pragma unroll 1
      for (int i = id; i < 576; i += 16) {
        const char* p = i < 288 ? (const char*)P.w1 + (size_t)i * CH : (const char*)P.w2 + (size_t)(i - 288) * CH;
        asm volatile("cp.async.bulk.prefetch.L2.global [%0], %1;" ::"l"(p), "r"(CH) : "memory");
      }
    }
    __syncwarp();
#pragma unroll 1
    for (int u0 = a * 12 + warp; u0 < 160; u0 += 48) {
      const int head = u0 / 5, u = u0;
      if (lane == 0) hint_wait(&g_f_kvp[head], 32 * ep, 50);
      __syncwarp();
      STAMPW(0, 1);
      uint4 v[32];
      int tries = 0;
      uint32_t bad;
#pragma unroll 1
      do {
        bad = 0;
#pragma unroll
        for (int j = 0; j < 32; j++) v[j] = ld_ll(&g_kvp[(u * 32 + j) * 32 + lane]);
#pragma unroll
        for (int j = 0; j < 32; j++) ll_chk(bad, v[j].x, v[j].z, par);
      } while (__any_sync(0xffffffffu, bad & 1) && ++tries < (1 << 20));
      float s0 = 0.f, s1 = 0.f, s2 = 0.f, s3 = 0.f;
#pragma unroll
      for (int j = 0; j < 32; j++) { s0 += __uint_as_float(v[j].x); s1 += __uint_as_float(v[j].y); s2 += __uint_as_float(v[j].z); s3 += __uint_as_float(v[j].w); }
      st_ll(&g_kvt[u * 32 + lane], __float_as_uint(s0), __float_as_uint(s1), __float_as_uint(s2), __float_as_uint(s3), par);
      hint_signal(&g_f_kvt[head]);
      STAMPW(0, 2);
    }
    __syncthreads();
    if (tid == 0) g_epoch[blockIdx.x] = ep;
    return;
  }

  const int cl = blockIdx.x >> 1, rank = blockIdx.x & 1;
  const int f = cl & 7, m = (cl >> 3) * 2 + rank;
  const int srole = f >= 6 ? 1 : 0;
  const uint32_t bar_full = sbase + SM_BAR, bar_empty = bar_full + 8 * NSTAGE, bar_xfree = bar_empty + 8 * NSTAGE, bar_ofull = bar_xfree + 72,
                 bar_d = bar_ofull + 72;

  if (tid == 0) {
#pragma unroll 1
    for (int i = 0; i < NSTAGE; i++) { mbar_init(bar_full + 8 * i, 1); mbar_init(bar_empty + 8 * i, 4); }
#pragma unroll 1
    for (int i = 0; i < 9; i++) { mbar_init(bar_xfree + 8 * i, 2); mbar_init(bar_ofull + 8 * i, 1); }
    mbar_init(bar_d, 1);
    asm volatile("fence.mbarrier_init.release.cluster;" ::: "memory");
  }
  __syncwarp();
  cluster_arrive_relaxed();

  if (warp >= 8) {
    const int srow = m * 128 + f * 16 + (warp - 8) * 4 + (lane >> 3);
    uint4 xs[9];
#pragma unroll
    for (int kb = 0; kb < 9; kb++) xs[kb] = __ldg(reinterpret_cast<const uint4*>(P.x + srow * D_) + (lane & 7) + kb * 8);
    auto stats = [&]() {
      const uint32_t* w = reinterpret_cast<const uint32_t*>(xs);
      float s0 = 0.f, s1 = 0.f;
#pragma unroll
      for (int i = 0; i < 36; i++) { s0 += bf_lo(w[i]); s1 += bf_hi(w[i]); }
      float sum = s0 + s1;
      sum += __shfl_xor_sync(0xffffffffu, sum, 1); sum += __shfl_xor_sync(0xffffffffu, sum, 2); sum += __shfl_xor_sync(0xffffffffu, sum, 4);
      const float mean = sum * (1.f / 576.f);
      s0 = 0.f; s1 = 0.f;
#pragma unroll
      for (int i = 0; i < 36; i++) { const float a = bf_lo(w[i]) - mean, b = bf_hi(w[i]) - mean; s0 = fmaf(a, a, s0); s1 = fmaf(b, b, s1); }
      float sq = s0 + s1;
      sq += __shfl_xor_sync(0xffffffffu, sq, 1); sq += __shfl_xor_sync(0xffffffffu, sq, 2); sq += __shfl_xor_sync(0xffffffffu, sq, 4);
      const float rstd = rsqrtf(sq * (1.f / 576.f) + 1e-5f);
      if ((lane & 7) == 0)
        asm volatile("{.reg .b64 a; mov.b64 a, {%1,%2}; st.relaxed.gpu.global.b64 [%0], a;}" ::"l"(&g_stat[srow]), "r"((__float_as_uint(rstd) & ~1u) | par), "r"(pack_bf16(-mean, -mean)) : "memory");
    };
    stats();
    asm volatile("setmaxnreg.dec.sync.aligned.u32 56;");
    cluster_wait();
    if (warp == 8) {
      if (lane == 0) {
        uint32_t stage = 0, phase = 1;
        const uint32_t sb = sbase + SM_B;
#pragma unroll 1
        for (int tl = 2 * srole; tl < 8 + 2 * srole; tl++) {
          const CUtensorMap* map = tl == 0 ? &P.tm_wqkv : (tl == 1 ? &P.tm_wqkv64 : (tl < 5 ? &P.tm_w1 : (tl < 8 ? &P.tm_w2 : (tl == 8 ? &P.tm_m : &P.tm_m64))));
          const int col = tl < 2 ? 288 * f + 192 * tl : (tl < 5 ? 576 * f + 192 * (tl - 2) : (tl < 8 ? 192 * (tl - 5) : (tl == 8 ? 192 * (f - 5) : 96 * (f - 6))));
          const bool perm = tl >= 5 && tl < 8;
          const bool z = (tl & 7) == 1;
          if (tl == 8) { flag_wait(g_f_m, 128 * ep); asm volatile("fence.proxy.async.global;" ::: "memory"); }
          const int cs = z ? 32 : 64, rs = z ? 64 : 32, nst = z ? 9 : 18;
#pragma unroll 1
          for (int st = 0; st < nst; st++) {
            int row = st * rs;
            if (perm) row += 576 * f + ((st < 6) ? 192 : (st < 12 ? -192 : 0));
            mbar_wait(bar_empty + 8 * stage, phase);
            mbar_expect(bar_full + 8 * stage, 12288);
            const uint32_t dst = sb + stage * STAGE_BYTES;
            if (((st ^ rank) & 1) == 0) {
              tma2d_mc(dst, map, col, row, bar_full + 8 * stage);
              tma2d_mc(dst + 8192, map, col + 2 * cs, row, bar_full + 8 * stage);
            } else {
              tma2d_mc(dst + 4096, map, col + cs, row, bar_full + 8 * stage);
            }
            if (++stage == NSTAGE) { stage = 0; phase ^= 1; }
          }
        }
      }
      __syncwarp();
    } else {
      const int aw = warp - 9, ta = tid - 288;
      const int hi = f >> 2;
      float* skv = reinterpret_cast<float*>(smem + SM_KV);
      const int hM = 4 * f + (m >> 2), nM = 144 * (m & 3) + 2 * (ta < 72 ? ta : 0);
      uint32_t wo[18];
#pragma unroll
      for (int e = 0; e < 18; e++) wo[e] = __ldg(reinterpret_cast<const uint32_t*>(P.wo + (hM * 18 + e) * D_ + nM));
      if (aw == 0) {
        if (lane < 2) hint_wait(&g_f_qkv[m * 8 + 2 + 2 * lane + hi], 16 * ep);
        __syncwarp();
        if (lane == 0) mbar_arrive(bar_d);
        STAMP(20);
      }
#pragma unroll 1
      for (int hh = aw; hh < 4; hh += 3) {
        if (lane == 0) hint_wait(&g_f_kvt[4 * f + hh], 5 * ep);
        __syncwarp();
        uint4 kv[5];
        int tries = 0;
        uint32_t bad;
#pragma unroll 1
        do {
          bad = 0;
#pragma unroll
          for (int j = 0; j < 5; j++) kv[j] = ld_ll(&g_kvt[((4 * f + hh) * 5 + j) * 32 + lane]);
#pragma unroll
          for (int j = 0; j < 5; j++) ll_chk(bad, kv[j].x, kv[j].z, par);
        } while (__any_sync(0xffffffffu, bad & 1) && ++tries < (1 << 20));
        uint2* row = reinterpret_cast<uint2*>(skv + (hh * 19 + g) * 20 + 2 * t);
#pragma unroll
        for (int j = 0; j < 3; j++)
          if (j < 2 || t < 2) { row[4 * j] = make_uint2(kv[j].x, kv[j].y); row[80 + 4 * j] = make_uint2(kv[j].z, kv[j].w); }
        if (g < 3) {
          row[160] = make_uint2(kv[3].x, kv[3].y); row[164] = make_uint2(kv[3].z, kv[3].w);
          if (t < 2) row[168] = make_uint2(kv[4].x, kv[4].y);
        }
      }
      asm volatile("bar.sync 5, 96;" ::: "memory");
      STAMPW(9, 22);
      if (ta < 72) {
#pragma unroll 1
        for (int d0 = 0; d0 < 20; d0 += 4) {
          float ac[8];
#pragma unroll
          for (int q = 0; q < 8; q++) ac[q] = 0.f;
#pragma unroll
          for (int e = 0; e < 18; e++) {
            const float4 k4 = *reinterpret_cast<const float4*>(skv + ((m >> 2) * 19 + e) * 20 + d0);
            const float w0 = bf_lo(wo[e]), w1 = bf_hi(wo[e]);
            ac[0] = fmaf(k4.x, w0, ac[0]); ac[1] = fmaf(k4.x, w1, ac[1]); ac[2] = fmaf(k4.y, w0, ac[2]); ac[3] = fmaf(k4.y, w1, ac[3]);
            ac[4] = fmaf(k4.z, w0, ac[4]); ac[5] = fmaf(k4.z, w1, ac[5]); ac[6] = fmaf(k4.w, w0, ac[6]); ac[7] = fmaf(k4.w, w1, ac[7]);
          }
#pragma unroll
          for (int q = 0; q < 4; q++)
            if (d0 + q < 18) *reinterpret_cast<uint32_t*>(g_m + (hM * 18 + d0 + q) * D_ + nM) = pack_bf16(ac[2 * q], ac[2 * q + 1]);
        }
      }
      __syncwarp();
      if (lane == 0) hint_wait(&g_f_qkv[m * 8 + hi], 16 * ep);
      __syncwarp();
      {
        const uint32_t* qf = reinterpret_cast<const uint32_t*>(g_qkvf) + m * 8 * 108 * 128 + g * 16;
        uint2 nx[3];
        auto ldq = [&](int it) {
#pragma unroll
          for (int b = 0; b < 3; b++) nx[b] = ld_ll64(qf + (it >> 2) * 108 * 128 + coloff(72 * f + (it & 3) * 18 + 8 * b + 2 * t));
        };
        ldq(aw);
#pragma unroll 1
        for (int it = aw; it < 32; it += 3) {
          int tries = 0;
#pragma unroll 1
          while (true) {
            uint32_t bad = 0;
            ll_chk(bad, nx[0].x, nx[1].x, par); ll_chk(bad, t == 0 ? nx[2].x : par, par, par);
            if (!__any_sync(0xffffffffu, bad & 1) || ++tries > (1 << 20)) break;
            ldq(it);
          }
          const uint2 q0 = nx[0], q1 = nx[1], q2 = nx[2];
          if (it + 3 < 32) ldq(it + 3);
          float p[12] = {phi(bf_lo(q0.x)), phi(bf_hi(q0.x)), phi(bf_lo(q1.x)), phi(bf_hi(q1.x)), phi(bf_lo(q2.x)), phi(bf_hi(q2.x)),
                         phi(bf_lo(q0.y)), phi(bf_hi(q0.y)), phi(bf_lo(q1.y)), phi(bf_hi(q1.y)), phi(bf_lo(q2.y)), phi(bf_hi(q2.y))};
          const float2* zp = reinterpret_cast<const float2*>(skv + ((it & 3) * 19 + 18) * 20 + 2 * t);
          const float2 z0 = zp[0], z1 = zp[4], z2 = *reinterpret_cast<const float2*>(skv + ((it & 3) * 19 + 18) * 20 + 16);
          float d0 = p[0] * z0.x + p[1] * z0.y + p[2] * z1.x + p[3] * z1.y, d1 = p[6] * z0.x + p[7] * z0.y + p[8] * z1.x + p[9] * z1.y;
          if (t == 0) { d0 += p[4] * z2.x + p[5] * z2.y; d1 += p[10] * z2.x + p[11] * z2.y; }
          d0 += __shfl_xor_sync(0xffffffffu, d0, 1); d1 += __shfl_xor_sync(0xffffffffu, d1, 1);
          d0 += __shfl_xor_sync(0xffffffffu, d0, 2); d1 += __shfl_xor_sync(0xffffffffu, d1, 2);
          const float r0 = __fdividef(1.f, d0 + 1e-6f), r1 = __fdividef(1.f, d1 + 1e-6f);
          __nv_bfloat16* po = g_a + (m * 128 + (it >> 2) * 16 + g) * D_ + 72 * f + (it & 3) * 18 + 2 * t;
#pragma unroll
          for (int b = 0; b < 3; b++)
            if (b < 2 || t == 0) {
              *reinterpret_cast<uint32_t*>(po + 8 * b) = pack_bf16(p[2 * b] * r0, p[2 * b + 1] * r0);
              *reinterpret_cast<uint32_t*>(po + 8 * D_ + 8 * b) = pack_bf16(p[6 + 2 * b] * r1, p[7 + 2 * b] * r1);
            }
        }
      }
      asm volatile("fence.proxy.async.global;" ::: "memory");
      asm volatile("bar.sync 5, 96;" ::: "memory");
      if (ta == 0) {
        asm volatile("fence.acq_rel.gpu;" ::: "memory");
        asm volatile("red.relaxed.gpu.global.add.u32 [%0], 1;" ::"l"(&g_f_a[m]) : "memory");
        asm volatile("red.relaxed.gpu.global.add.u32 [%0], 1;" ::"l"(g_f_m) : "memory");
      }
      __syncwarp();
      STAMPW(9, 23);
      if (srole && aw == 2) {
        if (lane == 0) {
          flag_wait(&g_f_a[m], 8 * ep);
          asm volatile("fence.proxy.async.global;" ::: "memory");
#pragma unroll 1
          for (int kb = 0; kb < 9; kb++) {
            mbar_wait(bar_xfree + 8 * kb, 0);
            mbar_expect(bar_ofull + 8 * kb, 16384);
            tma2d(sbase + SM_A + kb * 16384, &P.tm_a, kb * 64, m * 128, bar_ofull + 8 * kb);
          }
        }
        __syncwarp();
      }
      const int rbg = m * 8 + f;
#pragma unroll 1
      for (int ch = 0; ch < 2; ch++) {
        if (lane == 0) hint_wait(&g_f_rb[rbg * 8 + ch], 8 * ep);
        __syncwarp();
        STAMPW(9, 24 + 2 * ch);
#pragma unroll 1
        for (int v = ch * 12 + aw * 4; v < ch * 12 + aw * 4 + 4; v++) {
          const uint32_t b0 = __ldg(reinterpret_cast<const uint32_t*>(P.b2 + 16 * v + 2 * t)), b1 = __ldg(reinterpret_cast<const uint32_t*>(P.b2 + 16 * v + 8 + 2 * t));
          uint4 p[8];
          int tries = 0;
          uint32_t bad;
#pragma unroll 1
          do {
            bad = 0;
#pragma unroll
            for (int i = 0; i < 8; i++) p[i] = ld_ll(&g_part[((rbg * 8 + i) * 36 + v) * 32 + lane]);
#pragma unroll
            for (int i = 0; i < 8; i++) ll_chk(bad, p[i].x, p[i].z, par);
          } while (__any_sync(0xffffffffu, bad & 1) && ++tries < (1 << 20));
          const uint4 gt = gate_vec(p, b0, b1);
          st_ll(&g_g[(rbg * 24 + v) * 32 + lane], gt.x, gt.y, gt.z, gt.w, par);
        }
        hint_signal(&g_f_rb[rbg * 8 + 5 + ch]);
        STAMPW(9, 25 + 2 * ch);
      }
    }
    cluster_arrive_relaxed();
    cluster_wait();
  } else {
    const int wg = warp >> 2;
    {
      const int rs = lane >> 3, j = lane & 7;
      uint4 xv[4][9];
#pragma unroll
      for (int it = 0; it < 4; it++)
#pragma unroll
        for (int kb = 0; kb < 9; kb++) xv[it][kb] = __ldg(reinterpret_cast<const uint4*>(P.x + (m * 128 + warp * 16 + it * 4 + rs) * D_) + j + kb * 8);
      uint32_t bw0 = __ldg(reinterpret_cast<const uint32_t*>(P.b1 + 576 * f) + tid), bw1 = tid < 32 ? __ldg(reinterpret_cast<const uint32_t*>(P.b1 + 576 * f) + 256 + tid) : 0u;
      uint2 st[4];
      int tries = 0;
      uint32_t bad;
#pragma unroll 1
      do {
        bad = 0;
#pragma unroll
        for (int it = 0; it < 4; it++) st[it] = ld_ll64(reinterpret_cast<const uint32_t*>(&g_stat[m * 128 + warp * 16 + it * 4 + rs]));
        ll_chk(bad, st[0].x, st[1].x, par); ll_chk(bad, st[2].x, st[3].x, par);
      } while (__any_sync(0xffffffffu, bad & 1) && ++tries < (1 << 22));
      STAMPW(0, 19);
#pragma unroll
      for (int it = 0; it < 4; it++) {
        const uint32_t nm = st[it].y;
        uint8_t* dst = smem + SM_A + (warp * 16 + it * 4 + rs) * 128 + ((j ^ ((it * 4 + rs) & 7)) << 4);
#pragma unroll
        for (int kb = 0; kb < 9; kb++) {
          const uint4 w = xv[it][kb];
          *reinterpret_cast<uint4*>(dst + kb * 16384) = make_uint4(hadd2(w.x, nm), hadd2(w.y, nm), hadd2(w.z, nm), hadd2(w.w, nm));
        }
        if (j == 0) reinterpret_cast<uint32_t*>(smem + SM_RSTD)[warp * 16 + it * 4 + rs] = st[it].x;
      }
      reinterpret_cast<float2*>(smem + SM_BIAS)[tid] = make_float2(bf_lo(bw0) * GK, bf_hi(bw0) * GK);
      if (tid < 32) reinterpret_cast<float2*>(smem + SM_BIAS)[256 + tid] = make_float2(bf_lo(bw1) * GK, bf_hi(bw1) * GK);
      asm volatile("fence.proxy.async.shared::cta;" ::: "memory");
    }
    asm volatile("setmaxnreg.inc.sync.aligned.u32 224;");
    cluster_wait();
    asm volatile("bar.sync 1, 256;" ::: "memory");
    STAMPW(0, 1);
    Ctx c;
    c.full = bar_full;
    c.emb = __shfl_sync(0xffffffffu, mapa(bar_empty, (warp & 3) == 0 ? rank : (rank ^ 1)), 0);
    c.sig = lane == 0 && (warp & 3) < 2;
    c.stage = 0; c.phase = 0; c.prev = ~0u;
    c.dB = (((sbase + SM_B) & 0x3FFFF) >> 4) | ((4096u >> 4) << 16);
    c.dA = (((sbase + SM_A + wg * 8192) & 0x3FFFF) >> 4) | (1u << 16);
    const bool leader = (lane == 0) && ((warp & 3) == 0);

    const int rb = m * 8 + warp;
    const uint32_t bias_t = sbase + SM_BIAS + 8 * t;
    const uint32_t hst = sbase + SM_A + (warp * 16 + (lane & 7) + ((lane >> 3) & 1) * 8) * 128 + (((lane >> 4) ^ (lane & 7)) << 4);
    auto wg_sync = [&]() {
      asm volatile("fence.proxy.async.shared::cta;" ::: "memory");
      if (wg == 0) asm volatile("bar.sync 2, 128;" ::: "memory"); else asm volatile("bar.sync 3, 128;" ::: "memory");
    };
    float A[96], B[96];
#pragma unroll
    for (int i = 0; i < 96; i++) B[i] = 0.f;
#define GELU16(H0, H1, ACC, OFF) uint32_t E[8]; \
    _Pragma("unroll") for (int q = 0; q < 8; q++) E[q] = pack_bf16(fmaf(ACC[(OFF) + 2 * q], (q & 1) ? r1 : r0, bs[q >> 1].x), fmaf(ACC[(OFF) + 2 * q + 1], (q & 1) ? r1 : r0, bs[q >> 1].y)); \
    const uint4 H0 = gelu_group(E), H1 = gelu_group(E + 4);
#define SPART16(DST, ACC, OFF) { uint32_t E[8]; _Pragma("unroll") for (int q = 0; q < 8; q++) E[q] = pack_bf16(ACC[(OFF) + 2 * q] * ((q & 1) ? r1 : r0), ACC[(OFF) + 2 * q + 1] * ((q & 1) ? r1 : r0)); \
    st_ll(DST, E[0], E[1], E[2], E[3], par); st_ll(DST + 32, E[4], E[5], E[6], E[7], par); }
#define LDS_R(SC) float r0, r1; asm volatile("ld.shared.f32 %0, [%1];" : "=f"(r0) : "r"(rst)); asm volatile("ld.shared.f32 %0, [%1];" : "=f"(r1) : "r"(rst + 32)); r0 *= (SC); r1 *= (SC);
    const uint32_t rst = sbase + SM_RSTD + (warp * 16 + g) * 4;
#pragma unroll 1
    for (int i = srole; i < 4 + srole; i++) {
      {
        const uint32_t ow = i == 4 ? bar_ofull : 0u;
        if (ow) mbar_wait(ow, 0);
        issue192(A, c, 0, true);
        const int ln = opaque(lane);
        uint4* dst = i == 1 ? g_qkvf + (rb * 108 + 18 * f + 12) * 32 + ln : g_part + ((rb * 8 + f) * 36 + (i == 3 ? 0 : 24)) * 32 + ln;
        LDS_R(i == 2 ? GK : 1.f)
        retire(c);
        if (ow && leader) mbar_arrive(bar_xfree + 64);
        fence_regs<96>(B);
        int s = 1;
        if (i == 2) {
#pragma unroll 1
          for (; s < 3; s++) { issue192(A, c, s); retire(c); }
        }
        if (i > srole) {
#pragma unroll
          for (int u = 0; u < 6; u++, s++) {
            float2 bs[4];
            if (i == 2) lds_bias(bs, bias_t + (192 + 32 * u) * 4);
            if ((u & 1) && ow) mbar_wait(ow + 4 * s, 0);
            issue192(A, c, s);
            if (i == 2) {
              GELU16(h0, h1, B, 16 * u)
              stsm4((hst ^ ((2 * u & 3) << 5)) + (u >> 1) * 16384, h0);
              stsm4((hst ^ ((2 * u + 1 & 3) << 5)) + (u >> 1) * 16384, h1);
            } else if (i == 1) {
              if (u < 3) SPART16(dst + 2 * u * 32, B, 16 * u)
              if (u == 2) hint_signal(&g_f_qkv[m * 8 + f]);
            } else {
              part_groups<0, 2>(&B[16 * u], dst + 2 * u * 32, par);
              if (u == 5) hint_signal(&g_f_rb[rb * 8 + (i == 3 ? 0 : 2)]);
            }
            retire(c);
          }
        }
        const bool d1 = i == 1 + srole;
        const int send = d1 ? 9 : 15;
#pragma unroll 1
        for (; s < send; s++) {
          if (ow && !(s & 1)) mbar_wait(ow + 4 * s, 0);
          issue192(A, c, s);
          retire(c);
        }
        uint32_t W[48];
        if (d1) {
          const int head = 4 * f + (warp >> 1), rb0 = m * 8 + (warp & 1) * 4;
          issue192(A, c, 9);
          mbar_wait(bar_d, 0);
          d1_load(W, rb0, head, opaque(lane));
          retire(c);
          issue192(A, c, 10);
          retire(c);
          issue192(A, c, 11);
          int tries = 0;
#pragma unroll 1
          while (d1_bad(W, t, par) && ++tries < (1 << 20)) d1_load(W, rb0, head, opaque(lane));
          d1_phi(W, 0, t);
          retire(c);
          issue192(A, c, 12);
          d1_phi(W, 1, t); d1_mov(W, 0);
          retire(c);
          issue192(A, c, 13);
          d1_phi(W, 2, t); d1_mov(W, 1);
          retire(c);
          issue192(A, c, 14);
          d1_phi(W, 3, t); d1_mov(W, 2); d1_mov(W, 3);
          wg_wait<0>();
          asm volatile("bar.sync 4, 256;" ::: "memory");
          d1_mma_store(W, head, m * 2 + (warp & 1), opaque(lane), par);
          asm volatile("bar.sync 4, 256;" ::: "memory");
          STAMPW(0, 21);
          retire(c);
        }
        issue192(A, c, 15);
        if (i == 2) {
          const uint4* hsp = g_hsp + (blockIdx.x * 8 + warp) * 12 * 32 + opaque(lane);
#pragma unroll
          for (int q = 0; q < 12; q++) { const uint4 v = ldcg128(hsp + q * 32); W[4 * q] = v.x; W[4 * q + 1] = v.y; W[4 * q + 2] = v.z; W[4 * q + 3] = v.w; }
        } else {
#pragma unroll
          for (int q = 0; q < 48; q++) W[q] = 0;
        }
        retire(c);
        if (ow) mbar_wait(ow + 64, 0);
        issue192(A, c, 16);
        if (i == 2) wg_sync();
        retire(c);
        issue192(A, c, 17);
        if (i == 2) {
#pragma unroll
          for (int q = 0; q < 12; q++) stsm4((hst ^ ((q & 3) << 5)) + (3 + (q >> 2)) * 16384, make_uint4(W[4 * q], W[4 * q + 1], W[4 * q + 2], W[4 * q + 3]));
        }
        retire(c);
      }
      STAMPW(0, 2 + 2 * i);
      if ((i & 3) == 0) {
        issue96(B, c, 0, true);
        const int ln = opaque(lane);
        uint4* dst = i == 0 ? g_qkvf + (rb * 108 + 18 * f) * 32 + ln : g_s + (rb * 24 + 12 * (f - 6)) * 32 + ln;
        LDS_R(1.f)
        if (i != 0) { r0 = 1.f; r1 = 1.f; }
        retire(c);
        fence_regs<96>(A);
#pragma unroll
        for (int u = 0; u < 8; u++) {
          issue96(B, c, u + 1, false);
          if (u < 6) SPART16(dst + 2 * u * 32, A, 16 * (u < 6 ? u : 0))
          if (u == 5) hint_signal(i == 0 ? &g_f_qkv[m * 8 + f] : &g_f_rb[rb * 8 + f - 3]);
          retire(c);
        }
      } else {
        issue192(B, c, 0, true);
        const int ln = opaque(lane);
        uint4* dst = i == 1 ? g_hsp + (blockIdx.x * 8 + warp) * 12 * 32 + ln : g_part + ((rb * 8 + f) * 36 + 12) * 32 + ln;
        const bool xf = i == 3 && srole && leader;
        const uint32_t bsa = bias_t + (i == 1 ? 0 : 384) * 4;
        LDS_R(GK)
        retire(c);
        fence_regs<96>(A);
#pragma unroll
        for (int u = 0; u < 6; u++) {
          float2 bs[4];
          if (i != 3) lds_bias(bs, bsa + 32 * u * 4);
          issue192(B, c, u + 1);
          if (i != 3) {
            GELU16(h0, h1, A, 16 * u)
            if (i == 1) { dst[2 * u * 32] = h0; dst[(2 * u + 1) * 32] = h1; }
            else {
              stsm4((hst ^ ((2 * u & 3) << 5)) + (6 + (u >> 1)) * 16384, h0);
              stsm4((hst ^ ((2 * u + 1 & 3) << 5)) + (6 + (u >> 1)) * 16384, h1);
              if (u == 3) wg_sync();
            }
          } else {
            part_groups<0, 2>(&A[16 * u], dst + 2 * u * 32, par);
            if (u == 5) hint_signal(&g_f_rb[rb * 8 + 1]);
          }
          retire(c);
          if ((u & 1) && xf) mbar_arrive(bar_xfree + 4 * u - 4);
        }
#pragma unroll 1
        for (int s = 7; s < 17; s++) {
          issue192(B, c, s);
          if (s == 9 && i == 2) wg_sync();
          retire(c);
          if ((s & 1) == 0 && xf) mbar_arrive(bar_xfree + 4 * s - 8);
        }
        issue192(B, c, 17);
        retire(c);
      }
      STAMPW(0, 3 + 2 * i);
    }

    const int ln = opaque(lane);
    const __nv_bfloat16* xp = P.x + (rb * 16 + (ln >> 2)) * D_ + 2 * (ln & 3);
    __nv_bfloat16* op = P.out + (rb * 16 + (ln >> 2)) * D_ + 2 * (ln & 3);
    auto ldx = [&](uint32_t* xx, int col) {
      xx[0] = __ldg(reinterpret_cast<const uint32_t*>(xp + col)); xx[1] = __ldg(reinterpret_cast<const uint32_t*>(xp + 8 * D_ + col));
      xx[2] = __ldg(reinterpret_cast<const uint32_t*>(xp + col + 8)); xx[3] = __ldg(reinterpret_cast<const uint32_t*>(xp + 8 * D_ + col + 8));
    };
    auto stout = [&](int col, uint4 sv, uint4 gv, const uint32_t* xx) {
      *reinterpret_cast<uint32_t*>(op + col) = hfma2(sv.x, gv.x, xx[0]); *reinterpret_cast<uint32_t*>(op + 8 * D_ + col) = hfma2(sv.y, gv.y, xx[1]);
      *reinterpret_cast<uint32_t*>(op + col + 8) = hfma2(sv.z, gv.z, xx[2]); *reinterpret_cast<uint32_t*>(op + 8 * D_ + col + 8) = hfma2(sv.w, gv.w, xx[3]);
    };
    if (srole) {
      const int cb = 96 * (f - 6);
      uint32_t xx[24];
      uint4 gg[6];
#pragma unroll
      for (int q = 0; q < 6; q++) ldx(&xx[4 * q], cb + 16 * q);
      int tries = 0;
      uint32_t bad;
#pragma unroll 1
      do {
        bad = 0;
#pragma unroll
        for (int q = 0; q < 6; q++) gg[q] = ld_ll(&g_g[(rb * 24 + 6 * (f - 6) + q) * 32 + ln]);
#pragma unroll
        for (int q = 0; q < 6; q++) ll_chk(bad, gg[q].x, gg[q].z, par);
      } while (__any_sync(0xffffffffu, bad & 1) && ++tries < (1 << 20));
      STAMPW(0, 14);
      wg_wait<0>();
      c.release_prev();
      fence_regs<48>(B);
#pragma unroll
      for (int q = 0; q < 6; q++)
        stout(cb + 16 * q, make_uint4(pack_bf16(B[8 * q], B[8 * q + 1]), pack_bf16(B[8 * q + 2], B[8 * q + 3]), pack_bf16(B[8 * q + 4], B[8 * q + 5]), pack_bf16(B[8 * q + 6], B[8 * q + 7])), gg[q], &xx[4 * q]);
    } else {
      wg_wait<0>();
      c.release_prev();
      fence_regs<96>(B);
      part_groups<0, 12>(B, g_part + ((rb * 8 + f) * 36 + 24) * 32 + ln, par);
      hint_signal(&g_f_rb[rb * 8 + 2]);
      STAMPW(0, 12);
      uint32_t xx[16], bb[4];
#pragma unroll
      for (int j = 0; j < 4; j++) ldx(&xx[4 * j], 192 + 192 * (j >> 1) + 32 * f + 16 * (j & 1));
#pragma unroll
      for (int j = 0; j < 4; j++) bb[j] = __ldg(reinterpret_cast<const uint32_t*>(P.b2 + 384 + 32 * f + 8 * j + 2 * (ln & 3)));
      uint4 sv[4], gg[2];
      int tries = 0;
      uint32_t bad;
#pragma unroll 1
      do {
        bad = 0;
#pragma unroll
        for (int j = 0; j < 4; j++) sv[j] = ld_ll(&g_s[(rb * 24 + 12 * (j >> 1) + 2 * f + (j & 1)) * 32 + ln]);
#pragma unroll
        for (int j = 0; j < 2; j++) gg[j] = ld_ll(&g_g[(rb * 24 + 12 + 2 * f + j) * 32 + ln]);
#pragma unroll
        for (int j = 0; j < 4; j++) ll_chk(bad, sv[j].x, sv[j].z, par);
#pragma unroll
        for (int j = 0; j < 2; j++) ll_chk(bad, gg[j].x, gg[j].z, par);
      } while (__any_sync(0xffffffffu, bad & 1) && ++tries < (1 << 20));
#pragma unroll
      for (int j = 0; j < 2; j++) stout(192 + 32 * f + 16 * j, sv[j], gg[j], &xx[4 * j]);
      STAMPW(0, 13);
      if (ln == 0) hint_wait(&g_f_rb[rb * 8 + 2], 8u * ep, 20);
      __syncwarp();
      STAMPW(0, 14);
      uint4 p[2][8];
      tries = 0;
#pragma unroll 1
      do {
        bad = 0;
#pragma unroll
        for (int j = 0; j < 2; j++)
#pragma unroll
          for (int k = 0; k < 8; k++) p[j][k] = ld_ll(&g_part[((rb * 8 + k) * 36 + 24 + 2 * f + j) * 32 + ln]);
#pragma unroll
        for (int j = 0; j < 2; j++)
#pragma unroll
          for (int k = 0; k < 8; k++) ll_chk(bad, p[j][k].x, p[j][k].z, par);
      } while (__any_sync(0xffffffffu, bad & 1) && ++tries < (1 << 20));
#pragma unroll
      for (int j = 0; j < 2; j++) {
        stout(384 + 32 * f + 16 * j, sv[2 + j], gate_vec(p[j], bb[2 * j], bb[2 * j + 1]), &xx[8 + 4 * j]);
      }
    }
    STAMPW(0, 15);
    cluster_arrive_relaxed();
    cluster_wait();
    STAMPW(0, 16);
    if (tid == 0) g_epoch[blockIdx.x] = ep;
  }
}

typedef CUresult (*EncFn)(CUtensorMap*, CUtensorMapDataType, cuuint32_t, void*, const cuuint64_t*, const cuuint64_t*, const cuuint32_t*, const cuuint32_t*,
                          CUtensorMapInterleave, CUtensorMapSwizzle, CUtensorMapL2promotion, CUtensorMapFloatOOBfill);

void make_map(EncFn enc, CUtensorMap* tm, const void* ptr, int rows, int cols, int box_rows, bool sw64 = false) {
  cuuint64_t gd[2] = {(cuuint64_t)cols, (cuuint64_t)rows};
  cuuint64_t gs[1] = {(cuuint64_t)cols * 2};
  cuuint32_t bx[2] = {sw64 ? 32u : 64u, (cuuint32_t)box_rows};
  cuuint32_t es[2] = {1, 1};
  enc(tm, CU_TENSOR_MAP_DATA_TYPE_BFLOAT16, 2, const_cast<void*>(ptr), gd, gs, bx, es, CU_TENSOR_MAP_INTERLEAVE_NONE, sw64 ? CU_TENSOR_MAP_SWIZZLE_64B : CU_TENSOR_MAP_SWIZZLE_128B,
      CU_TENSOR_MAP_L2_PROMOTION_L2_256B, CU_TENSOR_MAP_FLOAT_OOB_FILL_NONE);
}

}

extern "C" void kernel_launch(void* const* d_in, const int* in_sizes, int n_in, void* d_out, int out_size) {
  (void)in_sizes; (void)n_in; (void)out_size;
  static EncFn enc = nullptr;
  static void *a_ptr = nullptr, *m_ptr = nullptr;
  if (!enc) {
    void* fn = nullptr; cudaDriverEntryPointQueryResult q;
    cudaGetDriverEntryPoint("cuTensorMapEncodeTiled", &fn, cudaEnableDefault, &q);
    enc = (EncFn)fn;
    cudaFuncSetAttribute(fused_kernel, cudaFuncAttributeMaxDynamicSharedMemorySize, SMEM_BYTES);
    cudaGetSymbolAddress(&a_ptr, g_a);
    cudaGetSymbolAddress(&m_ptr, g_m);
  }
  Params P;
  P.x = (const __nv_bfloat16*)d_in[0];
  P.wqkv = (const __nv_bfloat16*)d_in[1];
  P.wo = (const __nv_bfloat16*)d_in[2];
  P.w1 = (const __nv_bfloat16*)d_in[4];
  P.b1 = (const __nv_bfloat16*)d_in[5];
  P.w2 = (const __nv_bfloat16*)d_in[6];
  P.b2 = (const __nv_bfloat16*)d_in[7];
  P.out = (__nv_bfloat16*)d_out;
  make_map(enc, &P.tm_wqkv, P.wqkv, D_, Q3_, 32);
  make_map(enc, &P.tm_w1, P.w1, D_, F_, 32);
  make_map(enc, &P.tm_w2, P.w2, F_, D_, 32);
  make_map(enc, &P.tm_m, m_ptr, D_, D_, 32);
  make_map(enc, &P.tm_wqkv64, P.wqkv, D_, Q3_, 64, true);
  make_map(enc, &P.tm_m64, m_ptr, D_, D_, 64, true);
  make_map(enc, &P.tm_a, a_ptr, S_, D_, 128);
  fused_kernel<<<NCTAS, NTHREADS, SMEM_BYTES, cudaStreamPerThread>>>(P);
}
```

```cpp
#include <cuda_runtime.h>
#include <cuda.h>
#include <cuda_bf16.h>
#include <stdint.h>

namespace {

constexpr int S_ = 2048, D_ = 576, F_ = 4608, Q3_ = 1728;
constexpr int NSTAGE = 6, STAGE_BYTES = 12288;
constexpr int SM_A = 0, SM_B = 147456, SM_BIAS = SM_B + NSTAGE * STAGE_BYTES, SM_RSTD = SM_BIAS + 2304, SM_BAR = SM_RSTD + 512;
constexpr int SMEM_BYTES = SM_BAR + 320;
constexpr int NTHREADS = 384;
constexpr int NCTAS = 132;

__device__ uint4 g_qkvf[(128 * 108 + 1) * 32];
__device__ __align__(1024) __nv_bfloat16 g_a[S_ * D_];
__device__ __align__(1024) __nv_bfloat16 g_m[D_ * D_];
__device__ uint4 g_kvp[32 * 5 * 32 * 32];
__device__ uint4 g_z[32 * 2 * 4];
__device__ uint4 g_part[128 * 8 * 36 * 32];
__device__ uint4 g_s[128 * 24 * 32];
__device__ uint4 g_g[128 * 12 * 32];
__device__ uint4 g_hsp[128 * 12 * 256];
__device__ uint32_t g_f_qkv[16 * 8];
__device__ uint32_t g_f_kvp[32];
__device__ uint32_t g_f_z[32];
__device__ uint32_t g_f_a[16];
__device__ uint32_t g_f_m[1];
__device__ uint32_t g_f_rb[128 * 8];
__device__ uint2 g_stat[S_];
__device__ uint32_t g_epoch[NCTAS];

#define STAMP(i)
#define STAMPW(w, i)
#define WSTAMP(i)
__device__ __forceinline__ uint32_t smem_u32(const void* p) { return (uint32_t)__cvta_generic_to_shared(p); }
__device__ __forceinline__ void mbar_init(uint32_t a, int c) { asm volatile("mbarrier.init.shared::cta.b64 [%0], %1;" ::"r"(a), "r"(c)); }
__device__ __forceinline__ void mbar_expect(uint32_t a, uint32_t b) { asm volatile("mbarrier.arrive.expect_tx.shared::cta.b64 _, [%0], %1;" ::"r"(a), "r"(b) : "memory"); }
__device__ __forceinline__ void mbar_arrive(uint32_t a) { asm volatile("mbarrier.arrive.shared::cta.b64 _, [%0];" ::"r"(a) : "memory"); }
__device__ __forceinline__ void mbar_arrive_cl(uint32_t a) { asm volatile("mbarrier.arrive.shared::cluster.b64 _, [%0];" ::"r"(a) : "memory"); }
__device__ __forceinline__ uint32_t mapa(uint32_t a, uint32_t cta) { uint32_t r; asm volatile("mapa.shared::cluster.u32 %0, %1, %2;" : "=r"(r) : "r"(a), "r"(cta)); return r; }
__device__ __forceinline__ void mbar_wait(uint32_t a, uint32_t ph) {
  uint32_t ok; int it = 0;
#pragma unroll 1
  do {
    asm volatile("{.reg .pred p; mbarrier.try_wait.parity.shared::cta.b64 p, [%1], %2; selp.u32 %0,1,0,p;}" : "=r"(ok) : "r"(a), "r"(ph) : "memory");
  } while (!ok && ++it < (1 << 18));
}
__device__ __forceinline__ void tma2d(uint32_t dst, const CUtensorMap* m, int c0, int c1, uint32_t bar) {
  asm volatile("cp.async.bulk.tensor.2d.shared::cluster.global.mbarrier::complete_tx::bytes [%0], [%1, {%3,%4}], [%2];" ::"r"(dst), "l"(m), "r"(bar), "r"(c0), "r"(c1) : "memory");
}
__device__ __forceinline__ void tma2d_mc(uint32_t dst, const CUtensorMap* m, int c0, int c1, uint32_t bar) {
  asm volatile("cp.async.bulk.tensor.2d.shared::cluster.global.mbarrier::complete_tx::bytes.multicast::cluster [%0], [%1, {%3,%4}], [%2], %5;" ::"r"(dst), "l"(m), "r"(bar), "r"(c0), "r"(c1), "h"((uint16_t)3) : "memory");
}
__device__ __forceinline__ void cluster_arrive_relaxed() { asm volatile("barrier.cluster.arrive.relaxed.aligned;" ::: "memory"); }
__device__ __forceinline__ void cluster_wait() { asm volatile("barrier.cluster.wait.acquire.aligned;" ::: "memory"); }
__device__ __forceinline__ void wg_fence() { asm volatile("wgmma.fence.sync.aligned;" ::: "memory"); }
__device__ __forceinline__ void wg_commit() { asm volatile("wgmma.commit_group.sync.aligned;" ::: "memory"); }
template <int n> __device__ __forceinline__ void wg_wait() { asm volatile("wgmma.wait_group.sync.aligned %0;" ::"n"(n) : "memory"); }
__device__ __forceinline__ uint32_t ld_acquire(const uint32_t* p) { uint32_t v; asm volatile("ld.acquire.gpu.global.u32 %0, [%1];" : "=r"(v) : "l"(p) : "memory"); return v; }
__device__ __forceinline__ void flag_wait(const uint32_t* p, uint32_t target) {
  int it = 0;
#pragma unroll 1
  while ((int)(ld_acquire(p) - target) < 0 && ++it < (1 << 20)) __nanosleep(300);
}
__device__ __forceinline__ void hint_signal(uint32_t* p) {
  if ((threadIdx.x & 31) == 0) asm volatile("red.relaxed.gpu.global.add.u32 [%0], 1;" ::"l"(p) : "memory");
}
__device__ __forceinline__ void hint_wait(const uint32_t* p, uint32_t target, uint32_t ns = 400) {
  int it = 0; uint32_t v;
#pragma unroll 1
  do { asm volatile("ld.relaxed.gpu.global.u32 %0, [%1];" : "=r"(v) : "l"(p) : "memory"); if ((int)(v - target) >= 0) break; __nanosleep(ns); } while (++it < (1 << 20));
}
__device__ __forceinline__ uint32_t tag(uint32_t x, uint32_t par) { uint32_t r; asm("lop3.b32 %0, %1, 0xfffffffe, %2, 0xea;" : "=r"(r) : "r"(x), "r"(par)); return r; }
__device__ __forceinline__ void st_ll(uint4* p, uint32_t x, uint32_t y, uint32_t z, uint32_t w, uint32_t par) {
  asm volatile("{.reg .b64 a, b; mov.b64 a, {%1,%2}; mov.b64 b, {%3,%4}; st.relaxed.gpu.global.v2.b64 [%0], {a, b};}"
               ::"l"(p), "r"(tag(x, par)), "r"(y), "r"(tag(z, par)), "r"(w) : "memory");
}
__device__ __forceinline__ uint4 ld_ll(const uint4* p) {
  uint4 v;
  asm volatile("{.reg .b64 a, b; ld.relaxed.gpu.global.v2.b64 {a, b}, [%4]; mov.b64 {%0,%1}, a; mov.b64 {%2,%3}, b;}"
               : "=r"(v.x), "=r"(v.y), "=r"(v.z), "=r"(v.w) : "l"(p) : "memory");
  return v;
}
__device__ __forceinline__ uint2 ld_ll64(const uint32_t* p) {
  uint2 v;
  asm volatile("{.reg .b64 a; ld.relaxed.gpu.global.b64 a, [%2]; mov.b64 {%0,%1}, a;}" : "=r"(v.x), "=r"(v.y) : "l"(p) : "memory");
  return v;
}
__device__ __forceinline__ void ll_chk(uint32_t& bad, uint32_t a, uint32_t b, uint32_t par) {
  uint32_t u; asm("lop3.b32 %0, %1, %2, %3, 0x7e;" : "=r"(u) : "r"(a), "r"(b), "r"(par));
  asm("or.b32 %0, %0, %1;" : "+r"(bad) : "r"(u));
}
__device__ __forceinline__ uint32_t hadd2(uint32_t a, uint32_t b) { uint32_t d; asm("add.rn.bf16x2 %0, %1, %2;" : "=r"(d) : "r"(a), "r"(b)); return d; }
__device__ __forceinline__ uint32_t hfma2(uint32_t a, uint32_t b, uint32_t c) { uint32_t d; asm("fma.rn.bf16x2 %0, %1, %2, %3;" : "=r"(d) : "r"(a), "r"(b), "r"(c)); return d; }
__device__ __forceinline__ uint32_t pack_bf16(float lo, float hi) { uint32_t r; asm("cvt.rn.bf16x2.f32 %0, %1, %2;" : "=r"(r) : "f"(hi), "f"(lo)); return r; }
__device__ __forceinline__ float bf_lo(uint32_t v) { return __uint_as_float(v << 16); }
__device__ __forceinline__ float bf_hi(uint32_t v) { return __uint_as_float(v & 0xffff0000u); }
__device__ __forceinline__ uint32_t movmat(uint32_t a) { uint32_t d; asm volatile("movmatrix.sync.aligned.m8n8.trans.b16 %0, %1;" : "=r"(d) : "r"(a)); return d; }
__device__ __forceinline__ void mma16816(float* c, uint32_t a0, uint32_t a1, uint32_t a2, uint32_t a3, uint32_t b0, uint32_t b1) {
  asm volatile("mma.sync.aligned.m16n8k16.row.col.f32.bf16.bf16.f32 {%0,%1,%2,%3}, {%4,%5,%6,%7}, {%8,%9}, {%0,%1,%2,%3};"
               : "+f"(c[0]), "+f"(c[1]), "+f"(c[2]), "+f"(c[3]) : "r"(a0), "r"(a1), "r"(a2), "r"(a3), "r"(b0), "r"(b1));
}
__device__ __forceinline__ uint4 ldcg128(const void* p) { uint4 v; asm volatile("ld.global.cg.v4.u32 {%0,%1,%2,%3}, [%4];" : "=r"(v.x), "=r"(v.y), "=r"(v.z), "=r"(v.w) : "l"(p) : "memory"); return v; }

template <int N> __device__ __forceinline__ void wgmma_ss(float* d, uint64_t da, uint64_t db, int sc);
template <int N> __device__ __forceinline__ void wgmma_rs(float* d, const uint32_t* a, uint64_t db, int sc);
template <> __device__ __forceinline__ void wgmma_ss<96>(float* d, uint64_t da, uint64_t db, int sc) {
  asm volatile("{.reg .pred p; setp.ne.b32 p, %50, 0; wgmma.mma_async.sync.aligned.m64n96k16.f32.bf16.bf16 {%0, %1, %2, %3, %4, %5, %6, %7, %8, %9, %10, %11, %12, %13, %14, %15, %16, %17, %18, %19, %20, %21, %22, %23, %24, %25, %26, %27, %28, %29, %30, %31, %32, %33, %34, %35, %36, %37, %38, %39, %40, %41, %42, %43, %44, %45, %46, %47}, %48, %49, p, 1, 1, 0, 1;}"
   : "+f"(d[0]), "+f"(d[1]), "+f"(d[2]), "+f"(d[3]), "+f"(d[4]), "+f"(d[5]), "+f"(d[6]), "+f"(d[7]), "+f"(d[8]), "+f"(d[9]), "+f"(d[10]), "+f"(d[11]), "+f"(d[12]), "+f"(d[13]), "+f"(d[14]), "+f"(d[15]), "+f"(d[16]), "+f"(d[17]), "+f"(d[18]), "+f"(d[19]), "+f"(d[20]), "+f"(d[21]), "+f"(d[22]), "+f"(d[23]), "+f"(d[24]), "+f"(d[25]), "+f"(d[26]), "+f"(d[27]), "+f"(d[28]), "+f"(d[29]), "+f"(d[30]), "+f"(d[31]), "+f"(d[32]), "+f"(d[33]), "+f"(d[34]), "+f"(d[35]), "+f"(d[36]), "+f"(d[37]), "+f"(d[38]), "+f"(d[39]), "+f"(d[40]), "+f"(d[41]), "+f"(d[42]), "+f"(d[43]), "+f"(d[44]), "+f"(d[45]), "+f"(d[46]), "+f"(d[47]) : "l"(da), "l"(db), "r"(sc));
}
template <> __device__ __forceinline__ void wgmma_ss<192>(float* d, uint64_t da, uint64_t db, int sc) {
  asm volatile("{.reg .pred p; setp.ne.b32 p, %98, 0; wgmma.mma_async.sync.aligned.m64n192k16.f32.bf16.bf16 {%0, %1, %2, %3, %4, %5, %6, %7, %8, %9, %10, %11, %12, %13, %14, %15, %16, %17, %18, %19, %20, %21, %22, %23, %24, %25, %26, %27, %28, %29, %30, %31, %32, %33, %34, %35, %36, %37, %38, %39, %40, %41, %42, %43, %44, %45, %46, %47, %48, %49, %50, %51, %52, %53, %54, %55, %56, %57, %58, %59, %60, %61, %62, %63, %64, %65, %66, %67, %68, %69, %70, %71, %72, %73, %74, %75, %76, %77, %78, %79, %80, %81, %82, %83, %84, %85, %86, %87, %88, %89, %90, %91, %92, %93, %94, %95}, %96, %97, p, 1, 1, 0, 1;}"
   : "+f"(d[0]), "+f"(d[1]), "+f"(d[2]), "+f"(d[3]), "+f"(d[4]), "+f"(d[5]), "+f"(d[6]), "+f"(d[7]), "+f"(d[8]), "+f"(d[9]), "+f"(d[10]), "+f"(d[11]), "+f"(d[12]), "+f"(d[13]), "+f"(d[14]), "+f"(d[15]), "+f"(d[16]), "+f"(d[17]), "+f"(d[18]), "+f"(d[19]), "+f"(d[20]), "+f"(d[21]), "+f"(d[22]), "+f"(d[23]), "+f"(d[24]), "+f"(d[25]), "+f"(d[26]), "+f"(d[27]), "+f"(d[28]), "+f"(d[29]), "+f"(d[30]), "+f"(d[31]), "+f"(d[32]), "+f"(d[33]), "+f"(d[34]), "+f"(d[35]), "+f"(d[36]), "+f"(d[37]), "+f"(d[38]), "+f"(d[39]), "+f"(d[40]), "+f"(d[41]), "+f"(d[42]), "+f"(d[43]), "+f"(d[44]), "+f"(d[45]), "+f"(d[46]), "+f"(d[47]), "+f"(d[48]), "+f"(d[49]), "+f"(d[50]), "+f"(d[51]), "+f"(d[52]), "+f"(d[53]), "+f"(d[54]), "+f"(d[55]), "+f"(d[56]), "+f"(d[57]), "+f"(d[58]), "+f"(d[59]), "+f"(d[60]), "+f"(d[61]), "+f"(d[62]), "+f"(d[63]), "+f"(d[64]), "+f"(d[65]), "+f"(d[66]), "+f"(d[67]), "+f"(d[68]), "+f"(d[69]), "+f"(d[70]), "+f"(d[71]), "+f"(d[72]), "+f"(d[73]), "+f"(d[74]), "+f"(d[75]), "+f"(d[76]), "+f"(d[77]), "+f"(d[78]), "+f"(d[79]), "+f"(d[80]), "+f"(d[81]), "+f"(d[82]), "+f"(d[83]), "+f"(d[84]), "+f"(d[85]), "+f"(d[86]), "+f"(d[87]), "+f"(d[88]), "+f"(d[89]), "+f"(d[90]), "+f"(d[91]), "+f"(d[92]), "+f"(d[93]), "+f"(d[94]), "+f"(d[95]) : "l"(da), "l"(db), "r"(sc));
}

__device__ __forceinline__ uint64_t desc64(uint32_t lo, uint32_t hi) { uint64_t d; asm("mov.b64 %0, {%1, %2};" : "=l"(d) : "r"(lo), "r"(hi)); return d; }
constexpr uint32_t DESC_HI = (1024u >> 4) | (1u << 30);
constexpr uint32_t DESC_HI64 = (512u >> 4) | (2u << 30);
template <int n> __device__ __forceinline__ void fence_regs(float* a) {
#pragma unroll
  for (int i = 0; i < n; i++) asm volatile("" : "+f"(a[i])::"memory");
}

struct Ctx {
  uint32_t full;
  uint32_t emb;
  bool sig;
  uint32_t stage, phase, prev;
  uint32_t dB, dA;
  __device__ __forceinline__ void release_prev() { if (sig && prev != ~0u) mbar_arrive_cl(emb + prev); }
  __device__ __forceinline__ void wait_full() {
    mbar_wait(full + 8 * stage, phase);
    wg_fence();
  }
};

__device__ __forceinline__ void issue192(float* acc, Ctx& c, int s, bool first = false) {
  c.wait_full();
  const uint32_t db = c.dB + c.stage * (STAGE_BYTES >> 4);
  const uint32_t da = c.dA + (s >> 1) * 1024 + (s & 1) * 4;
  wgmma_ss<192>(acc, desc64(da, DESC_HI), desc64(db, DESC_HI), first ? 0 : 1);
  wgmma_ss<192>(acc, desc64(da + 2, DESC_HI), desc64(db + 128, DESC_HI), 1);
  wg_commit();
}
__device__ __forceinline__ void issue96(float* acc, Ctx& c, int s, bool first) {
  c.wait_full();
  const uint32_t db = c.dB + c.stage * (STAGE_BYTES >> 4);
  const uint32_t da = c.dA + s * 1024;
  if (first) { wgmma_ss<192>(acc, desc64(da, DESC_HI), desc64(db, DESC_HI64), 0); wg_fence(); }
#pragma unroll
  for (int kk = first ? 1 : 0; kk < 4; kk++) wgmma_ss<96>(acc, desc64(da + 2 * kk, DESC_HI), desc64(db + 64 * kk, DESC_HI64), 1);
  wg_commit();
}
__device__ __forceinline__ void retire(Ctx& c) {
  wg_wait<1>();
  c.release_prev();
  c.prev = 8 * c.stage;
  if (++c.stage == NSTAGE) { c.stage = 0; c.phase ^= 1; }
}
constexpr float GK = 0.32920349f;
__device__ __forceinline__ uint32_t gelu_pair(uint32_t y) {
  uint32_t u, th;
  asm("mul.rn.bf16x2 %0, %1, %2;" : "=r"(u) : "r"(hfma2(y, y, 0x401b401bu)), "r"(y));
  asm("tanh.approx.bf16x2 %0, %1;" : "=r"(th) : "r"(u));
  return hfma2(y, th, y);
}
__device__ __forceinline__ uint4 gelu_group(const uint32_t* a) { return make_uint4(gelu_pair(a[0]), gelu_pair(a[1]), gelu_pair(a[2]), gelu_pair(a[3])); }
__device__ __forceinline__ void lds_bias(float2* b, uint32_t addr) {
#pragma unroll
  for (int j = 0; j < 4; j++) asm volatile("ld.shared.v2.f32 {%0,%1}, [%2];" : "=f"(b[j].x), "=f"(b[j].y) : "r"(addr + 32 * j));
}
__device__ __forceinline__ int opaque(int v) { asm volatile("" : "+r"(v)); return v; }
__device__ __forceinline__ void stsm4(uint32_t addr, uint4 r) {
  asm volatile("stmatrix.sync.aligned.m8n8.x4.shared.b16 [%0], {%1,%2,%3,%4};" ::"r"(addr), "r"(r.x), "r"(r.y), "r"(r.z), "r"(r.w) : "memory");
}
__device__ __forceinline__ float ex2f(float x) { float r; asm("ex2.approx.ftz.f32 %0, %1;" : "=f"(r) : "f"(x)); return r; }
__device__ __forceinline__ uint32_t phi_pack(uint32_t tp, float a0, float a1) {
  uint32_t x, y;
  asm("max.bf16x2 %0, %1, %2;" : "=r"(x) : "r"(tp), "r"(0x35863586u));
  asm("min.bf16x2 %0, %1, %2;" : "=r"(y) : "r"(pack_bf16(ex2f(a0), ex2f(a1))), "r"(0x3f803f80u));
  return hadd2(x, y);
}
template <int q0, int q1>
__device__ __forceinline__ void part_groups(const float* a, uint4* p, uint32_t par) {
#pragma unroll
  for (int q = q0; q < q1; q++)
    st_ll(p + q * 32, pack_bf16(a[8 * q], a[8 * q + 1]), pack_bf16(a[8 * q + 2], a[8 * q + 3]), pack_bf16(a[8 * q + 4], a[8 * q + 5]), pack_bf16(a[8 * q + 6], a[8 * q + 7]), par);
}
__device__ __forceinline__ float silu(float y) { return __fdividef(y, 1.f + ex2f(y * -1.4426950408889634f)); }
__device__ __forceinline__ uint32_t gate_word(uint32_t w0, uint32_t w1, uint32_t w2, uint32_t w3, uint32_t w4, uint32_t w5, uint32_t w6, uint32_t w7, uint32_t bb) {
  const uint32_t u0 = hadd2(hadd2(w0, w1), hadd2(w2, w3)), u1 = hadd2(hadd2(w4, w5), hadd2(w6, w7));
  return pack_bf16(silu(fmaf(bf_lo(u0) + bf_lo(u1), 0.5f / GK, bf_lo(bb))), silu(fmaf(bf_hi(u0) + bf_hi(u1), 0.5f / GK, bf_hi(bb))));
}
__device__ __forceinline__ uint4 gate_vec(const uint4* p, uint32_t b0, uint32_t b1) {
  return make_uint4(gate_word(p[0].x, p[1].x, p[2].x, p[3].x, p[4].x, p[5].x, p[6].x, p[7].x, b0), gate_word(p[0].y, p[1].y, p[2].y, p[3].y, p[4].y, p[5].y, p[6].y, p[7].y, b0),
                    gate_word(p[0].z, p[1].z, p[2].z, p[3].z, p[4].z, p[5].z, p[6].z, p[7].z, b1), gate_word(p[0].w, p[1].w, p[2].w, p[3].w, p[4].w, p[5].w, p[6].w, p[7].w, b1));
}
__device__ __forceinline__ int coloff(int c) { return (c >> 4) * 128 + ((c & 7) >> 1) * 4 + ((c >> 3) & 1) * 2; }

__device__ __forceinline__ void d1_load(uint32_t* W, int rb0, int head, int ln) {
  const uint32_t* qf = reinterpret_cast<const uint32_t*>(g_qkvf) + rb0 * 108 * 128 + (ln >> 2) * 16;
#pragma unroll
  for (int b = 0; b < 3; b++) {
    const uint32_t* p = qf + coloff(576 + head * 18 + 8 * b + 2 * (ln & 3));
#pragma unroll
    for (int j = 0; j < 4; j++) {
      const uint2 kk = ld_ll64(p + j * 108 * 128), vv = ld_ll64(p + j * 108 * 128 + 36 * 128);
      W[6 * j + 2 * b] = kk.x; W[6 * j + 2 * b + 1] = kk.y; W[24 + 6 * j + 2 * b] = vv.x; W[24 + 6 * j + 2 * b + 1] = vv.y;
    }
  }
}
__device__ __forceinline__ bool d1_bad(const uint32_t* W, int t, uint32_t par) {
  uint32_t bad = 0, bad2 = 0;
#pragma unroll
  for (int q = 0; q < 12; q++) ll_chk((q % 3) != 2 ? bad : bad2, W[2 * q], W[24 + 2 * q], par);
  return __any_sync(0xffffffffu, (bad | (t == 0 ? bad2 : 0u)) & 1);
}
__device__ __forceinline__ void d1_mov(uint32_t* W, int j, int t) {
  if (t != 0) { W[6 * j + 4] = W[6 * j + 5] = 0u; W[24 + 6 * j + 4] = W[24 + 6 * j + 5] = (t == 1 ? 0x00003f80u : 0u); }
#pragma unroll
  for (int q = 0; q < 6; q++) { W[6 * j + q] = movmat(W[6 * j + q]); W[24 + 6 * j + q] = movmat(W[24 + 6 * j + q]); }
}
__device__ __forceinline__ void d1_mma_store(const uint32_t* W, int head, int blk, int ln, uint32_t par) {
  float c0[3][4], c1[3][4];
#pragma unroll
  for (int j = 0; j < 3; j++) { c0[j][0] = c0[j][1] = c0[j][2] = c0[j][3] = 0.f; c1[j][0] = c1[j][1] = c1[j][2] = c1[j][3] = 0.f; }
#pragma unroll
  for (int ks = 0; ks < 4; ks++)
#pragma unroll
    for (int j = 0; j < 3; j++) {
      mma16816(c0[j], W[24 + 6 * ks], W[24 + 6 * ks + 2], W[24 + 6 * ks + 1], W[24 + 6 * ks + 3], W[6 * ks + 2 * j], W[6 * ks + 2 * j + 1]);
      mma16816(c1[j], W[24 + 6 * ks + 4], 0u, W[24 + 6 * ks + 5], 0u, W[6 * ks + 2 * j], W[6 * ks + 2 * j + 1]);
    }
  uint4* dst = &g_kvp[(head * 160 + blk) * 32 + ln];
#pragma unroll
  for (int j = 0; j < 3; j++) st_ll(dst + j * 1024, __float_as_uint(c0[j][0]), __float_as_uint(c0[j][1]), __float_as_uint(c0[j][2]), __float_as_uint(c0[j][3]), par);
  st_ll(dst + 3072, __float_as_uint(c1[0][0]), __float_as_uint(c1[0][1]), __float_as_uint(c1[1][0]), __float_as_uint(c1[1][1]), par);
  st_ll(dst + 4096, __float_as_uint(c1[2][0]), __float_as_uint(c1[2][1]), 0u, 0u, par);
  hint_signal(&g_f_kvp[head]);
}

struct Params {
  CUtensorMap tm_wqkv, tm_w1, tm_w2, tm_m, tm_wqkv64, tm_m64, tm_a;
  const __nv_bfloat16 *x, *b1, *b2, *wqkv, *w1, *w2, *wo;
  __nv_bfloat16* out;
};

__global__ void __cluster_dims__(2, 1, 1) __launch_bounds__(NTHREADS, 1) fused_kernel(const __grid_constant__ Params P) {
  extern __shared__ __align__(1024) uint8_t smem[];
  const uint32_t sbase = smem_u32(smem);
  const int tid = threadIdx.x, lane = tid & 31;
  const int warp = __shfl_sync(0xffffffffu, tid >> 5, 0);
  const int g = lane >> 2, t = lane & 3;
  const uint32_t ep = __shfl_sync(0xffffffffu, g_epoch[blockIdx.x], 0) + 1;
  const uint32_t par = ep & 1;
  STAMPW(0, 0);

  if (blockIdx.x >= 128) {
    const int a = blockIdx.x - 128;
    constexpr int WP = 1168, SM_T = 152 * WP, SM_HB = SM_T + 8 * 32 * 80;
    if (tid == 0) {
      mbar_init(sbase + SM_HB, 1);
      asm volatile("fence.mbarrier_init.release.cluster;" ::: "memory");
      mbar_expect(sbase + SM_HB, 144 * 1152);
    }
    for (int i = tid; i < (8 * WP + 8 * 32 * 80) / 4; i += NTHREADS) reinterpret_cast<uint32_t*>(smem + 144 * WP)[i] = 0u;
    __syncthreads();
    __nanosleep(1500);
    if (tid < 144)
      asm volatile("cp.async.bulk.shared::cluster.global.mbarrier::complete_tx::bytes [%0], [%1], %2, [%3];" ::"r"(sbase + tid * WP), "l"(P.wo + (a * 144 + tid) * D_), "r"(1152), "r"(sbase + SM_HB) : "memory");
    if (warp >= 8 && lane == 0) {
      const int id = a * 4 + (warp - 8);
      constexpr uint32_t CH = 9216 * 2;
#pragma unroll 1
      for (int i = id; i < 576; i += 16) {
        const char* p = i < 288 ? (const char*)P.w1 + (size_t)i * CH : (const char*)P.w2 + (size_t)(i - 288) * CH;
        asm volatile("cp.async.bulk.prefetch.L2.global [%0], %1;" ::"l"(p), "r"(CH) : "memory");
      }
    }
    __syncwarp();
    if (lane < 8) hint_wait(&g_f_kvp[a * 8 + lane], 32 * ep, 50);
    __syncwarp();
    STAMPW(0, 1);
#pragma unroll 1
    for (int u = warp; u < 40; u += 12) {
      const int hh = u & 7, w = 4 - (u >> 3), head = a * 8 + hh;
      uint4 v[32];
      int tries = 0;
      uint32_t bad;
#pragma unroll 1
      do {
        bad = 0;
#pragma unroll
        for (int j = 0; j < 32; j++) v[j] = ld_ll(&g_kvp[((head * 5 + w) * 32 + j) * 32 + lane]);
#pragma unroll
        for (int j = 0; j < 32; j++) ll_chk(bad, v[j].x, v[j].z, par);
      } while (__any_sync(0xffffffffu, bad & 1) && ++tries < (1 << 20));
      float s0 = 0.f, s1 = 0.f, s2 = 0.f, s3 = 0.f;
#pragma unroll
      for (int j = 0; j < 32; j++) { s0 += __uint_as_float(v[j].x); s1 += __uint_as_float(v[j].y); s2 += __uint_as_float(v[j].z); s3 += __uint_as_float(v[j].w); }
      if (w >= 3) {
        if (g == 2) st_ll(&g_z[(head * 2 + w - 3) * 4 + t], __float_as_uint(s0), __float_as_uint(s1), __float_as_uint(s2), __float_as_uint(s3), par);
        __syncwarp();
        hint_signal(&g_f_z[head]);
      }
      const int e0 = w < 3 ? g : 16 + g, e1 = w < 3 ? g + 8 : 16 + g, d0 = (w < 3 ? 8 * w : (w == 3 ? 0 : 16)) + 2 * t, d1 = w < 3 ? d0 : d0 + 8;
      __nv_bfloat16* T = reinterpret_cast<__nv_bfloat16*>(smem + SM_T) + hh * 32 * 40;
      if (e0 < 18) {
        T[d0 * 40 + e0] = __float2bfloat16(s0); T[(d0 + 1) * 40 + e0] = __float2bfloat16(s1);
        T[d1 * 40 + e1] = __float2bfloat16(s2); T[(d1 + 1) * 40 + e1] = __float2bfloat16(s3);
      }
    }
    __syncthreads();
    STAMPW(0, 2);
    mbar_wait(sbase + SM_HB, 0);
#pragma unroll 1
    for (int u = warp; u < 24; u += 12) {
      const int hh = u / 3, c0 = (u % 3) * 192;
      const uint32_t* T = reinterpret_cast<const uint32_t*>(smem + SM_T) + hh * 32 * 20 + g * 20 + t;
      const uint32_t a00 = T[0], a01 = T[160], a02 = T[4], a03 = T[164], a10 = T[8], a11 = T[168], b00 = T[320], b02 = T[324], b10 = T[328];
      const uint32_t rowa = sbase + (hh * 18 + (lane & 15)) * WP + (c0 + (lane >> 4) * 8) * 2, rowb = sbase + (hh * 18 + 16 + (lane & 7)) * WP + (c0 + ((lane >> 3) & 1) * 8) * 2;
#pragma unroll 2
      for (int j = 0; j < 12; j++) {
        uint32_t w0, w1, w2, w3, w4, w5;
        asm volatile("ldmatrix.sync.aligned.m8n8.x4.trans.shared.b16 {%0,%1,%2,%3}, [%4];" : "=r"(w0), "=r"(w1), "=r"(w2), "=r"(w3) : "r"(rowa + j * 32));
        asm volatile("ldmatrix.sync.aligned.m8n8.x2.trans.shared.b16 {%0,%1}, [%2];" : "=r"(w4), "=r"(w5) : "r"(rowb + j * 32));
        float p[4][4];
#pragma unroll
        for (int q = 0; q < 4; q++) p[q][0] = p[q][1] = p[q][2] = p[q][3] = 0.f;
        mma16816(p[0], a00, a01, a02, a03, w0, w1); mma16816(p[1], a00, a01, a02, a03, w2, w3);
        mma16816(p[2], b00, 0u, b02, 0u, w0, w1); mma16816(p[3], b00, 0u, b02, 0u, w2, w3);
        mma16816(p[0], a10, a11, 0u, 0u, w4, 0u); mma16816(p[1], a10, a11, 0u, 0u, w5, 0u);
        mma16816(p[2], b10, 0u, 0u, 0u, w4, 0u); mma16816(p[3], b10, 0u, 0u, 0u, w5, 0u);
        stsm4(rowa + j * 32, make_uint4(pack_bf16(p[0][0], p[0][1]), pack_bf16(p[0][2], p[0][3]), pack_bf16(p[1][0], p[1][1]), pack_bf16(p[1][2], p[1][3])));
        if (g < 2) {
          uint32_t* r = reinterpret_cast<uint32_t*>(smem + (hh * 18 + 16 + g) * WP + (c0 + j * 16 + 2 * t) * 2);
          r[0] = pack_bf16(p[2][0], p[2][1]); r[4] = pack_bf16(p[3][0], p[3][1]);
        }
      }
      asm volatile("fence.proxy.async.shared::cta;" ::: "memory");
      __syncwarp();
      if (lane < 18) {
        asm volatile("cp.async.bulk.global.shared::cta.bulk_group [%0], [%1], %2;" ::"l"(g_m + (a * 144 + hh * 18 + lane) * D_ + c0), "r"(sbase + (hh * 18 + lane) * WP + c0 * 2), "r"(384) : "memory");
        asm volatile("cp.async.bulk.commit_group;" ::: "memory");
      }
    }
    asm volatile("cp.async.bulk.wait_group 0;" ::: "memory");
    asm volatile("fence.proxy.async.global;" ::: "memory");
    __syncwarp();
    if (lane == 0) asm volatile("red.release.gpu.global.add.u32 [%0], 1;" ::"l"(g_f_m) : "memory");
    STAMPW(0, 3);
    __syncthreads();
    if (tid == 0) g_epoch[blockIdx.x] = ep;
    return;
  }

  const int cl = blockIdx.x >> 1, rank = blockIdx.x & 1;
  const int f = cl & 7, m = (cl >> 3) * 2 + rank;
  const int srole = f >= 6 ? 1 : 0;
  const uint32_t bar_full = sbase + SM_BAR, bar_empty = bar_full + 8 * NSTAGE, bar_xfree = bar_empty + 8 * NSTAGE, bar_ofull = bar_xfree + 72,
                 bar_d = bar_ofull + 72;

  if (tid == 0) {
#pragma unroll 1
    for (int i = 0; i < NSTAGE; i++) { mbar_init(bar_full + 8 * i, 1); mbar_init(bar_empty + 8 * i, 4); }
#pragma unroll 1
    for (int i = 0; i < 9; i++) { mbar_init(bar_xfree + 8 * i, 2); mbar_init(bar_ofull + 8 * i, 1); }
    mbar_init(bar_d, 1);
    asm volatile("fence.mbarrier_init.release.cluster;" ::: "memory");
  }
  __syncwarp();
  cluster_arrive_relaxed();

  if (warp >= 8) {
    const int srow = m * 128 + f * 16 + (warp - 8) * 4 + (lane >> 3);
    uint4 xs[9];
#pragma unroll
    for (int kb = 0; kb < 9; kb++) xs[kb] = __ldg(reinterpret_cast<const uint4*>(P.x + srow * D_) + (lane & 7) + kb * 8);
    auto stats = [&]() {
      const uint32_t* w = reinterpret_cast<const uint32_t*>(xs);
      float s0 = 0.f, s1 = 0.f;
#pragma unroll
      for (int i = 0; i < 36; i++) { s0 += bf_lo(w[i]); s1 += bf_hi(w[i]); }
      float sum = s0 + s1;
      sum += __shfl_xor_sync(0xffffffffu, sum, 1); sum += __shfl_xor_sync(0xffffffffu, sum, 2); sum += __shfl_xor_sync(0xffffffffu, sum, 4);
      const float mean = sum * (1.f / 576.f);
      s0 = 0.f; s1 = 0.f;
#pragma unroll
      for (int i = 0; i < 36; i++) { const float a = bf_lo(w[i]) - mean, b = bf_hi(w[i]) - mean; s0 = fmaf(a, a, s0); s1 = fmaf(b, b, s1); }
      float sq = s0 + s1;
      sq += __shfl_xor_sync(0xffffffffu, sq, 1); sq += __shfl_xor_sync(0xffffffffu, sq, 2); sq += __shfl_xor_sync(0xffffffffu, sq, 4);
      const float rstd = rsqrtf(sq * (1.f / 576.f) + 1e-5f);
      if ((lane & 7) == 0)
        asm volatile("{.reg .b64 a; mov.b64 a, {%1,%2}; st.relaxed.gpu.global.b64 [%0], a;}" ::"l"(&g_stat[srow]), "r"((__float_as_uint(rstd) & ~1u) | par), "r"(pack_bf16(-mean, -mean)) : "memory");
    };
    stats();
    asm volatile("setmaxnreg.dec.sync.aligned.u32 40;");
    cluster_wait();
    if (warp == 8) {
      if (lane == 0) {
        uint32_t stage = 0, phase = 1;
        const uint32_t sb = sbase + SM_B;
#pragma unroll 1
        for (int tl = 2 * srole; tl < 8 + 2 * srole; tl++) {
          const CUtensorMap* map = tl == 0 ? &P.tm_wqkv : (tl == 1 ? &P.tm_wqkv64 : (tl < 5 ? &P.tm_w1 : (tl < 8 ? &P.tm_w2 : (tl == 8 ? &P.tm_m : &P.tm_m64))));
          const int col = tl < 2 ? 288 * f + 192 * tl : (tl < 5 ? 576 * f + 192 * (tl - 2) : (tl < 8 ? 192 * (tl - 5) : (tl == 8 ? 192 * (f - 5) : 96 * (f - 6))));
          const bool perm = tl >= 5 && tl < 8;
          const bool z = (tl & 7) == 1;
          if (tl == 8) { flag_wait(g_f_m, 48 * ep); asm volatile("fence.proxy.async.global;" ::: "memory"); }
          const int cs = z ? 32 : 64, rs = z ? 64 : 32, nst = z ? 9 : 18;
#pragma unroll 1
          for (int st = 0; st < nst; st++) {
            int row = st * rs;
            if (perm) row += 576 * f + ((st < 6) ? 192 : (st < 12 ? -192 : 0));
            mbar_wait(bar_empty + 8 * stage, phase);
            mbar_expect(bar_full + 8 * stage, 12288);
            const uint32_t dst = sb + stage * STAGE_BYTES;
            if (((st ^ rank) & 1) == 0) {
              tma2d_mc(dst, map, col, row, bar_full + 8 * stage);
              tma2d_mc(dst + 8192, map, col + 2 * cs, row, bar_full + 8 * stage);
            } else {
              tma2d_mc(dst + 4096, map, col + cs, row, bar_full + 8 * stage);
            }
            if (++stage == NSTAGE) { stage = 0; phase ^= 1; }
          }
        }
      }
      __syncwarp();
    } else {
      const int aw = warp - 9;
      const int hi = f >> 2;
      if (aw == 0) {
        if (lane < 2) hint_wait(&g_f_qkv[m * 8 + 2 + 2 * lane + hi], 16 * ep, 200);
        __syncwarp();
        if (lane == 0) mbar_arrive(bar_d);
        STAMP(20);
      }
      if (lane < 5) hint_wait(lane < 4 ? &g_f_z[4 * f + lane] : &g_f_qkv[m * 8 + hi], lane < 4 ? 2 * ep : 16 * ep);
      __syncwarp();
      STAMPW(9, 22);
#pragma unroll 1
      for (int hh = 0; hh < 4; hh++) {
        const int rb0 = (aw + hh) % 3;
        const uint32_t* qf = reinterpret_cast<const uint32_t*>(g_qkvf) + (m * 8 + rb0) * 108 * 128 + g * 16;
        const int last = rb0 < 2 ? 6 * 108 * 128 : 0;
        uint2 q[3][3];
        uint4 z01; uint2 z2;
        int tries = 0;
        uint32_t bad;
#pragma unroll 1
        do {
          bad = 0;
          z01 = ld_ll(&g_z[(4 * f + hh) * 8 + t]);
          z2 = ld_ll64(reinterpret_cast<const uint32_t*>(&g_z[(4 * f + hh) * 8 + 4 + t]));
#pragma unroll
          for (int b = 0; b < 3; b++) {
            const int o = coloff(72 * f + hh * 18 + 8 * b + 2 * t);
#pragma unroll
            for (int j = 0; j < 3; j++) q[j][b] = ld_ll64(qf + o + (j < 2 ? j * 3 * 108 * 128 : last));
          }
          ll_chk(bad, z01.x, z01.z, par); ll_chk(bad, z2.x, par, par);
#pragma unroll
          for (int j = 0; j < 3; j++) { ll_chk(bad, q[j][0].x, q[j][1].x, par); if (t != 0) q[j][2] = make_uint2(par, 0u); ll_chk(bad, q[j][2].x, par, par); }
        } while (__any_sync(0xffffffffu, bad & 1) && ++tries < (1 << 20));
        float d[6];
#pragma unroll
        for (int j = 0; j < 3; j++) {
          d[2 * j] = bf_lo(q[j][0].x) * __uint_as_float(z01.x) + bf_hi(q[j][0].x) * __uint_as_float(z01.y) + bf_lo(q[j][1].x) * __uint_as_float(z01.z) + bf_hi(q[j][1].x) * __uint_as_float(z01.w) +
                     bf_lo(q[j][2].x) * __uint_as_float(z2.x) + bf_hi(q[j][2].x) * __uint_as_float(z2.y);
          d[2 * j + 1] = bf_lo(q[j][0].y) * __uint_as_float(z01.x) + bf_hi(q[j][0].y) * __uint_as_float(z01.y) + bf_lo(q[j][1].y) * __uint_as_float(z01.z) + bf_hi(q[j][1].y) * __uint_as_float(z01.w) +
                         bf_lo(q[j][2].y) * __uint_as_float(z2.x) + bf_hi(q[j][2].y) * __uint_as_float(z2.y);
        }
#pragma unroll
        for (int j = 0; j < 6; j++) d[j] += __shfl_xor_sync(0xffffffffu, d[j], 1);
#pragma unroll
        for (int j = 0; j < 6; j++) d[j] = __fdividef(1.f, d[j] + __shfl_xor_sync(0xffffffffu, d[j], 2) + 1e-6f);
        uint32_t* po = reinterpret_cast<uint32_t*>(g_a + (m * 128 + rb0 * 16 + g) * D_ + 72 * f + hh * 18 + 2 * t);
#pragma unroll
        for (int j = 0; j < 3; j++)
          if (rb0 + 3 * j < 8) {
            const uint32_t r0 = pack_bf16(d[2 * j], d[2 * j]), r1 = pack_bf16(d[2 * j + 1], d[2 * j + 1]);
#pragma unroll
            for (int b = 0; b < 3; b++)
              if (b < 2 || t == 0) {
                po[j * 24 * D_ + 4 * b] = hfma2(q[j][b].x, r0, 0x80008000u);
                po[j * 24 * D_ + 4 * D_ + 4 * b] = hfma2(q[j][b].y, r1, 0x80008000u);
              }
          }
      }
      asm volatile("fence.proxy.async.global;" ::: "memory");
      asm volatile("bar.sync 5, 96;" ::: "memory");
      if (tid == 288) asm volatile("red.release.gpu.global.add.u32 [%0], 1;" ::"l"(&g_f_a[m]) : "memory");
      __syncwarp();
      STAMPW(9, 23);
      if (srole && aw == 2) {
        if (lane == 0) {
          flag_wait(&g_f_a[m], 8 * ep);
          asm volatile("fence.proxy.async.global;" ::: "memory");
#pragma unroll 1
          for (int kb = 0; kb < 9; kb++) {
            mbar_wait(bar_xfree + 8 * kb, 0);
            mbar_expect(bar_ofull + 8 * kb, 16384);
            tma2d(sbase + SM_A + kb * 16384, &P.tm_a, kb * 64, m * 128, bar_ofull + 8 * kb);
          }
        }
        __syncwarp();
      }
      const int rbg = m * 8 + f;
      if (lane == 0) hint_wait(&g_f_rb[rbg * 8], 8 * ep);
      __syncwarp();
      STAMPW(9, 24);
#pragma unroll 1
      for (int hv = aw * 8; hv < aw * 8 + 8; hv++) {
        const uint32_t bb = __ldg(reinterpret_cast<const uint32_t*>(P.b2 + 8 * hv + 2 * t));
        uint2 p[8];
        int tries = 0;
        uint32_t bad;
#pragma unroll 1
        do {
          bad = 0;
#pragma unroll
          for (int i = 0; i < 8; i++) p[i] = ld_ll64(reinterpret_cast<const uint32_t*>(&g_part[((rbg * 8 + i) * 36 + (hv >> 1)) * 32 + lane]) + (hv & 1) * 2);
#pragma unroll
          for (int i = 0; i < 8; i += 2) ll_chk(bad, p[i].x, p[i + 1].x, par);
        } while (__any_sync(0xffffffffu, bad & 1) && ++tries < (1 << 20));
        const uint32_t g0 = gate_word(p[0].x, p[1].x, p[2].x, p[3].x, p[4].x, p[5].x, p[6].x, p[7].x, bb), g1 = gate_word(p[0].y, p[1].y, p[2].y, p[3].y, p[4].y, p[5].y, p[6].y, p[7].y, bb);
        asm volatile("{.reg .b64 a; mov.b64 a, {%1,%2}; st.relaxed.gpu.global.b64 [%0], a;}" ::"l"(reinterpret_cast<uint32_t*>(&g_g[(rbg * 12 + (hv >> 1)) * 32 + lane]) + (hv & 1) * 2), "r"(tag(g0, par)), "r"(g1) : "memory");
      }
      STAMPW(9, 25);
    }
    cluster_arrive_relaxed();
    cluster_wait();
  } else {
    const int wg = warp >> 2;
    {
      const int rs = lane >> 3, j = lane & 7;
      uint4 xv[4][9];
#pragma unroll
      for (int it = 0; it < 4; it++)
#pragma unroll
        for (int kb = 0; kb < 9; kb++) xv[it][kb] = __ldg(reinterpret_cast<const uint4*>(P.x + (m * 128 + warp * 16 + it * 4 + rs) * D_) + j + kb * 8);
      uint32_t bw0 = __ldg(reinterpret_cast<const uint32_t*>(P.b1 + 576 * f) + tid), bw1 = tid < 32 ? __ldg(reinterpret_cast<const uint32_t*>(P.b1 + 576 * f) + 256 + tid) : 0u;
      uint2 st[4];
      int tries = 0;
      uint32_t bad;
#pragma unroll 1
      do {
        bad = 0;
#pragma unroll
        for (int it = 0; it < 4; it++) st[it] = ld_ll64(reinterpret_cast<const uint32_t*>(&g_stat[m * 128 + warp * 16 + it * 4 + rs]));
        ll_chk(bad, st[0].x, st[1].x, par); ll_chk(bad, st[2].x, st[3].x, par);
      } while (__any_sync(0xffffffffu, bad & 1) && ++tries < (1 << 22));
      STAMPW(0, 19);
#pragma unroll
      for (int it = 0; it < 4; it++) {
        const uint32_t nm = st[it].y;
        uint8_t* dst = smem + SM_A + (warp * 16 + it * 4 + rs) * 128 + ((j ^ ((it * 4 + rs) & 7)) << 4);
#pragma unroll
        for (int kb = 0; kb < 9; kb++) {
          const uint4 w = xv[it][kb];
          *reinterpret_cast<uint4*>(dst + kb * 16384) = make_uint4(hadd2(w.x, nm), hadd2(w.y, nm), hadd2(w.z, nm), hadd2(w.w, nm));
        }
        if (j == 0) reinterpret_cast<uint32_t*>(smem + SM_RSTD)[warp * 16 + it * 4 + rs] = st[it].x;
      }
      reinterpret_cast<float2*>(smem + SM_BIAS)[tid] = make_float2(bf_lo(bw0) * GK, bf_hi(bw0) * GK);
      if (tid < 32) reinterpret_cast<float2*>(smem + SM_BIAS)[256 + tid] = make_float2(bf_lo(bw1) * GK, bf_hi(bw1) * GK);
      asm volatile("fence.proxy.async.shared::cta;" ::: "memory");
    }
    asm volatile("setmaxnreg.inc.sync.aligned.u32 232;");
    cluster_wait();
    asm volatile("bar.sync 1, 256;" ::: "memory");
    STAMPW(0, 1);
    Ctx c;
    c.full = bar_full;
    c.emb = __shfl_sync(0xffffffffu, mapa(bar_empty, (warp & 3) == 0 ? rank : (rank ^ 1)), 0);
    c.sig = lane == 0 && (warp & 3) < 2;
    c.stage = 0; c.phase = 0; c.prev = ~0u;
    c.dB = (((sbase + SM_B) & 0x3FFFF) >> 4) | ((4096u >> 4) << 16);
    c.dA = (((sbase + SM_A + wg * 8192) & 0x3FFFF) >> 4) | (1u << 16);
    const bool leader = (lane == 0) && ((warp & 3) == 0);

    const int rb = m * 8 + warp;
    const uint32_t bias_t = sbase + SM_BIAS + 8 * t;
    const uint32_t hst = sbase + SM_A + (warp * 16 + (lane & 7) + ((lane >> 3) & 1) * 8) * 128 + (((lane >> 4) ^ (lane & 7)) << 4);
    auto wg_sync = [&]() {
      asm volatile("fence.proxy.async.shared::cta;" ::: "memory");
      if (wg == 0) asm volatile("bar.sync 2, 128;" ::: "memory"); else asm volatile("bar.sync 3, 128;" ::: "memory");
    };
    float A[96], B[96];
#pragma unroll
    for (int i = 0; i < 96; i++) B[i] = 0.f;
#define GELU16(H0, H1, ACC, OFF) uint32_t E[8]; \
    _Pragma("unroll") for (int q = 0; q < 8; q++) E[q] = pack_bf16(fmaf(ACC[(OFF) + 2 * q], (q & 1) ? r1 : r0, bs[q >> 1].x), fmaf(ACC[(OFF) + 2 * q + 1], (q & 1) ? r1 : r0, bs[q >> 1].y)); \
    const uint4 H0 = gelu_group(E), H1 = gelu_group(E + 4);
#define SPART16(DST, ACC, OFF) { uint32_t E[8]; _Pragma("unroll") for (int q = 0; q < 8; q++) E[q] = pack_bf16(ACC[(OFF) + 2 * q] * ((q & 1) ? r1 : r0), ACC[(OFF) + 2 * q + 1] * ((q & 1) ? r1 : r0)); \
    if (f < 4) { const float l0 = r0 * 1.4426950408889634f, l1 = r1 * 1.4426950408889634f; \
      _Pragma("unroll") for (int q = 0; q < 8; q++) E[q] = phi_pack(E[q], ACC[(OFF) + 2 * q] * ((q & 1) ? l1 : l0), ACC[(OFF) + 2 * q + 1] * ((q & 1) ? l1 : l0)); } \
    st_ll(DST, E[0], E[1], E[2], E[3], par); st_ll(DST + 32, E[4], E[5], E[6], E[7], par); }
#define LDS_R(SC) float r0, r1; asm volatile("ld.shared.f32 %0, [%1];" : "=f"(r0) : "r"(rst)); asm volatile("ld.shared.f32 %0, [%1];" : "=f"(r1) : "r"(rst + 32)); r0 *= (SC); r1 *= (SC);
    const uint32_t rst = sbase + SM_RSTD + (warp * 16 + g) * 4;
#pragma unroll 1
    for (int i = srole; i < 4 + srole; i++) {
      {
        const uint32_t ow = i == 4 ? bar_ofull : 0u;
        if (ow) mbar_wait(ow, 0);
        issue192(A, c, 0, true);
        const int ln = opaque(lane);
        uint4* dst = i == 1 ? g_qkvf + (rb * 108 + 18 * f + 12) * 32 + ln : g_part + ((rb * 8 + f) * 36 + (i == 3 ? 0 : 24)) * 32 + ln;
        LDS_R(i == 2 ? GK : 1.f)
        retire(c);
        if (ow && leader) mbar_arrive(bar_xfree + 64);
        fence_regs<96>(B);
        int s = 1;
        if (i == 2) {
#pragma unroll 1
          for (; s < 3; s++) { issue192(A, c, s); retire(c); }
        }
        if (i > srole) {
#pragma unroll
          for (int u = 0; u < 6; u++, s++) {
            float2 bs[4];
            if (i == 2) lds_bias(bs, bias_t + (192 + 32 * u) * 4);
            if ((u & 1) && ow) mbar_wait(ow + 4 * s, 0);
            issue192(A, c, s);
            if (i == 2) {
              GELU16(h0, h1, B, 16 * u)
              stsm4((hst ^ ((2 * u & 3) << 5)) + (u >> 1) * 16384, h0);
              stsm4((hst ^ ((2 * u + 1 & 3) << 5)) + (u >> 1) * 16384, h1);
            } else if (i == 1) {
              if (u < 3) SPART16(dst + 2 * u * 32, B, 16 * u)
              if (u == 2) hint_signal(&g_f_qkv[m * 8 + f]);
            } else {
              part_groups<0, 2>(&B[16 * u], dst + 2 * u * 32, par);
              if (u == 5) hint_signal(&g_f_rb[rb * 8 + (i == 3 ? 0 : 2)]);
            }
            retire(c);
          }
        }
        const bool d1 = i == 1 + srole;
        const int send = d1 ? 10 : 15;
#pragma unroll 1
        for (; s < send; s++) {
          if (ow && !(s & 1)) mbar_wait(ow + 4 * s, 0);
          issue192(A, c, s);
          retire(c);
        }
        uint32_t W[48];
        if (d1) {
          const int head = 4 * f + (warp >> 1), rb0 = m * 8 + (warp & 1) * 4;
          issue192(A, c, 10);
          mbar_wait(bar_d, 0);
          d1_load(W, rb0, head, opaque(lane));
          retire(c);
#pragma unroll 1
          for (s = 11; s < 13; s++) { issue192(A, c, s); retire(c); }
          issue192(A, c, 13);
          int tries = 0;
#pragma unroll 1
          while (d1_bad(W, t, par) && ++tries < (1 << 20)) d1_load(W, rb0, head, opaque(lane));
          d1_mov(W, 0, t); d1_mov(W, 1, t);
          retire(c);
          issue192(A, c, 14);
          d1_mov(W, 2, t); d1_mov(W, 3, t);
          wg_wait<0>();
          asm volatile("bar.sync 4, 256;" ::: "memory");
          d1_mma_store(W, head, m * 2 + (warp & 1), opaque(lane), par);
          asm volatile("bar.sync 4, 256;" ::: "memory");
          STAMPW(0, 21);
          retire(c);
        }
        issue192(A, c, 15);
        if (i == 2) {
          const uint4* hsp = g_hsp + (blockIdx.x * 8 + warp) * 12 * 32 + opaque(lane);
#pragma unroll
          for (int q = 0; q < 12; q++) { const uint4 v = ldcg128(hsp + q * 32); W[4 * q] = v.x; W[4 * q + 1] = v.y; W[4 * q + 2] = v.z; W[4 * q + 3] = v.w; }
        } else {
#pragma unroll
          for (int q = 0; q < 48; q++) W[q] = 0;
        }
        retire(c);
        if (ow) mbar_wait(ow + 64, 0);
        issue192(A, c, 16);
        if (i == 2) wg_sync();
        retire(c);
        issue192(A, c, 17);
        if (i == 2) {
#pragma unroll
          for (int q = 0; q < 12; q++) stsm4((hst ^ ((q & 3) << 5)) + (3 + (q >> 2)) * 16384, make_uint4(W[4 * q], W[4 * q + 1], W[4 * q + 2], W[4 * q + 3]));
        }
        retire(c);
      }
      STAMPW(0, 2 + 2 * i);
      if ((i & 3) == 0) {
        issue96(B, c, 0, true);
        const int ln = opaque(lane);
        uint4* dst = i == 0 ? g_qkvf + (rb * 108 + 18 * f) * 32 + ln : g_s + (rb * 24 + 12 * (f - 6)) * 32 + ln;
        LDS_R(1.f)
        if (i != 0) { r0 = 1.f; r1 = 1.f; }
        retire(c);
        fence_regs<96>(A);
#pragma unroll
        for (int u = 0; u < 8; u++) {
          issue96(B, c, u + 1, false);
          if (u < 6) SPART16(dst + 2 * u * 32, A, 16 * (u < 6 ? u : 0))
          if (u == 5 && i == 0) hint_signal(&g_f_qkv[m * 8 + f]);
          retire(c);
        }
      } else {
        issue192(B, c, 0, true);
        const int ln = opaque(lane);
        uint4* dst = i == 1 ? g_hsp + (blockIdx.x * 8 + warp) * 12 * 32 + ln : g_part + ((rb * 8 + f) * 36 + 12) * 32 + ln;
        const bool xf = i == 3 && srole && leader;
        const uint32_t bsa = bias_t + (i == 1 ? 0 : 384) * 4;
        LDS_R(GK)
        retire(c);
        fence_regs<96>(A);
#pragma unroll
        for (int u = 0; u < 6; u++) {
          float2 bs[4];
          if (i != 3) lds_bias(bs, bsa + 32 * u * 4);
          issue192(B, c, u + 1);
          if (i != 3) {
            GELU16(h0, h1, A, 16 * u)
            if (i == 1) { dst[2 * u * 32] = h0; dst[(2 * u + 1) * 32] = h1; }
            else {
              stsm4((hst ^ ((2 * u & 3) << 5)) + (6 + (u >> 1)) * 16384, h0);
              stsm4((hst ^ ((2 * u + 1 & 3) << 5)) + (6 + (u >> 1)) * 16384, h1);
              if (u == 3) wg_sync();
            }
          } else {
            part_groups<0, 2>(&A[16 * u], dst + 2 * u * 32, par);
          }
          retire(c);
          if ((u & 1) && xf) mbar_arrive(bar_xfree + 4 * u - 4);
        }
#pragma unroll 1
        for (int s = 7; s < 17; s++) {
          issue192(B, c, s);
          if (s == 9 && i == 2) wg_sync();
          retire(c);
          if ((s & 1) == 0 && xf) mbar_arrive(bar_xfree + 4 * s - 8);
        }
        issue192(B, c, 17);
        retire(c);
      }
      STAMPW(0, 3 + 2 * i);
    }

    const int ln = opaque(lane);
    const __nv_bfloat16* xp = P.x + (rb * 16 + (ln >> 2)) * D_ + 2 * (ln & 3);
    __nv_bfloat16* op = P.out + (rb * 16 + (ln >> 2)) * D_ + 2 * (ln & 3);
    auto ldx = [&](uint32_t* xx, int col) {
      xx[0] = __ldg(reinterpret_cast<const uint32_t*>(xp + col)); xx[1] = __ldg(reinterpret_cast<const uint32_t*>(xp + 8 * D_ + col));
      xx[2] = __ldg(reinterpret_cast<const uint32_t*>(xp + col + 8)); xx[3] = __ldg(reinterpret_cast<const uint32_t*>(xp + 8 * D_ + col + 8));
    };
    auto stout = [&](int col, uint4 sv, uint4 gv, const uint32_t* xx) {
      *reinterpret_cast<uint32_t*>(op + col) = hfma2(sv.x, gv.x, xx[0]); *reinterpret_cast<uint32_t*>(op + 8 * D_ + col) = hfma2(sv.y, gv.y, xx[1]);
      *reinterpret_cast<uint32_t*>(op + col + 8) = hfma2(sv.z, gv.z, xx[2]); *reinterpret_cast<uint32_t*>(op + 8 * D_ + col + 8) = hfma2(sv.w, gv.w, xx[3]);
    };
    if (srole) {
      const int cb = 96 * (f - 6);
      uint32_t xx[24];
      uint4 gg[6];
#pragma unroll
      for (int q = 0; q < 6; q++) ldx(&xx[4 * q], cb + 16 * q);
      int tries = 0;
      uint32_t bad;
#pragma unroll 1
      do {
        bad = 0;
#pragma unroll
        for (int q = 0; q < 6; q++) gg[q] = ld_ll(&g_g[(rb * 12 + 6 * (f - 6) + q) * 32 + ln]);
#pragma unroll
        for (int q = 0; q < 6; q++) ll_chk(bad, gg[q].x, gg[q].z, par);
      } while (__any_sync(0xffffffffu, bad & 1) && ++tries < (1 << 20));
      STAMPW(0, 14);
      wg_wait<0>();
      c.release_prev();
      fence_regs<48>(B);
#pragma unroll
      for (int q = 0; q < 6; q++)
        stout(cb + 16 * q, make_uint4(pack_bf16(B[8 * q], B[8 * q + 1]), pack_bf16(B[8 * q + 2], B[8 * q + 3]), pack_bf16(B[8 * q + 4], B[8 * q + 5]), pack_bf16(B[8 * q + 6], B[8 * q + 7])), gg[q], &xx[4 * q]);
    } else {
      wg_wait<0>();
      c.release_prev();
      fence_regs<96>(B);
      part_groups<0, 12>(B, g_part + ((rb * 8 + f) * 36 + 24) * 32 + ln, par);
      hint_signal(&g_f_rb[rb * 8 + 2]);
      STAMPW(0, 12);
#pragma unroll 1
      for (int ch = 1; ch < 3; ch++) {
        const int cb = 192 * ch + 32 * f;
        uint32_t xx[8], bb[4];
        ldx(xx, cb); ldx(xx + 4, cb + 16);
#pragma unroll
        for (int j = 0; j < 4; j++) bb[j] = __ldg(reinterpret_cast<const uint32_t*>(P.b2 + cb + 8 * j + 2 * (ln & 3)));
        if (ln == 0 && ch == 2) hint_wait(&g_f_rb[rb * 8 + 2], 8u * ep, 20);
        __syncwarp();
        STAMPW(0, 12 + ch);
        uint4 p[2][8], sv[2];
        int tries = 0;
        uint32_t bad;
#pragma unroll 1
        do {
          bad = 0;
#pragma unroll
          for (int j = 0; j < 2; j++) {
#pragma unroll
            for (int k = 0; k < 8; k++) p[j][k] = ld_ll(&g_part[((rb * 8 + k) * 36 + 12 * ch + 2 * f + j) * 32 + ln]);
            sv[j] = ld_ll(&g_s[(rb * 24 + 12 * (ch - 1) + 2 * f + j) * 32 + ln]);
          }
#pragma unroll
          for (int j = 0; j < 2; j++) {
#pragma unroll
            for (int k = 0; k < 8; k++) ll_chk(bad, p[j][k].x, p[j][k].z, par);
            ll_chk(bad, sv[j].x, sv[j].z, par);
          }
        } while (__any_sync(0xffffffffu, bad & 1) && ++tries < (1 << 20));
#pragma unroll
        for (int j = 0; j < 2; j++) stout(cb + 16 * j, sv[j], gate_vec(p[j], bb[2 * j], bb[2 * j + 1]), &xx[4 * j]);
      }
    }
    STAMPW(0, 15);
    cluster_arrive_relaxed();
    cluster_wait();
    STAMPW(0, 16);
    if (tid == 0) g_epoch[blockIdx.x] = ep;
  }
}

typedef CUresult (*EncFn)(CUtensorMap*, CUtensorMapDataType, cuuint32_t, void*, const cuuint64_t*, const cuuint64_t*, const cuuint32_t*, const cuuint32_t*,
                          CUtensorMapInterleave, CUtensorMapSwizzle, CUtensorMapL2promotion, CUtensorMapFloatOOBfill);

void make_map(EncFn enc, CUtensorMap* tm, const void* ptr, int rows, int cols, int box_rows, bool sw64 = false) {
  cuuint64_t gd[2] = {(cuuint64_t)cols, (cuuint64_t)rows};
  cuuint64_t gs[1] = {(cuuint64_t)cols * 2};
  cuuint32_t bx[2] = {sw64 ? 32u : 64u, (cuuint32_t)box_rows};
  cuuint32_t es[2] = {1, 1};
  enc(tm, CU_TENSOR_MAP_DATA_TYPE_BFLOAT16, 2, const_cast<void*>(ptr), gd, gs, bx, es, CU_TENSOR_MAP_INTERLEAVE_NONE, sw64 ? CU_TENSOR_MAP_SWIZZLE_64B : CU_TENSOR_MAP_SWIZZLE_128B,
      CU_TENSOR_MAP_L2_PROMOTION_L2_256B, CU_TENSOR_MAP_FLOAT_OOB_FILL_NONE);
}

}

extern "C" void kernel_launch(void* const* d_in, const int* in_sizes, int n_in, void* d_out, int out_size) {
  (void)in_sizes; (void)n_in; (void)out_size;
  static EncFn enc = nullptr;
  static void *a_ptr = nullptr, *m_ptr = nullptr;
  if (!enc) {
    void* fn = nullptr; cudaDriverEntryPointQueryResult q;
    cudaGetDriverEntryPoint("cuTensorMapEncodeTiled", &fn, cudaEnableDefault, &q);
    enc = (EncFn)fn;
    cudaFuncSetAttribute(fused_kernel, cudaFuncAttributeMaxDynamicSharedMemorySize, SMEM_BYTES);
    cudaGetSymbolAddress(&a_ptr, g_a);
    cudaGetSymbolAddress(&m_ptr, g_m);
  }
  Params P;
  P.x = (const __nv_bfloat16*)d_in[0];
  P.wqkv = (const __nv_bfloat16*)d_in[1];
  P.wo = (const __nv_bfloat16*)d_in[2];
  P.w1 = (const __nv_bfloat16*)d_in[4];
  P.b1 = (const __nv_bfloat16*)d_in[5];
  P.w2 = (const __nv_bfloat16*)d_in[6];
  P.b2 = (const __nv_bfloat16*)d_in[7];
  P.out = (__nv_bfloat16*)d_out;
  make_map(enc, &P.tm_wqkv, P.wqkv, D_, Q3_, 32);
  make_map(enc, &P.tm_w1, P.w1, D_, F_, 32);
  make_map(enc, &P.tm_w2, P.w2, F_, D_, 32);
  make_map(enc, &P.tm_m, m_ptr, D_, D_, 32);
  make_map(enc, &P.tm_wqkv64, P.wqkv, D_, Q3_, 64, true);
  make_map(enc, &P.tm_m64, m_ptr, D_, D_, 64, true);
  make_map(enc, &P.tm_a, a_ptr, S_, D_, 128);
  fused_kernel<<<NCTAS, NTHREADS, SMEM_BYTES, cudaStreamPerThread>>>(P);
}
```

```cpp
#include <cuda_runtime.h>
#include <cuda.h>
#include <cuda_bf16.h>
#include <stdint.h>

namespace {

constexpr int S_ = 2048, D_ = 576, F_ = 4608, Q3_ = 1728;
constexpr int NSTAGE = 6, STAGE_BYTES = 12288;
constexpr int SM_A = 0, SM_B = 147456, SM_BIAS = SM_B + NSTAGE * STAGE_BYTES, SM_RSTD = SM_BIAS + 2304, SM_SCR = SM_RSTD + 512, SM_BAR = SM_SCR + 7168;
constexpr int SMEM_BYTES = SM_BAR + 320;
constexpr int NTHREADS = 384;
constexpr int NCTAS = 132;

__device__ uint4 g_qkvf[(128 * 108 + 1) * 32];
__device__ __align__(1024) __nv_bfloat16 g_a[S_ * D_];
__device__ __align__(1024) __nv_bfloat16 g_m[D_ * D_];
__device__ uint4 g_kvp[32 * 5 * 16 * 32];
__device__ uint4 g_z[32 * 2 * 4];
__device__ uint4 g_part[128 * 8 * 36 * 32];
__device__ uint4 g_s[128 * 24 * 32];
__device__ uint4 g_g[128 * 12 * 32];
__device__ uint4 g_hsp[128 * 12 * 256];
__device__ uint32_t g_f_qkv[16 * 8];
__device__ uint32_t g_f_kvp[32];
__device__ uint32_t g_f_z[32];
__device__ uint32_t g_f_a[16];
__device__ uint32_t g_f_m[1];
__device__ uint32_t g_f_rb[128 * 8];
__device__ uint2 g_stat[S_];
__device__ uint32_t g_epoch[NCTAS];

#define STAMP(i)
#define STAMPW(w, i)
#define WSTAMP(i)
__device__ __forceinline__ uint32_t smem_u32(const void* p) { return (uint32_t)__cvta_generic_to_shared(p); }
__device__ __forceinline__ void mbar_init(uint32_t a, int c) { asm volatile("mbarrier.init.shared::cta.b64 [%0], %1;" ::"r"(a), "r"(c)); }
__device__ __forceinline__ void mbar_expect(uint32_t a, uint32_t b) { asm volatile("mbarrier.arrive.expect_tx.shared::cta.b64 _, [%0], %1;" ::"r"(a), "r"(b) : "memory"); }
__device__ __forceinline__ void mbar_arrive(uint32_t a) { asm volatile("mbarrier.arrive.shared::cta.b64 _, [%0];" ::"r"(a) : "memory"); }
__device__ __forceinline__ void mbar_arrive_cl(uint32_t a) { asm volatile("mbarrier.arrive.shared::cluster.b64 _, [%0];" ::"r"(a) : "memory"); }
__device__ __forceinline__ uint32_t mapa(uint32_t a, uint32_t cta) { uint32_t r; asm volatile("mapa.shared::cluster.u32 %0, %1, %2;" : "=r"(r) : "r"(a), "r"(cta)); return r; }
__device__ __forceinline__ void mbar_wait(uint32_t a, uint32_t ph) {
  uint32_t ok; int it = 0;
#pragma unroll 1
  do {
    asm volatile("{.reg .pred p; mbarrier.try_wait.parity.shared::cta.b64 p, [%1], %2; selp.u32 %0,1,0,p;}" : "=r"(ok) : "r"(a), "r"(ph) : "memory");
  } while (!ok && ++it < (1 << 18));
}
__device__ __forceinline__ void tma2d(uint32_t dst, const CUtensorMap* m, int c0, int c1, uint32_t bar) {
  asm volatile("cp.async.bulk.tensor.2d.shared::cluster.global.mbarrier::complete_tx::bytes [%0], [%1, {%3,%4}], [%2];" ::"r"(dst), "l"(m), "r"(bar), "r"(c0), "r"(c1) : "memory");
}
__device__ __forceinline__ void tma2d_mc(uint32_t dst, const CUtensorMap* m, int c0, int c1, uint32_t bar) {
  asm volatile("cp.async.bulk.tensor.2d.shared::cluster.global.mbarrier::complete_tx::bytes.multicast::cluster [%0], [%1, {%3,%4}], [%2], %5;" ::"r"(dst), "l"(m), "r"(bar), "r"(c0), "r"(c1), "h"((uint16_t)3) : "memory");
}
__device__ __forceinline__ void cluster_arrive_relaxed() { asm volatile("barrier.cluster.arrive.relaxed.aligned;" ::: "memory"); }
__device__ __forceinline__ void cluster_wait() { asm volatile("barrier.cluster.wait.acquire.aligned;" ::: "memory"); }
__device__ __forceinline__ void wg_fence() { asm volatile("wgmma.fence.sync.aligned;" ::: "memory"); }
__device__ __forceinline__ void wg_commit() { asm volatile("wgmma.commit_group.sync.aligned;" ::: "memory"); }
template <int n> __device__ __forceinline__ void wg_wait() { asm volatile("wgmma.wait_group.sync.aligned %0;" ::"n"(n) : "memory"); }
__device__ __forceinline__ uint32_t ld_acquire(const uint32_t* p) { uint32_t v; asm volatile("ld.acquire.gpu.global.u32 %0, [%1];" : "=r"(v) : "l"(p) : "memory"); return v; }
__device__ __forceinline__ void flag_wait(const uint32_t* p, uint32_t target) {
  int it = 0;
#pragma unroll 1
  while ((int)(ld_acquire(p) - target) < 0 && ++it < (1 << 20)) __nanosleep(300);
}
__device__ __forceinline__ void hint_signal(uint32_t* p) {
  if ((threadIdx.x & 31) == 0) asm volatile("red.relaxed.gpu.global.add.u32 [%0], 1;" ::"l"(p) : "memory");
}
__device__ __forceinline__ void hint_wait(const uint32_t* p, uint32_t target, uint32_t ns = 400) {
  int it = 0; uint32_t v;
#pragma unroll 1
  do { asm volatile("ld.relaxed.gpu.global.u32 %0, [%1];" : "=r"(v) : "l"(p) : "memory"); if ((int)(v - target) >= 0) break; __nanosleep(ns); } while (++it < (1 << 20));
}
__device__ __forceinline__ uint32_t tag(uint32_t x, uint32_t par) { uint32_t r; asm("lop3.b32 %0, %1, 0xfffffffe, %2, 0xea;" : "=r"(r) : "r"(x), "r"(par)); return r; }
__device__ __forceinline__ void st_ll(uint4* p, uint32_t x, uint32_t y, uint32_t z, uint32_t w, uint32_t par) {
  asm volatile("{.reg .b64 a, b; mov.b64 a, {%1,%2}; mov.b64 b, {%3,%4}; st.relaxed.gpu.global.v2.b64 [%0], {a, b};}"
               ::"l"(p), "r"(tag(x, par)), "r"(y), "r"(tag(z, par)), "r"(w) : "memory");
}
__device__ __forceinline__ uint4 ld_ll(const uint4* p) {
  uint4 v;
  asm volatile("{.reg .b64 a, b; ld.relaxed.gpu.global.v2.b64 {a, b}, [%4]; mov.b64 {%0,%1}, a; mov.b64 {%2,%3}, b;}"
               : "=r"(v.x), "=r"(v.y), "=r"(v.z), "=r"(v.w) : "l"(p) : "memory");
  return v;
}
__device__ __forceinline__ uint2 ld_ca64(const uint32_t* p) {
  uint2 v;
  asm volatile("{.reg .b64 a; ld.global.ca.b64 a, [%2]; mov.b64 {%0,%1}, a;}" : "=r"(v.x), "=r"(v.y) : "l"(p) : "memory");
  return v;
}
__device__ __forceinline__ uint2 ld_ll64(const uint32_t* p) {
  uint2 v;
  asm volatile("{.reg .b64 a; ld.relaxed.gpu.global.b64 a, [%2]; mov.b64 {%0,%1}, a;}" : "=r"(v.x), "=r"(v.y) : "l"(p) : "memory");
  return v;
}
__device__ __forceinline__ void ll_chk(uint32_t& bad, uint32_t a, uint32_t b, uint32_t par) {
  uint32_t u; asm("lop3.b32 %0, %1, %2, %3, 0x7e;" : "=r"(u) : "r"(a), "r"(b), "r"(par));
  asm("or.b32 %0, %0, %1;" : "+r"(bad) : "r"(u));
}
__device__ __forceinline__ uint32_t hadd2(uint32_t a, uint32_t b) { uint32_t d; asm("add.rn.bf16x2 %0, %1, %2;" : "=r"(d) : "r"(a), "r"(b)); return d; }
__device__ __forceinline__ uint32_t hfma2(uint32_t a, uint32_t b, uint32_t c) { uint32_t d; asm("fma.rn.bf16x2 %0, %1, %2, %3;" : "=r"(d) : "r"(a), "r"(b), "r"(c)); return d; }
__device__ __forceinline__ uint32_t pack_bf16(float lo, float hi) { uint32_t r; asm("cvt.rn.bf16x2.f32 %0, %1, %2;" : "=r"(r) : "f"(hi), "f"(lo)); return r; }
__device__ __forceinline__ float bf_lo(uint32_t v) { return __uint_as_float(v << 16); }
__device__ __forceinline__ float bf_hi(uint32_t v) { return __uint_as_float(v & 0xffff0000u); }
__device__ __forceinline__ uint32_t movmat(uint32_t a) { uint32_t d; asm volatile("movmatrix.sync.aligned.m8n8.trans.b16 %0, %1;" : "=r"(d) : "r"(a)); return d; }
__device__ __forceinline__ void mma16816(float* c, uint32_t a0, uint32_t a1, uint32_t a2, uint32_t a3, uint32_t b0, uint32_t b1) {
  asm volatile("mma.sync.aligned.m16n8k16.row.col.f32.bf16.bf16.f32 {%0,%1,%2,%3}, {%4,%5,%6,%7}, {%8,%9}, {%0,%1,%2,%3};"
               : "+f"(c[0]), "+f"(c[1]), "+f"(c[2]), "+f"(c[3]) : "r"(a0), "r"(a1), "r"(a2), "r"(a3), "r"(b0), "r"(b1));
}
__device__ __forceinline__ uint4 ldcg128(const void* p) { uint4 v; asm volatile("ld.global.cg.v4.u32 {%0,%1,%2,%3}, [%4];" : "=r"(v.x), "=r"(v.y), "=r"(v.z), "=r"(v.w) : "l"(p) : "memory"); return v; }

template <int N> __device__ __forceinline__ void wgmma_ss(float* d, uint64_t da, uint64_t db, int sc);
template <int N> __device__ __forceinline__ void wgmma_rs(float* d, const uint32_t* a, uint64_t db, int sc);
template <> __device__ __forceinline__ void wgmma_ss<96>(float* d, uint64_t da, uint64_t db, int sc) {
  asm volatile("{.reg .pred p; setp.ne.b32 p, %50, 0; wgmma.mma_async.sync.aligned.m64n96k16.f32.bf16.bf16 {%0, %1, %2, %3, %4, %5, %6, %7, %8, %9, %10, %11, %12, %13, %14, %15, %16, %17, %18, %19, %20, %21, %22, %23, %24, %25, %26, %27, %28, %29, %30, %31, %32, %33, %34, %35, %36, %37, %38, %39, %40, %41, %42, %43, %44, %45, %46, %47}, %48, %49, p, 1, 1, 0, 1;}"
   : "+f"(d[0]), "+f"(d[1]), "+f"(d[2]), "+f"(d[3]), "+f"(d[4]), "+f"(d[5]), "+f"(d[6]), "+f"(d[7]), "+f"(d[8]), "+f"(d[9]), "+f"(d[10]), "+f"(d[11]), "+f"(d[12]), "+f"(d[13]), "+f"(d[14]), "+f"(d[15]), "+f"(d[16]), "+f"(d[17]), "+f"(d[18]), "+f"(d[19]), "+f"(d[20]), "+f"(d[21]), "+f"(d[22]), "+f"(d[23]), "+f"(d[24]), "+f"(d[25]), "+f"(d[26]), "+f"(d[27]), "+f"(d[28]), "+f"(d[29]), "+f"(d[30]), "+f"(d[31]), "+f"(d[32]), "+f"(d[33]), "+f"(d[34]), "+f"(d[35]), "+f"(d[36]), "+f"(d[37]), "+f"(d[38]), "+f"(d[39]), "+f"(d[40]), "+f"(d[41]), "+f"(d[42]), "+f"(d[43]), "+f"(d[44]), "+f"(d[45]), "+f"(d[46]), "+f"(d[47]) : "l"(da), "l"(db), "r"(sc));
}
template <> __device__ __forceinline__ void wgmma_ss<192>(float* d, uint64_t da, uint64_t db, int sc) {
  asm volatile("{.reg .pred p; setp.ne.b32 p, %98, 0; wgmma.mma_async.sync.aligned.m64n192k16.f32.bf16.bf16 {%0, %1, %2, %3, %4, %5, %6, %7, %8, %9, %10, %11, %12, %13, %14, %15, %16, %17, %18, %19, %20, %21, %22, %23, %24, %25, %26, %27, %28, %29, %30, %31, %32, %33, %34, %35, %36, %37, %38, %39, %40, %41, %42, %43, %44, %45, %46, %47, %48, %49, %50, %51, %52, %53, %54, %55, %56, %57, %58, %59, %60, %61, %62, %63, %64, %65, %66, %67, %68, %69, %70, %71, %72, %73, %74, %75, %76, %77, %78, %79, %80, %81, %82, %83, %84, %85, %86, %87, %88, %89, %90, %91, %92, %93, %94, %95}, %96, %97, p, 1, 1, 0, 1;}"
   : "+f"(d[0]), "+f"(d[1]), "+f"(d[2]), "+f"(d[3]), "+f"(d[4]), "+f"(d[5]), "+f"(d[6]), "+f"(d[7]), "+f"(d[8]), "+f"(d[9]), "+f"(d[10]), "+f"(d[11]), "+f"(d[12]), "+f"(d[13]), "+f"(d[14]), "+f"(d[15]), "+f"(d[16]), "+f"(d[17]), "+f"(d[18]), "+f"(d[19]), "+f"(d[20]), "+f"(d[21]), "+f"(d[22]), "+f"(d[23]), "+f"(d[24]), "+f"(d[25]), "+f"(d[26]), "+f"(d[27]), "+f"(d[28]), "+f"(d[29]), "+f"(d[30]), "+f"(d[31]), "+f"(d[32]), "+f"(d[33]), "+f"(d[34]), "+f"(d[35]), "+f"(d[36]), "+f"(d[37]), "+f"(d[38]), "+f"(d[39]), "+f"(d[40]), "+f"(d[41]), "+f"(d[42]), "+f"(d[43]), "+f"(d[44]), "+f"(d[45]), "+f"(d[46]), "+f"(d[47]), "+f"(d[48]), "+f"(d[49]), "+f"(d[50]), "+f"(d[51]), "+f"(d[52]), "+f"(d[53]), "+f"(d[54]), "+f"(d[55]), "+f"(d[56]), "+f"(d[57]), "+f"(d[58]), "+f"(d[59]), "+f"(d[60]), "+f"(d[61]), "+f"(d[62]), "+f"(d[63]), "+f"(d[64]), "+f"(d[65]), "+f"(d[66]), "+f"(d[67]), "+f"(d[68]), "+f"(d[69]), "+f"(d[70]), "+f"(d[71]), "+f"(d[72]), "+f"(d[73]), "+f"(d[74]), "+f"(d[75]), "+f"(d[76]), "+f"(d[77]), "+f"(d[78]), "+f"(d[79]), "+f"(d[80]), "+f"(d[81]), "+f"(d[82]), "+f"(d[83]), "+f"(d[84]), "+f"(d[85]), "+f"(d[86]), "+f"(d[87]), "+f"(d[88]), "+f"(d[89]), "+f"(d[90]), "+f"(d[91]), "+f"(d[92]), "+f"(d[93]), "+f"(d[94]), "+f"(d[95]) : "l"(da), "l"(db), "r"(sc));
}

__device__ __forceinline__ uint64_t desc64(uint32_t lo, uint32_t hi) { uint64_t d; asm("mov.b64 %0, {%1, %2};" : "=l"(d) : "r"(lo), "r"(hi)); return d; }
constexpr uint32_t DESC_HI = (1024u >> 4) | (1u << 30);
constexpr uint32_t DESC_HI64 = (512u >> 4) | (2u << 30);
template <int n> __device__ __forceinline__ void fence_regs(float* a) {
#pragma unroll
  for (int i = 0; i < n; i++) asm volatile("" : "+f"(a[i])::"memory");
}

struct Ctx {
  uint32_t full;
  uint32_t emb;
  bool sig;
  uint32_t stage, phase, prev;
  uint32_t dB, dA;
  __device__ __forceinline__ void release_prev() { if (sig && prev != ~0u) mbar_arrive_cl(emb + prev); }
  __device__ __forceinline__ void wait_full() {
    mbar_wait(full + 8 * stage, phase);
    wg_fence();
  }
};

__device__ __forceinline__ void issue192(float* acc, Ctx& c, int s, bool first = false) {
  c.wait_full();
  const uint32_t db = c.dB + c.stage * (STAGE_BYTES >> 4);
  const uint32_t da = c.dA + (s >> 1) * 1024 + (s & 1) * 4;
  wgmma_ss<192>(acc, desc64(da, DESC_HI), desc64(db, DESC_HI), first ? 0 : 1);
  wgmma_ss<192>(acc, desc64(da + 2, DESC_HI), desc64(db + 128, DESC_HI), 1);
  wg_commit();
}
__device__ __forceinline__ void issue96(float* acc, Ctx& c, int s, bool first) {
  c.wait_full();
  const uint32_t db = c.dB + c.stage * (STAGE_BYTES >> 4);
  const uint32_t da = c.dA + s * 1024;
  if (first) { wgmma_ss<192>(acc, desc64(da, DESC_HI), desc64(db, DESC_HI64), 0); wg_fence(); }
#pragma unroll
  for (int kk = first ? 1 : 0; kk < 4; kk++) wgmma_ss<96>(acc, desc64(da + 2 * kk, DESC_HI), desc64(db + 64 * kk, DESC_HI64), 1);
  wg_commit();
}
__device__ __forceinline__ void retire(Ctx& c) {
  wg_wait<1>();
  c.release_prev();
  c.prev = 8 * c.stage;
  if (++c.stage == NSTAGE) { c.stage = 0; c.phase ^= 1; }
}
constexpr float GK = 0.32920349f;
__device__ __forceinline__ uint32_t gelu_pair(uint32_t y) {
  uint32_t u, th;
  asm("mul.rn.bf16x2 %0, %1, %2;" : "=r"(u) : "r"(hfma2(y, y, 0x401b401bu)), "r"(y));
  asm("tanh.approx.bf16x2 %0, %1;" : "=r"(th) : "r"(u));
  return hfma2(y, th, y);
}
__device__ __forceinline__ uint4 gelu_group(const uint32_t* a) { return make_uint4(gelu_pair(a[0]), gelu_pair(a[1]), gelu_pair(a[2]), gelu_pair(a[3])); }
__device__ __forceinline__ void lds_bias(float2* b, uint32_t addr) {
#pragma unroll
  for (int j = 0; j < 4; j++) asm volatile("ld.shared.v2.f32 {%0,%1}, [%2];" : "=f"(b[j].x), "=f"(b[j].y) : "r"(addr + 32 * j));
}
__device__ __forceinline__ int opaque(int v) { asm volatile("" : "+r"(v)); return v; }
__device__ __forceinline__ void stsm4(uint32_t addr, uint4 r) {
  asm volatile("stmatrix.sync.aligned.m8n8.x4.shared.b16 [%0], {%1,%2,%3,%4};" ::"r"(addr), "r"(r.x), "r"(r.y), "r"(r.z), "r"(r.w) : "memory");
}
__device__ __forceinline__ float ex2f(float x) { float r; asm("ex2.approx.ftz.f32 %0, %1;" : "=f"(r) : "f"(x)); return r; }
__device__ __forceinline__ uint32_t phi_pack(uint32_t tp, float a0, float a1) {
  uint32_t x, y;
  asm("max.bf16x2 %0, %1, %2;" : "=r"(x) : "r"(tp), "r"(0x35863586u));
  asm("min.bf16x2 %0, %1, %2;" : "=r"(y) : "r"(pack_bf16(ex2f(a0), ex2f(a1))), "r"(0x3f803f80u));
  return hadd2(x, y);
}
template <int q0, int q1>
__device__ __forceinline__ void part_groups(const float* a, uint4* p, uint32_t par) {
#pragma unroll
  for (int q = q0; q < q1; q++)
    st_ll(p + q * 32, pack_bf16(a[8 * q], a[8 * q + 1]), pack_bf16(a[8 * q + 2], a[8 * q + 3]), pack_bf16(a[8 * q + 4], a[8 * q + 5]), pack_bf16(a[8 * q + 6], a[8 * q + 7]), par);
}
__device__ __forceinline__ float silu(float y) { return __fdividef(y, 1.f + ex2f(y * -1.4426950408889634f)); }
__device__ __forceinline__ uint32_t gate_word(uint32_t w0, uint32_t w1, uint32_t w2, uint32_t w3, uint32_t w4, uint32_t w5, uint32_t w6, uint32_t w7, uint32_t bb) {
  const uint32_t u0 = hadd2(hadd2(w0, w1), hadd2(w2, w3)), u1 = hadd2(hadd2(w4, w5), hadd2(w6, w7));
  return pack_bf16(silu(fmaf(bf_lo(u0) + bf_lo(u1), 0.5f / GK, bf_lo(bb))), silu(fmaf(bf_hi(u0) + bf_hi(u1), 0.5f / GK, bf_hi(bb))));
}
__device__ __forceinline__ uint4 gate_vec(const uint4* p, uint32_t b0, uint32_t b1) {
  return make_uint4(gate_word(p[0].x, p[1].x, p[2].x, p[3].x, p[4].x, p[5].x, p[6].x, p[7].x, b0), gate_word(p[0].y, p[1].y, p[2].y, p[3].y, p[4].y, p[5].y, p[6].y, p[7].y, b0),
                    gate_word(p[0].z, p[1].z, p[2].z, p[3].z, p[4].z, p[5].z, p[6].z, p[7].z, b1), gate_word(p[0].w, p[1].w, p[2].w, p[3].w, p[4].w, p[5].w, p[6].w, p[7].w, b1));
}
__device__ __forceinline__ int coloff(int c) { return (c >> 4) * 128 + ((c & 7) >> 1) * 4 + ((c >> 3) & 1) * 2; }

template <bool STRONG> __device__ __forceinline__ void d1_load(uint32_t* W, int rb0, int head, int ln) {
  const uint32_t* qf = reinterpret_cast<const uint32_t*>(g_qkvf) + rb0 * 108 * 128 + (ln >> 2) * 16;
#pragma unroll
  for (int b = 0; b < 3; b++) {
    const uint32_t* p = qf + coloff(576 + head * 18 + 8 * b + 2 * (ln & 3));
#pragma unroll
    for (int j = 0; j < 4; j++) {
      const uint2 kk = STRONG ? ld_ll64(p + j * 108 * 128) : ld_ca64(p + j * 108 * 128), vv = STRONG ? ld_ll64(p + j * 108 * 128 + 36 * 128) : ld_ca64(p + j * 108 * 128 + 36 * 128);
      W[6 * j + 2 * b] = kk.x; W[6 * j + 2 * b + 1] = kk.y; W[24 + 6 * j + 2 * b] = vv.x; W[24 + 6 * j + 2 * b + 1] = vv.y;
    }
  }
}
__device__ __forceinline__ bool d1_bad(const uint32_t* W, int t, uint32_t par) {
  uint32_t bad = 0, bad2 = 0;
#pragma unroll
  for (int q = 0; q < 12; q++) ll_chk((q % 3) != 2 ? bad : bad2, W[2 * q], W[24 + 2 * q], par);
  return __any_sync(0xffffffffu, (bad | (t == 0 ? bad2 : 0u)) & 1);
}
__device__ __forceinline__ void d1_mov(uint32_t* W, int j, int t) {
  if (t != 0) { W[6 * j + 4] = W[6 * j + 5] = 0u; W[24 + 6 * j + 4] = W[24 + 6 * j + 5] = (t == 1 ? 0x00003f80u : 0u); }
#pragma unroll
  for (int q = 0; q < 6; q++) { W[6 * j + q] = movmat(W[6 * j + q]); W[24 + 6 * j + q] = movmat(W[24 + 6 * j + q]); }
}
__device__ __forceinline__ void d1_mma(const uint32_t* W, float* R) {
  float c1[3][4];
#pragma unroll
  for (int j = 0; j < 12; j++) { R[j] = 0.f; c1[j >> 2][j & 3] = 0.f; }
#pragma unroll
  for (int ks = 0; ks < 4; ks++)
#pragma unroll
    for (int j = 0; j < 3; j++) {
      mma16816(R + 4 * j, W[24 + 6 * ks], W[24 + 6 * ks + 2], W[24 + 6 * ks + 1], W[24 + 6 * ks + 3], W[6 * ks + 2 * j], W[6 * ks + 2 * j + 1]);
      mma16816(c1[j], W[24 + 6 * ks + 4], 0u, W[24 + 6 * ks + 5], 0u, W[6 * ks + 2 * j], W[6 * ks + 2 * j + 1]);
    }
#pragma unroll
  for (int j = 0; j < 3; j++) { R[12 + 2 * j] = c1[j][0]; R[13 + 2 * j] = c1[j][1]; }
}
__device__ __forceinline__ bool kv_valid(int w, int ln) { return (w < 3 || ln < 12) && ((w != 2 && w != 4) || (ln & 3) == 0); }

struct Params {
  CUtensorMap tm_wqkv, tm_w1, tm_w2, tm_m, tm_wqkv64, tm_m64, tm_a;
  const __nv_bfloat16 *x, *b1, *b2, *wqkv, *w1, *w2, *wo;
  __nv_bfloat16* out;
};

__global__ void __cluster_dims__(2, 1, 1) __launch_bounds__(NTHREADS, 1) fused_kernel(const __grid_constant__ Params P) {
  extern __shared__ __align__(1024) uint8_t smem[];
  const uint32_t sbase = smem_u32(smem);
  const int tid = threadIdx.x, lane = tid & 31;
  const int warp = __shfl_sync(0xffffffffu, tid >> 5, 0);
  const int g = lane >> 2, t = lane & 3;
  const uint32_t ep = __shfl_sync(0xffffffffu, g_epoch[blockIdx.x], 0) + 1;
  const uint32_t par = ep & 1;
  STAMPW(0, 0);

  if (blockIdx.x >= 128) {
    const int a = blockIdx.x - 128;
    constexpr int WP = 1168, SM_T = 152 * WP, SM_HB = SM_T + 8 * 32 * 80;
    if (tid == 0) {
      mbar_init(sbase + SM_HB, 1);
      asm volatile("fence.mbarrier_init.release.cluster;" ::: "memory");
      mbar_expect(sbase + SM_HB, 144 * 1152);
    }
    for (int i = tid; i < (8 * WP + 8 * 32 * 80) / 4; i += NTHREADS) reinterpret_cast<uint32_t*>(smem + 144 * WP)[i] = 0u;
    __syncthreads();
    __nanosleep(1500);
    if (tid < 144)
      asm volatile("cp.async.bulk.shared::cluster.global.mbarrier::complete_tx::bytes [%0], [%1], %2, [%3];" ::"r"(sbase + tid * WP), "l"(P.wo + (a * 144 + tid) * D_), "r"(1152), "r"(sbase + SM_HB) : "memory");
    if (warp >= 8 && lane == 0) {
      const int id = a * 4 + (warp - 8);
      constexpr uint32_t CH = 9216 * 2;
#pragma unroll 1
      for (int i = id; i < 576; i += 16) {
        const char* p = i < 288 ? (const char*)P.w1 + (size_t)i * CH : (const char*)P.w2 + (size_t)(i - 288) * CH;
        asm volatile("cp.async.bulk.prefetch.L2.global [%0], %1;" ::"l"(p), "r"(CH) : "memory");
      }
    }
    __syncwarp();
    if (lane < 8) hint_wait(&g_f_kvp[a * 8 + lane], 16 * ep, 50);
    __syncwarp();
    STAMPW(0, 1);
#pragma unroll 1
    for (int u = warp; u < 40; u += 12) {
      const int hh = u & 7, w = 4 - (u >> 3), head = a * 8 + hh;
      uint4 v[16];
      int tries = 0;
      uint32_t bad;
      const bool val = kv_valid(w, lane);
#pragma unroll 1
      do {
        bad = 0;
#pragma unroll
        for (int j = 0; j < 16; j++) v[j] = val ? ld_ll(&g_kvp[((head * 5 + w) * 16 + j) * 32 + lane]) : make_uint4(par, 0u, par, 0u);
#pragma unroll
        for (int j = 0; j < 16; j++) ll_chk(bad, v[j].x, v[j].z, par);
      } while (__any_sync(0xffffffffu, bad & 1) && ++tries < (1 << 20));
      float s0 = 0.f, s1 = 0.f, s2 = 0.f, s3 = 0.f;
#pragma unroll
      for (int j = 0; j < 16; j++) { s0 += __uint_as_float(v[j].x); s1 += __uint_as_float(v[j].y); s2 += __uint_as_float(v[j].z); s3 += __uint_as_float(v[j].w); }
      if (w >= 3) {
        if (g == 2) st_ll(&g_z[(head * 2 + w - 3) * 4 + t], __float_as_uint(s0), __float_as_uint(s1), __float_as_uint(s2), __float_as_uint(s3), par);
        __syncwarp();
        hint_signal(&g_f_z[head]);
      }
      const int e0 = w < 3 ? g : 16 + g, e1 = w < 3 ? g + 8 : 16 + g, d0 = (w < 3 ? 8 * w : (w == 3 ? 0 : 16)) + 2 * t, d1 = w < 3 ? d0 : d0 + 8;
      __nv_bfloat16* T = reinterpret_cast<__nv_bfloat16*>(smem + SM_T) + hh * 32 * 40;
      if (e0 < 18) {
        T[d0 * 40 + e0] = __float2bfloat16(s0); T[(d0 + 1) * 40 + e0] = __float2bfloat16(s1);
        T[d1 * 40 + e1] = __float2bfloat16(s2); T[(d1 + 1) * 40 + e1] = __float2bfloat16(s3);
      }
    }
    __syncthreads();
    STAMPW(0, 2);
    mbar_wait(sbase + SM_HB, 0);
#pragma unroll 1
    for (int u = warp; u < 24; u += 12) {
      const int hh = u / 3, c0 = (u % 3) * 192;
      const uint32_t* T = reinterpret_cast<const uint32_t*>(smem + SM_T) + hh * 32 * 20 + g * 20 + t;
      const uint32_t a00 = T[0], a01 = T[160], a02 = T[4], a03 = T[164], a10 = T[8], a11 = T[168], b00 = T[320], b02 = T[324], b10 = T[328];
      const uint32_t rowa = sbase + (hh * 18 + (lane & 15)) * WP + (c0 + (lane >> 4) * 8) * 2, rowb = sbase + (hh * 18 + 16 + (lane & 7)) * WP + (c0 + ((lane >> 3) & 1) * 8) * 2;
#pragma unroll 3
      for (int j = 0; j < 12; j++) {
        uint32_t w0, w1, w2, w3, w4, w5;
        asm volatile("ldmatrix.sync.aligned.m8n8.x4.trans.shared.b16 {%0,%1,%2,%3}, [%4];" : "=r"(w0), "=r"(w1), "=r"(w2), "=r"(w3) : "r"(rowa + j * 32));
        asm volatile("ldmatrix.sync.aligned.m8n8.x2.trans.shared.b16 {%0,%1}, [%2];" : "=r"(w4), "=r"(w5) : "r"(rowb + j * 32));
        float p[4][4];
#pragma unroll
        for (int q = 0; q < 4; q++) p[q][0] = p[q][1] = p[q][2] = p[q][3] = 0.f;
        mma16816(p[0], a00, a01, a02, a03, w0, w1); mma16816(p[1], a00, a01, a02, a03, w2, w3);
        mma16816(p[2], b00, 0u, b02, 0u, w0, w1); mma16816(p[3], b00, 0u, b02, 0u, w2, w3);
        mma16816(p[0], a10, a11, 0u, 0u, w4, 0u); mma16816(p[1], a10, a11, 0u, 0u, w5, 0u);
        mma16816(p[2], b10, 0u, 0u, 0u, w4, 0u); mma16816(p[3], b10, 0u, 0u, 0u, w5, 0u);
        stsm4(rowa + j * 32, make_uint4(pack_bf16(p[0][0], p[0][1]), pack_bf16(p[0][2], p[0][3]), pack_bf16(p[1][0], p[1][1]), pack_bf16(p[1][2], p[1][3])));
        if (g < 2) {
          uint32_t* r = reinterpret_cast<uint32_t*>(smem + (hh * 18 + 16 + g) * WP + (c0 + j * 16 + 2 * t) * 2);
          r[0] = pack_bf16(p[2][0], p[2][1]); r[4] = pack_bf16(p[3][0], p[3][1]);
        }
      }
      asm volatile("fence.proxy.async.shared::cta;" ::: "memory");
      __syncwarp();
      if (lane < 18) {
        asm volatile("cp.async.bulk.global.shared::cta.bulk_group [%0], [%1], %2;" ::"l"(g_m + (a * 144 + hh * 18 + lane) * D_ + c0), "r"(sbase + (hh * 18 + lane) * WP + c0 * 2), "r"(384) : "memory");
        asm volatile("cp.async.bulk.commit_group;" ::: "memory");
      }
    }
    asm volatile("cp.async.bulk.wait_group 0;" ::: "memory");
    asm volatile("fence.proxy.async.global;" ::: "memory");
    __syncwarp();
    if (lane == 0) asm volatile("red.release.gpu.global.add.u32 [%0], 1;" ::"l"(g_f_m) : "memory");
    STAMPW(0, 3);
    __syncthreads();
    if (tid == 0) g_epoch[blockIdx.x] = ep;
    return;
  }

  const int cl = blockIdx.x >> 1, rank = blockIdx.x & 1;
  const int f = cl & 7, m = (cl >> 3) * 2 + rank;
  const int srole = f >= 6 ? 1 : 0;
  const uint32_t bar_full = sbase + SM_BAR, bar_empty = bar_full + 8 * NSTAGE, bar_xfree = bar_empty + 8 * NSTAGE, bar_ofull = bar_xfree + 72,
                 bar_d = bar_ofull + 72;

  if (tid == 0) {
#pragma unroll 1
    for (int i = 0; i < NSTAGE; i++) { mbar_init(bar_full + 8 * i, 1); mbar_init(bar_empty + 8 * i, 4); }
#pragma unroll 1
    for (int i = 0; i < 9; i++) { mbar_init(bar_xfree + 8 * i, 2); mbar_init(bar_ofull + 8 * i, 1); }
    mbar_init(bar_d, 1);
    asm volatile("fence.mbarrier_init.release.cluster;" ::: "memory");
  }
  __syncwarp();
  cluster_arrive_relaxed();

  if (warp >= 8) {
    const int srow = m * 128 + f * 16 + (warp - 8) * 4 + (lane >> 3);
    uint4 xs[9];
#pragma unroll
    for (int kb = 0; kb < 9; kb++) xs[kb] = __ldg(reinterpret_cast<const uint4*>(P.x + srow * D_) + (lane & 7) + kb * 8);
    auto stats = [&]() {
      const uint32_t* w = reinterpret_cast<const uint32_t*>(xs);
      float s0 = 0.f, s1 = 0.f;
#pragma unroll
      for (int i = 0; i < 36; i++) { s0 += bf_lo(w[i]); s1 += bf_hi(w[i]); }
      float sum = s0 + s1;
      sum += __shfl_xor_sync(0xffffffffu, sum, 1); sum += __shfl_xor_sync(0xffffffffu, sum, 2); sum += __shfl_xor_sync(0xffffffffu, sum, 4);
      const float mean = sum * (1.f / 576.f);
      s0 = 0.f; s1 = 0.f;
#pragma unroll
      for (int i = 0; i < 36; i++) { const float a = bf_lo(w[i]) - mean, b = bf_hi(w[i]) - mean; s0 = fmaf(a, a, s0); s1 = fmaf(b, b, s1); }
      float sq = s0 + s1;
      sq += __shfl_xor_sync(0xffffffffu, sq, 1); sq += __shfl_xor_sync(0xffffffffu, sq, 2); sq += __shfl_xor_sync(0xffffffffu, sq, 4);
      const float rstd = rsqrtf(sq * (1.f / 576.f) + 1e-5f);
      if ((lane & 7) == 0)
        asm volatile("{.reg .b64 a; mov.b64 a, {%1,%2}; st.relaxed.gpu.global.b64 [%0], a;}" ::"l"(&g_stat[srow]), "r"((__float_as_uint(rstd) & ~1u) | par), "r"(pack_bf16(-mean, -mean)) : "memory");
    };
    stats();
    asm volatile("setmaxnreg.dec.sync.aligned.u32 40;");
    cluster_wait();
    if (warp == 8) {
      if (lane == 0) {
        uint32_t stage = 0, phase = 1;
        const uint32_t sb = sbase + SM_B;
#pragma unroll 1
        for (int tl = 2 * srole; tl < 8 + 2 * srole; tl++) {
          const CUtensorMap* map = tl == 0 ? &P.tm_wqkv : (tl == 1 ? &P.tm_wqkv64 : (tl < 5 ? &P.tm_w1 : (tl < 8 ? &P.tm_w2 : (tl == 8 ? &P.tm_m : &P.tm_m64))));
          const int col = tl < 2 ? 288 * f + 192 * tl : (tl < 5 ? 576 * f + 192 * (tl - 2) : (tl < 8 ? 192 * (tl - 5) : (tl == 8 ? 192 * (f - 5) : 96 * (f - 6))));
          const bool perm = tl >= 5 && tl < 8;
          const bool z = (tl & 7) == 1;
          if (tl == 8) { flag_wait(g_f_m, 48 * ep); asm volatile("fence.proxy.async.global;" ::: "memory"); }
          const int cs = z ? 32 : 64, rs = z ? 64 : 32, nst = z ? 9 : 18;
#pragma unroll 1
          for (int st = 0; st < nst; st++) {
            int row = st * rs;
            if (perm) row += 576 * f + ((st < 6) ? 192 : (st < 12 ? -192 : 0));
            mbar_wait(bar_empty + 8 * stage, phase);
            mbar_expect(bar_full + 8 * stage, 12288);
            const uint32_t dst = sb + stage * STAGE_BYTES;
            if (((st ^ rank) & 1) == 0) {
              tma2d_mc(dst, map, col, row, bar_full + 8 * stage);
              tma2d_mc(dst + 8192, map, col + 2 * cs, row, bar_full + 8 * stage);
            } else {
              tma2d_mc(dst + 4096, map, col + cs, row, bar_full + 8 * stage);
            }
            if (++stage == NSTAGE) { stage = 0; phase ^= 1; }
          }
        }
      }
      __syncwarp();
    } else {
      const int aw = warp - 9;
      const int hi = f >> 2;
      if (aw == 0) {
        if (lane < 2) hint_wait(&g_f_qkv[m * 8 + 2 + 2 * lane + hi], 16 * ep, 200);
        __syncwarp();
        if (lane == 0) mbar_arrive(bar_d);
        STAMP(20);
      }
      if (lane < 5) hint_wait(lane < 4 ? &g_f_z[4 * f + lane] : &g_f_qkv[m * 8 + hi], lane < 4 ? 2 * ep : 16 * ep);
      __syncwarp();
      STAMPW(9, 22);
      uint32_t* stg = reinterpret_cast<uint32_t*>(smem + SM_SCR + aw * 2304);
#pragma unroll 1
      for (int u = aw * 2; u < 16; u += (u & 1) ? 5 : 1) {
        const int rbl = u >> 1, hp = (u & 1) * 2;
        const uint32_t* qf = reinterpret_cast<const uint32_t*>(g_qkvf) + (m * 8 + rbl) * 108 * 128 + g * 16;
        uint2 q[2][3];
        float d[4];
        int tries = 0;
        uint32_t bad;
#pragma unroll 1
        do {
          bad = tries ? ld_acquire(g_f_m) & 0u : 0u;
#pragma unroll
          for (int j = 0; j < 2; j++)
#pragma unroll
            for (int b = 0; b < 3; b++) q[j][b] = ld_ca64(qf + coloff(72 * f + (hp + j) * 18 + 8 * b + 2 * t));
#pragma unroll
          for (int j = 0; j < 2; j++) {
            const uint32_t* zp = reinterpret_cast<const uint32_t*>(&g_z[(4 * f + hp + j) * 8 + t]);
            const uint2 z0 = ld_ca64(zp), z1 = ld_ca64(zp + 2), z2 = ld_ca64(zp + 16);
            if (t != 0) q[j][2] = make_uint2(par, 0u);
            ll_chk(bad, z0.x, z1.x, par); ll_chk(bad, z2.x, q[j][2].x, par); ll_chk(bad, q[j][0].x, q[j][1].x, par);
            d[2 * j] = bf_lo(q[j][0].x) * __uint_as_float(z0.x) + bf_hi(q[j][0].x) * __uint_as_float(z0.y) + bf_lo(q[j][1].x) * __uint_as_float(z1.x) + bf_hi(q[j][1].x) * __uint_as_float(z1.y) +
                       bf_lo(q[j][2].x) * __uint_as_float(z2.x) + bf_hi(q[j][2].x) * __uint_as_float(z2.y);
            d[2 * j + 1] = bf_lo(q[j][0].y) * __uint_as_float(z0.x) + bf_hi(q[j][0].y) * __uint_as_float(z0.y) + bf_lo(q[j][1].y) * __uint_as_float(z1.x) + bf_hi(q[j][1].y) * __uint_as_float(z1.y) +
                           bf_lo(q[j][2].y) * __uint_as_float(z2.x) + bf_hi(q[j][2].y) * __uint_as_float(z2.y);
          }
        } while (__any_sync(0xffffffffu, bad & 1) && ++tries < (1 << 20));
#pragma unroll
        for (int j = 0; j < 4; j++) d[j] += __shfl_xor_sync(0xffffffffu, d[j], 1);
#pragma unroll
        for (int j = 0; j < 4; j++) d[j] = __fdividef(1.f, d[j] + __shfl_xor_sync(0xffffffffu, d[j], 2) + 1e-6f);
        if (hp == 0) { asm volatile("cp.async.bulk.wait_group.read 0;" ::: "memory"); __syncwarp(); }
#pragma unroll
        for (int j = 0; j < 2; j++) {
          const uint32_t r0 = pack_bf16(d[2 * j], d[2 * j]), r1 = pack_bf16(d[2 * j + 1], d[2 * j + 1]);
#pragma unroll
          for (int b = 0; b < 3; b++)
            if (b < 2 || t == 0) {
              stg[g * 36 + (hp + j) * 9 + 4 * b + t] = hfma2(q[j][b].x, r0, 0x80008000u);
              stg[(g + 8) * 36 + (hp + j) * 9 + 4 * b + t] = hfma2(q[j][b].y, r1, 0x80008000u);
            }
        }
        if (hp != 0) {
          asm volatile("fence.proxy.async.shared::cta;" ::: "memory");
          __syncwarp();
          if (lane < 16) {
            asm volatile("cp.async.bulk.global.shared::cta.bulk_group [%0], [%1], %2;" ::"l"(g_a + (m * 128 + rbl * 16 + lane) * D_ + 72 * f), "r"(smem_u32(stg) + lane * 144), "r"(144) : "memory");
            asm volatile("cp.async.bulk.commit_group;" ::: "memory");
          }
        }
      }
      asm volatile("cp.async.bulk.wait_group 0;" ::: "memory");
      asm volatile("fence.proxy.async.global;" ::: "memory");
      STAMPW(9, 26);
      asm volatile("bar.sync 5, 96;" ::: "memory");
      if (tid == 288) asm volatile("red.release.gpu.global.add.u32 [%0], 1;" ::"l"(&g_f_a[m]) : "memory");
      __syncwarp();
      STAMPW(9, 23);
      if (srole && aw == 2) {
        if (lane == 0) {
          flag_wait(&g_f_a[m], 8 * ep);
          asm volatile("fence.proxy.async.global;" ::: "memory");
#pragma unroll 1
          for (int kb = 0; kb < 9; kb++) {
            mbar_wait(bar_xfree + 8 * kb, 0);
            mbar_expect(bar_ofull + 8 * kb, 16384);
            tma2d(sbase + SM_A + kb * 16384, &P.tm_a, kb * 64, m * 128, bar_ofull + 8 * kb);
          }
        }
        __syncwarp();
      }
      const int rbg = m * 8 + f;
      if (lane == 0) hint_wait(&g_f_rb[rbg * 8], 8 * ep);
      __syncwarp();
      STAMPW(9, 24);
#pragma unroll 1
      for (int hv = aw * 8; hv < aw * 8 + 8; hv++) {
        const uint32_t bb = __ldg(reinterpret_cast<const uint32_t*>(P.b2 + 8 * hv + 2 * t));
        uint2 p[8];
        int tries = 0;
        uint32_t bad;
#pragma unroll 1
        do {
          bad = tries ? ld_acquire(g_f_m) & 0u : 0u;
#pragma unroll
          for (int i = 0; i < 8; i++) p[i] = ld_ca64(reinterpret_cast<const uint32_t*>(&g_part[((rbg * 8 + i) * 36 + (hv >> 1)) * 32 + lane]) + (hv & 1) * 2);
#pragma unroll
          for (int i = 0; i < 8; i += 2) ll_chk(bad, p[i].x, p[i + 1].x, par);
        } while (__any_sync(0xffffffffu, bad & 1) && ++tries < (1 << 20));
        const uint32_t g0 = gate_word(p[0].x, p[1].x, p[2].x, p[3].x, p[4].x, p[5].x, p[6].x, p[7].x, bb), g1 = gate_word(p[0].y, p[1].y, p[2].y, p[3].y, p[4].y, p[5].y, p[6].y, p[7].y, bb);
        asm volatile("{.reg .b64 a; mov.b64 a, {%1,%2}; st.relaxed.gpu.global.b64 [%0], a;}" ::"l"(reinterpret_cast<uint32_t*>(&g_g[(rbg * 12 + (hv >> 1)) * 32 + lane]) + (hv & 1) * 2), "r"(tag(g0, par)), "r"(g1) : "memory");
      }
      STAMPW(9, 25);
    }
    cluster_arrive_relaxed();
    cluster_wait();
  } else {
    const int wg = warp >> 2;
    {
      const int rs = lane >> 3, j = lane & 7;
      uint4 xv[4][9];
#pragma unroll
      for (int it = 0; it < 4; it++)
#pragma unroll
        for (int kb = 0; kb < 9; kb++) xv[it][kb] = __ldg(reinterpret_cast<const uint4*>(P.x + (m * 128 + warp * 16 + it * 4 + rs) * D_) + j + kb * 8);
      uint32_t bw0 = __ldg(reinterpret_cast<const uint32_t*>(P.b1 + 576 * f) + tid), bw1 = tid < 32 ? __ldg(reinterpret_cast<const uint32_t*>(P.b1 + 576 * f) + 256 + tid) : 0u;
      uint2 st[4];
      int tries = 0;
      uint32_t bad;
#pragma unroll 1
      do {
        bad = 0;
#pragma unroll
        for (int it = 0; it < 4; it++) st[it] = ld_ll64(reinterpret_cast<const uint32_t*>(&g_stat[m * 128 + warp * 16 + it * 4 + rs]));
        ll_chk(bad, st[0].x, st[1].x, par); ll_chk(bad, st[2].x, st[3].x, par);
      } while (__any_sync(0xffffffffu, bad & 1) && ++tries < (1 << 22));
      STAMPW(0, 19);
#pragma unroll
      for (int it = 0; it < 4; it++) {
        const uint32_t nm = st[it].y;
        uint8_t* dst = smem + SM_A + (warp * 16 + it * 4 + rs) * 128 + ((j ^ ((it * 4 + rs) & 7)) << 4);
#pragma unroll
        for (int kb = 0; kb < 9; kb++) {
          const uint4 w = xv[it][kb];
          *reinterpret_cast<uint4*>(dst + kb * 16384) = make_uint4(hadd2(w.x, nm), hadd2(w.y, nm), hadd2(w.z, nm), hadd2(w.w, nm));
        }
        if (j == 0) reinterpret_cast<uint32_t*>(smem + SM_RSTD)[warp * 16 + it * 4 + rs] = st[it].x;
      }
      reinterpret_cast<float2*>(smem + SM_BIAS)[tid] = make_float2(bf_lo(bw0) * GK, bf_hi(bw0) * GK);
      if (tid < 32) reinterpret_cast<float2*>(smem + SM_BIAS)[256 + tid] = make_float2(bf_lo(bw1) * GK, bf_hi(bw1) * GK);
      asm volatile("fence.proxy.async.shared::cta;" ::: "memory");
    }
    asm volatile("setmaxnreg.inc.sync.aligned.u32 232;");
    cluster_wait();
    asm volatile("bar.sync 1, 256;" ::: "memory");
    STAMPW(0, 1);
    Ctx c;
    c.full = bar_full;
    c.emb = __shfl_sync(0xffffffffu, mapa(bar_empty, (warp & 3) == 0 ? rank : (rank ^ 1)), 0);
    c.sig = lane == 0 && (warp & 3) < 2;
    c.stage = 0; c.phase = 0; c.prev = ~0u;
    c.dB = (((sbase + SM_B) & 0x3FFFF) >> 4) | ((4096u >> 4) << 16);
    c.dA = (((sbase + SM_A + wg * 8192) & 0x3FFFF) >> 4) | (1u << 16);
    const bool leader = (lane == 0) && ((warp & 3) == 0);

    const int rb = m * 8 + warp;
    const uint32_t bias_t = sbase + SM_BIAS + 8 * t;
    const uint32_t hst = sbase + SM_A + (warp * 16 + (lane & 7) + ((lane >> 3) & 1) * 8) * 128 + (((lane >> 4) ^ (lane & 7)) << 4);
    auto wg_sync = [&]() {
      asm volatile("fence.proxy.async.shared::cta;" ::: "memory");
      if (wg == 0) asm volatile("bar.sync 2, 128;" ::: "memory"); else asm volatile("bar.sync 3, 128;" ::: "memory");
    };
    float A[96], B[96];
#pragma unroll
    for (int i = 0; i < 96; i++) B[i] = 0.f;
#define GELU16(H0, H1, ACC, OFF) uint32_t E[8]; \
    _Pragma("unroll") for (int q = 0; q < 8; q++) E[q] = pack_bf16(fmaf(ACC[(OFF) + 2 * q], (q & 1) ? r1 : r0, bs[q >> 1].x), fmaf(ACC[(OFF) + 2 * q + 1], (q & 1) ? r1 : r0, bs[q >> 1].y)); \
    const uint4 H0 = gelu_group(E), H1 = gelu_group(E + 4);
#define SPART16(DST, ACC, OFF) { uint32_t E[8]; _Pragma("unroll") for (int q = 0; q < 8; q++) E[q] = pack_bf16(ACC[(OFF) + 2 * q] * ((q & 1) ? r1 : r0), ACC[(OFF) + 2 * q + 1] * ((q & 1) ? r1 : r0)); \
    if (f < 4) { const float l0 = r0 * 1.4426950408889634f, l1 = r1 * 1.4426950408889634f; \
      _Pragma("unroll") for (int q = 0; q < 8; q++) E[q] = phi_pack(E[q], ACC[(OFF) + 2 * q] * ((q & 1) ? l1 : l0), ACC[(OFF) + 2 * q + 1] * ((q & 1) ? l1 : l0)); } \
    st_ll(DST, E[0], E[1], E[2], E[3], par); st_ll(DST + 32, E[4], E[5], E[6], E[7], par); }
#define LDS_R(SC) float r0, r1; asm volatile("ld.shared.f32 %0, [%1];" : "=f"(r0) : "r"(rst)); asm volatile("ld.shared.f32 %0, [%1];" : "=f"(r1) : "r"(rst + 32)); r0 *= (SC); r1 *= (SC);
    const uint32_t rst = sbase + SM_RSTD + (warp * 16 + g) * 4;
#pragma unroll 1
    for (int i = srole; i < 4 + srole; i++) {
      {
        const uint32_t ow = i == 4 ? bar_ofull : 0u;
        if (ow) mbar_wait(ow, 0);
        issue192(A, c, 0, true);
        const int ln = opaque(lane);
        uint4* dst = i == 1 ? g_qkvf + (rb * 108 + 18 * f + 12) * 32 + ln : g_part + ((rb * 8 + f) * 36 + (i == 3 ? 0 : 24)) * 32 + ln;
        LDS_R(i == 2 ? GK : 1.f)
        retire(c);
        if (ow && leader) mbar_arrive(bar_xfree + 64);
        fence_regs<96>(B);
        int s = 1;
        if (i == 2) {
#pragma unroll 1
          for (; s < 3; s++) { issue192(A, c, s); retire(c); }
        }
        if (i > srole) {
#pragma unroll
          for (int u = 0; u < 6; u++, s++) {
            float2 bs[4];
            if (i == 2) lds_bias(bs, bias_t + (192 + 32 * u) * 4);
            if ((u & 1) && ow) mbar_wait(ow + 4 * s, 0);
            issue192(A, c, s);
            if (i == 2) {
              GELU16(h0, h1, B, 16 * u)
              stsm4((hst ^ ((2 * u & 3) << 5)) + (u >> 1) * 16384, h0);
              stsm4((hst ^ ((2 * u + 1 & 3) << 5)) + (u >> 1) * 16384, h1);
            } else if (i == 1) {
              if (u < 3) SPART16(dst + 2 * u * 32, B, 16 * u)
              if (u == 2) hint_signal(&g_f_qkv[m * 8 + f]);
            } else {
              part_groups<0, 2>(&B[16 * u], dst + 2 * u * 32, par);
              if (u == 5) hint_signal(&g_f_rb[rb * 8 + (i == 3 ? 0 : 2)]);
            }
            retire(c);
          }
        }
        const bool d1 = i == 1 + srole;
        const int send = d1 ? 10 : 15;
#pragma unroll 1
        for (; s < send; s++) {
          if (ow && !(s & 1)) mbar_wait(ow + 4 * s, 0);
          issue192(A, c, s);
          retire(c);
        }
        uint32_t W[48];
        if (d1) {
          const int head = 4 * f + (warp >> 1), rb0 = m * 8 + (warp & 1) * 4;
          issue192(A, c, 10);
          mbar_wait(bar_d, 0);
          d1_load<false>(W, rb0, head, opaque(lane));
          retire(c);
#pragma unroll 1
          for (s = 11; s < 13; s++) { issue192(A, c, s); retire(c); }
          issue192(A, c, 13);
          int tries = 0;
#pragma unroll 1
          while (d1_bad(W, t, par) && ++tries < (1 << 20)) d1_load<true>(W, rb0, head, opaque(lane));
          d1_mov(W, 0, t); d1_mov(W, 1, t);
          retire(c);
          issue192(A, c, 14);
          d1_mov(W, 2, t); d1_mov(W, 3, t);
          wg_wait<0>();
          asm volatile("bar.sync 4, 256;" ::: "memory");
          float R[18];
          d1_mma(W, R);
          float2* xch = reinterpret_cast<float2*>(smem + SM_SCR + (warp >> 1) * 1792) + opaque(lane);
          if (warp & 1) {
#pragma unroll
            for (int q = 0; q < 6; q++) xch[q * 32] = make_float2(R[2 * q], R[2 * q + 1]);
            if (lane < 12) { xch[192] = make_float2(R[12], R[13]); xch[204] = make_float2(R[14], R[15]); if (t == 0) xch[216 - lane + g] = make_float2(R[16], R[17]); }
          } else if (R[17] == 1.2345e-30f) R[16] = 0.f;
          asm volatile("bar.sync 4, 256;" ::: "memory");
          retire(c);
          issue192(A, c, 15);
          if (!(warp & 1)) {
            const int ln = opaque(lane);
#pragma unroll
            for (int q = 0; q < 6; q++) { const float2 o = xch[q * 32]; R[2 * q] += o.x; R[2 * q + 1] += o.y; }
            if (ln < 12) {
              const float2 o0 = xch[192], o1 = xch[204], o2 = xch[216 - ln + (ln >> 2)];
              R[12] += o0.x; R[13] += o0.y; R[14] += o1.x; R[15] += o1.y; R[16] += o2.x; R[17] += o2.y;
            }
            uint4* dkv = &g_kvp[(head * 80 + m) * 32 + ln];
#pragma unroll
            for (int w = 0; w < 5; w++)
              if (kv_valid(w, ln)) st_ll(dkv + w * 512, __float_as_uint(R[4 * w]), __float_as_uint(R[4 * w + 1]), w < 4 ? __float_as_uint(R[4 * w + 2]) : 0u, w < 4 ? __float_as_uint(R[4 * w + 3]) : 0u, par);
            __syncwarp();
            hint_signal(&g_f_kvp[head]);
          }
          STAMPW(0, 21);
        } else issue192(A, c, 15);
        if (i == 2) {
          const uint4* hsp = g_hsp + (blockIdx.x * 8 + warp) * 12 * 32 + opaque(lane);
#pragma unroll
          for (int q = 0; q < 12; q++) { const uint4 v = ldcg128(hsp + q * 32); W[4 * q] = v.x; W[4 * q + 1] = v.y; W[4 * q + 2] = v.z; W[4 * q + 3] = v.w; }
        } else {
#pragma unroll
          for (int q = 0; q < 48; q++) W[q] = 0;
        }
        retire(c);
        if (ow) mbar_wait(ow + 64, 0);
        issue192(A, c, 16);
        if (i == 2) wg_sync();
        retire(c);
        issue192(A, c, 17);
        if (i == 2) {
#pragma unroll
          for (int q = 0; q < 12; q++) stsm4((hst ^ ((q & 3) << 5)) + (3 + (q >> 2)) * 16384, make_uint4(W[4 * q], W[4 * q + 1], W[4 * q + 2], W[4 * q + 3]));
        }
        retire(c);
      }
      STAMPW(0, 2 + 2 * i);
      if ((i & 3) == 0) {
        issue96(B, c, 0, true);
        const int ln = opaque(lane);
        uint4* dst = i == 0 ? g_qkvf + (rb * 108 + 18 * f) * 32 + ln : g_s + (rb * 24 + 12 * (f - 6)) * 32 + ln;
        LDS_R(1.f)
        if (i != 0) { r0 = 1.f; r1 = 1.f; }
        retire(c);
        fence_regs<96>(A);
#pragma unroll
        for (int u = 0; u < 8; u++) {
          issue96(B, c, u + 1, false);
          if (u < 6) SPART16(dst + 2 * u * 32, A, 16 * (u < 6 ? u : 0))
          if (u == 5 && i == 0) hint_signal(&g_f_qkv[m * 8 + f]);
          retire(c);
        }
      } else {
        issue192(B, c, 0, true);
        const int ln = opaque(lane);
        uint4* dst = i == 1 ? g_hsp + (blockIdx.x * 8 + warp) * 12 * 32 + ln : g_part + ((rb * 8 + f) * 36 + 12) * 32 + ln;
        const bool xf = i == 3 && srole && leader;
        const uint32_t bsa = bias_t + (i == 1 ? 0 : 384) * 4;
        LDS_R(GK)
        retire(c);
        fence_regs<96>(A);
#pragma unroll
        for (int u = 0; u < 6; u++) {
          float2 bs[4];
          if (i != 3) lds_bias(bs, bsa + 32 * u * 4);
          issue192(B, c, u + 1);
          if (i != 3) {
            GELU16(h0, h1, A, 16 * u)
            if (i == 1) { dst[2 * u * 32] = h0; dst[(2 * u + 1) * 32] = h1; }
            else {
              stsm4((hst ^ ((2 * u & 3) << 5)) + (6 + (u >> 1)) * 16384, h0);
              stsm4((hst ^ ((2 * u + 1 & 3) << 5)) + (6 + (u >> 1)) * 16384, h1);
              if (u == 3) wg_sync();
            }
          } else {
            part_groups<0, 2>(&A[16 * u], dst + 2 * u * 32, par);
          }
          retire(c);
          if ((u & 1) && xf) mbar_arrive(bar_xfree + 4 * u - 4);
        }
#pragma unroll 1
        for (int s = 7; s < 17; s++) {
          issue192(B, c, s);
          if (s == 9 && i == 2) wg_sync();
          retire(c);
          if ((s & 1) == 0 && xf) mbar_arrive(bar_xfree + 4 * s - 8);
        }
        issue192(B, c, 17);
        retire(c);
      }
      STAMPW(0, 3 + 2 * i);
    }

    const int ln = opaque(lane);
    const __nv_bfloat16* xp = P.x + (rb * 16 + (ln >> 2)) * D_ + 2 * (ln & 3);
    __nv_bfloat16* op = P.out + (rb * 16 + (ln >> 2)) * D_ + 2 * (ln & 3);
    auto ldx = [&](uint32_t* xx, int col) {
      xx[0] = __ldg(reinterpret_cast<const uint32_t*>(xp + col)); xx[1] = __ldg(reinterpret_cast<const uint32_t*>(xp + 8 * D_ + col));
      xx[2] = __ldg(reinterpret_cast<const uint32_t*>(xp + col + 8)); xx[3] = __ldg(reinterpret_cast<const uint32_t*>(xp + 8 * D_ + col + 8));
    };
    auto stout = [&](int col, uint4 sv, uint4 gv, const uint32_t* xx) {
      *reinterpret_cast<uint32_t*>(op + col) = hfma2(sv.x, gv.x, xx[0]); *reinterpret_cast<uint32_t*>(op + 8 * D_ + col) = hfma2(sv.y, gv.y, xx[1]);
      *reinterpret_cast<uint32_t*>(op + col + 8) = hfma2(sv.z, gv.z, xx[2]); *reinterpret_cast<uint32_t*>(op + 8 * D_ + col + 8) = hfma2(sv.w, gv.w, xx[3]);
    };
    if (srole) {
      const int cb = 96 * (f - 6);
      uint32_t xx[24];
      uint4 gg[6];
#pragma unroll
      for (int q = 0; q < 6; q++) ldx(&xx[4 * q], cb + 16 * q);
      int tries = 0;
      uint32_t bad;
#pragma unroll 1
      do {
        bad = 0;
#pragma unroll
        for (int q = 0; q < 6; q++) gg[q] = ld_ll(&g_g[(rb * 12 + 6 * (f - 6) + q) * 32 + ln]);
#pragma unroll
        for (int q = 0; q < 6; q++) ll_chk(bad, gg[q].x, gg[q].z, par);
      } while (__any_sync(0xffffffffu, bad & 1) && ++tries < (1 << 20));
      STAMPW(0, 14);
      wg_wait<0>();
      c.release_prev();
      fence_regs<48>(B);
#pragma unroll
      for (int q = 0; q < 6; q++)
        stout(cb + 16 * q, make_uint4(pack_bf16(B[8 * q], B[8 * q + 1]), pack_bf16(B[8 * q + 2], B[8 * q + 3]), pack_bf16(B[8 * q + 4], B[8 * q + 5]), pack_bf16(B[8 * q + 6], B[8 * q + 7])), gg[q], &xx[4 * q]);
    } else {
      wg_wait<0>();
      c.release_prev();
      fence_regs<96>(B);
      part_groups<0, 12>(B, g_part + ((rb * 8 + f) * 36 + 24) * 32 + ln, par);
      hint_signal(&g_f_rb[rb * 8 + 2]);
      STAMPW(0, 12);
#pragma unroll 1
      for (int ch = 1; ch < 3; ch++) {
        const int cb = 192 * ch + 32 * f;
        uint32_t xx[8], bb[4];
        ldx(xx, cb); ldx(xx + 4, cb + 16);
#pragma unroll
        for (int j = 0; j < 4; j++) bb[j] = __ldg(reinterpret_cast<const uint32_t*>(P.b2 + cb + 8 * j + 2 * (ln & 3)));
        if (ln == 0 && ch == 2) hint_wait(&g_f_rb[rb * 8 + 2], 8u * ep, 20);
        __syncwarp();
        STAMPW(0, 12 + ch);
        uint4 p[2][8], sv[2];
        int tries = 0;
        uint32_t bad;
#pragma unroll 1
        do {
          bad = 0;
#pragma unroll
          for (int j = 0; j < 2; j++) {
#pragma unroll
            for (int k = 0; k < 8; k++) p[j][k] = ld_ll(&g_part[((rb * 8 + k) * 36 + 12 * ch + 2 * f + j) * 32 + ln]);
            sv[j] = ld_ll(&g_s[(rb * 24 + 12 * (ch - 1) + 2 * f + j) * 32 + ln]);
          }
#pragma unroll
          for (int j = 0; j < 2; j++) {
#pragma unroll
            for (int k = 0; k < 8; k++) ll_chk(bad, p[j][k].x, p[j][k].z, par);
            ll_chk(bad, sv[j].x, sv[j].z, par);
          }
        } while (__any_sync(0xffffffffu, bad & 1) && ++tries < (1 << 20));
#pragma unroll
        for (int j = 0; j < 2; j++) stout(cb + 16 * j, sv[j], gate_vec(p[j], bb[2 * j], bb[2 * j + 1]), &xx[4 * j]);
      }
    }
    STAMPW(0, 15);
    cluster_arrive_relaxed();
    cluster_wait();
    STAMPW(0, 16);
    if (tid == 0) g_epoch[blockIdx.x] = ep;
  }
}

typedef CUresult (*EncFn)(CUtensorMap*, CUtensorMapDataType, cuuint32_t, void*, const cuuint64_t*, const cuuint64_t*, const cuuint32_t*, const cuuint32_t*,
                          CUtensorMapInterleave, CUtensorMapSwizzle, CUtensorMapL2promotion, CUtensorMapFloatOOBfill);

void make_map(EncFn enc, CUtensorMap* tm, const void* ptr, int rows, int cols, int box_rows, bool sw64 = false) {
  cuuint64_t gd[2] = {(cuuint64_t)cols, (cuuint64_t)rows};
  cuuint64_t gs[1] = {(cuuint64_t)cols * 2};
  cuuint32_t bx[2] = {sw64 ? 32u : 64u, (cuuint32_t)box_rows};
  cuuint32_t es[2] = {1, 1};
  enc(tm, CU_TENSOR_MAP_DATA_TYPE_BFLOAT16, 2, const_cast<void*>(ptr), gd, gs, bx, es, CU_TENSOR_MAP_INTERLEAVE_NONE, sw64 ? CU_TENSOR_MAP_SWIZZLE_64B : CU_TENSOR_MAP_SWIZZLE_128B,
      CU_TENSOR_MAP_L2_PROMOTION_L2_256B, CU_TENSOR_MAP_FLOAT_OOB_FILL_NONE);
}

}

extern "C" void kernel_launch(void* const* d_in, const int* in_sizes, int n_in, void* d_out, int out_size) {
  (void)in_sizes; (void)n_in; (void)out_size;
  static EncFn enc = nullptr;
  static void *a_ptr = nullptr, *m_ptr = nullptr;
  if (!enc) {
    void* fn = nullptr; cudaDriverEntryPointQueryResult q;
    cudaGetDriverEntryPoint("cuTensorMapEncodeTiled", &fn, cudaEnableDefault, &q);
    enc = (EncFn)fn;
    cudaFuncSetAttribute(fused_kernel, cudaFuncAttributeMaxDynamicSharedMemorySize, SMEM_BYTES);
    cudaGetSymbolAddress(&a_ptr, g_a);
    cudaGetSymbolAddress(&m_ptr, g_m);
  }
  Params P;
  P.x = (const __nv_bfloat16*)d_in[0];
  P.wqkv = (const __nv_bfloat16*)d_in[1];
  P.wo = (const __nv_bfloat16*)d_in[2];
  P.w1 = (const __nv_bfloat16*)d_in[4];
  P.b1 = (const __nv_bfloat16*)d_in[5];
  P.w2 = (const __nv_bfloat16*)d_in[6];
  P.b2 = (const __nv_bfloat16*)d_in[7];
  P.out = (__nv_bfloat16*)d_out;
  make_map(enc, &P.tm_wqkv, P.wqkv, D_, Q3_, 32);
  make_map(enc, &P.tm_w1, P.w1, D_, F_, 32);
  make_map(enc, &P.tm_w2, P.w2, F_, D_, 32);
  make_map(enc, &P.tm_m, m_ptr, D_, D_, 32);
  make_map(enc, &P.tm_wqkv64, P.wqkv, D_, Q3_, 64, true);
  make_map(enc, &P.tm_m64, m_ptr, D_, D_, 64, true);
  make_map(enc, &P.tm_a, a_ptr, S_, D_, 128);
  fused_kernel<<<NCTAS, NTHREADS, SMEM_BYTES, cudaStreamPerThread>>>(P);
}
```

```cpp
#include <cuda_runtime.h>
#include <cuda.h>
#include <cuda_bf16.h>
#include <stdint.h>

namespace {

constexpr int S_ = 2048, D_ = 576, F_ = 4608, Q3_ = 1728;
constexpr int NSTAGE = 6, STAGE_BYTES = 12288;
constexpr int SM_A = 0, SM_B = 147456, SM_BIAS = SM_B + NSTAGE * STAGE_BYTES, SM_RSTD = SM_BIAS + 2304, SM_SCR = SM_RSTD + 512, SM_BAR = SM_SCR + 7168;
constexpr int SMEM_BYTES = SM_BAR + 320;
constexpr int NTHREADS = 384;
constexpr int NCTAS = 132;

__device__ uint2 g_qkv[128 * 8 * 864 + 8];
__device__ __align__(1024) __nv_bfloat16 g_a[S_ * D_];
__device__ __align__(1024) __nv_bfloat16 g_m[D_ * D_];
__device__ uint4 g_kvp[32 * 5 * 16 * 32];
__device__ uint4 g_z[32 * 2 * 4];
__device__ uint4 g_part[128 * 8 * 36 * 32];
__device__ uint4 g_s[128 * 24 * 32];
__device__ uint4 g_g[128 * 12 * 32];
__device__ uint4 g_hsp[128 * 12 * 256];
__device__ uint32_t g_f_qkv[16 * 8];
__device__ uint32_t g_f_kvp[32];
__device__ uint32_t g_f_z[32];
__device__ uint32_t g_f_a[16];
__device__ uint32_t g_f_m[1];
__device__ uint32_t g_f_rb[128 * 8];
__device__ uint2 g_stat[S_];
__device__ uint32_t g_epoch[NCTAS];

#define STAMP(i)
#define STAMPW(w, i)
#define WSTAMP(i)
__device__ __forceinline__ uint32_t smem_u32(const void* p) { return (uint32_t)__cvta_generic_to_shared(p); }
__device__ __forceinline__ void mbar_init(uint32_t a, int c) { asm volatile("mbarrier.init.shared::cta.b64 [%0], %1;" ::"r"(a), "r"(c)); }
__device__ __forceinline__ void mbar_expect(uint32_t a, uint32_t b) { asm volatile("mbarrier.arrive.expect_tx.shared::cta.b64 _, [%0], %1;" ::"r"(a), "r"(b) : "memory"); }
__device__ __forceinline__ void mbar_arrive(uint32_t a) { asm volatile("mbarrier.arrive.shared::cta.b64 _, [%0];" ::"r"(a) : "memory"); }
__device__ __forceinline__ void mbar_arrive_cl(uint32_t a) { asm volatile("mbarrier.arrive.shared::cluster.b64 _, [%0];" ::"r"(a) : "memory"); }
__device__ __forceinline__ uint32_t mapa(uint32_t a, uint32_t cta) { uint32_t r; asm volatile("mapa.shared::cluster.u32 %0, %1, %2;" : "=r"(r) : "r"(a), "r"(cta)); return r; }
__device__ __forceinline__ void mbar_wait(uint32_t a, uint32_t ph) {
  uint32_t ok; int it = 0;
#pragma unroll 1
  do {
    asm volatile("{.reg .pred p; mbarrier.try_wait.parity.shared::cta.b64 p, [%1], %2; selp.u32 %0,1,0,p;}" : "=r"(ok) : "r"(a), "r"(ph) : "memory");
  } while (!ok && ++it < (1 << 18));
}
__device__ __forceinline__ void tma2d(uint32_t dst, const CUtensorMap* m, int c0, int c1, uint32_t bar) {
  asm volatile("cp.async.bulk.tensor.2d.shared::cluster.global.mbarrier::complete_tx::bytes [%0], [%1, {%3,%4}], [%2];" ::"r"(dst), "l"(m), "r"(bar), "r"(c0), "r"(c1) : "memory");
}
__device__ __forceinline__ void tma2d_mc(uint32_t dst, const CUtensorMap* m, int c0, int c1, uint32_t bar) {
  asm volatile("cp.async.bulk.tensor.2d.shared::cluster.global.mbarrier::complete_tx::bytes.multicast::cluster [%0], [%1, {%3,%4}], [%2], %5;" ::"r"(dst), "l"(m), "r"(bar), "r"(c0), "r"(c1), "h"((uint16_t)3) : "memory");
}
__device__ __forceinline__ void cluster_arrive_relaxed() { asm volatile("barrier.cluster.arrive.relaxed.aligned;" ::: "memory"); }
__device__ __forceinline__ void cluster_wait() { asm volatile("barrier.cluster.wait.acquire.aligned;" ::: "memory"); }
__device__ __forceinline__ void wg_fence() { asm volatile("wgmma.fence.sync.aligned;" ::: "memory"); }
__device__ __forceinline__ void wg_commit() { asm volatile("wgmma.commit_group.sync.aligned;" ::: "memory"); }
template <int n> __device__ __forceinline__ void wg_wait() { asm volatile("wgmma.wait_group.sync.aligned %0;" ::"n"(n) : "memory"); }
__device__ __forceinline__ uint32_t ld_acquire(const uint32_t* p) { uint32_t v; asm volatile("ld.acquire.gpu.global.u32 %0, [%1];" : "=r"(v) : "l"(p) : "memory"); return v; }
__device__ __forceinline__ void flag_wait(const uint32_t* p, uint32_t target) {
  int it = 0;
#pragma unroll 1
  while ((int)(ld_acquire(p) - target) < 0 && ++it < (1 << 20)) __nanosleep(300);
}
__device__ __forceinline__ void hint_signal(uint32_t* p) {
  if ((threadIdx.x & 31) == 0) asm volatile("red.relaxed.gpu.global.add.u32 [%0], 1;" ::"l"(p) : "memory");
}
__device__ __forceinline__ void hint_wait(const uint32_t* p, uint32_t target, uint32_t ns = 400) {
  int it = 0; uint32_t v;
#pragma unroll 1
  do { asm volatile("ld.relaxed.gpu.global.u32 %0, [%1];" : "=r"(v) : "l"(p) : "memory"); if ((int)(v - target) >= 0) break; __nanosleep(ns); } while (++it < (1 << 20));
}
__device__ __forceinline__ uint32_t tag(uint32_t x, uint32_t par) { uint32_t r; asm("lop3.b32 %0, %1, 0xfffffffe, %2, 0xea;" : "=r"(r) : "r"(x), "r"(par)); return r; }
__device__ __forceinline__ void st_ll(uint4* p, uint32_t x, uint32_t y, uint32_t z, uint32_t w, uint32_t par) {
  asm volatile("{.reg .b64 a, b; mov.b64 a, {%1,%2}; mov.b64 b, {%3,%4}; st.relaxed.gpu.global.v2.b64 [%0], {a, b};}"
               ::"l"(p), "r"(tag(x, par)), "r"(y), "r"(tag(z, par)), "r"(w) : "memory");
}
__device__ __forceinline__ uint4 ld_ll(const uint4* p) {
  uint4 v;
  asm volatile("{.reg .b64 a, b; ld.relaxed.gpu.global.v2.b64 {a, b}, [%4]; mov.b64 {%0,%1}, a; mov.b64 {%2,%3}, b;}"
               : "=r"(v.x), "=r"(v.y), "=r"(v.z), "=r"(v.w) : "l"(p) : "memory");
  return v;
}
__device__ __forceinline__ void st_ll64(uint2* p, uint32_t x, uint32_t y, uint32_t par) {
  asm volatile("{.reg .b64 a; mov.b64 a, {%1,%2}; st.relaxed.gpu.global.b64 [%0], a;}" ::"l"(p), "r"(tag(x, par)), "r"(y) : "memory");
}
__device__ __forceinline__ uint2 ld_ca64(const void* p) {
  uint2 v;
  asm volatile("{.reg .b64 a; ld.global.ca.b64 a, [%2]; mov.b64 {%0,%1}, a;}" : "=r"(v.x), "=r"(v.y) : "l"(p) : "memory");
  return v;
}
__device__ __forceinline__ uint2 ld_ll64(const void* p) {
  uint2 v;
  asm volatile("{.reg .b64 a; ld.relaxed.gpu.global.b64 a, [%2]; mov.b64 {%0,%1}, a;}" : "=r"(v.x), "=r"(v.y) : "l"(p) : "memory");
  return v;
}
__device__ __forceinline__ void ll_chk(uint32_t& bad, uint32_t a, uint32_t b, uint32_t par) {
  uint32_t u; asm("lop3.b32 %0, %1, %2, %3, 0x7e;" : "=r"(u) : "r"(a), "r"(b), "r"(par));
  asm("or.b32 %0, %0, %1;" : "+r"(bad) : "r"(u));
}
__device__ __forceinline__ uint32_t hadd2(uint32_t a, uint32_t b) { uint32_t d; asm("add.rn.bf16x2 %0, %1, %2;" : "=r"(d) : "r"(a), "r"(b)); return d; }
__device__ __forceinline__ uint32_t hfma2(uint32_t a, uint32_t b, uint32_t c) { uint32_t d; asm("fma.rn.bf16x2 %0, %1, %2, %3;" : "=r"(d) : "r"(a), "r"(b), "r"(c)); return d; }
__device__ __forceinline__ uint32_t pack_bf16(float lo, float hi) { uint32_t r; asm("cvt.rn.bf16x2.f32 %0, %1, %2;" : "=r"(r) : "f"(hi), "f"(lo)); return r; }
__device__ __forceinline__ float bf_lo(uint32_t v) { return __uint_as_float(v << 16); }
__device__ __forceinline__ float bf_hi(uint32_t v) { return __uint_as_float(v & 0xffff0000u); }
__device__ __forceinline__ uint32_t movmat(uint32_t a) { uint32_t d; asm volatile("movmatrix.sync.aligned.m8n8.trans.b16 %0, %1;" : "=r"(d) : "r"(a)); return d; }
__device__ __forceinline__ void mma16816(float* c, uint32_t a0, uint32_t a1, uint32_t a2, uint32_t a3, uint32_t b0, uint32_t b1) {
  asm volatile("mma.sync.aligned.m16n8k16.row.col.f32.bf16.bf16.f32 {%0,%1,%2,%3}, {%4,%5,%6,%7}, {%8,%9}, {%0,%1,%2,%3};"
               : "+f"(c[0]), "+f"(c[1]), "+f"(c[2]), "+f"(c[3]) : "r"(a0), "r"(a1), "r"(a2), "r"(a3), "r"(b0), "r"(b1));
}
__device__ __forceinline__ uint4 ldcg128(const void* p) { uint4 v; asm volatile("ld.global.cg.v4.u32 {%0,%1,%2,%3}, [%4];" : "=r"(v.x), "=r"(v.y), "=r"(v.z), "=r"(v.w) : "l"(p) : "memory"); return v; }

template <int N> __device__ __forceinline__ void wgmma_ss(float* d, uint64_t da, uint64_t db, int sc);
template <int N> __device__ __forceinline__ void wgmma_rs(float* d, const uint32_t* a, uint64_t db, int sc);
template <> __device__ __forceinline__ void wgmma_ss<96>(float* d, uint64_t da, uint64_t db, int sc) {
  asm volatile("{.reg .pred p; setp.ne.b32 p, %50, 0; wgmma.mma_async.sync.aligned.m64n96k16.f32.bf16.bf16 {%0, %1, %2, %3, %4, %5, %6, %7, %8, %9, %10, %11, %12, %13, %14, %15, %16, %17, %18, %19, %20, %21, %22, %23, %24, %25, %26, %27, %28, %29, %30, %31, %32, %33, %34, %35, %36, %37, %38, %39, %40, %41, %42, %43, %44, %45, %46, %47}, %48, %49, p, 1, 1, 0, 1;}"
   : "+f"(d[0]), "+f"(d[1]), "+f"(d[2]), "+f"(d[3]), "+f"(d[4]), "+f"(d[5]), "+f"(d[6]), "+f"(d[7]), "+f"(d[8]), "+f"(d[9]), "+f"(d[10]), "+f"(d[11]), "+f"(d[12]), "+f"(d[13]), "+f"(d[14]), "+f"(d[15]), "+f"(d[16]), "+f"(d[17]), "+f"(d[18]), "+f"(d[19]), "+f"(d[20]), "+f"(d[21]), "+f"(d[22]), "+f"(d[23]), "+f"(d[24]), "+f"(d[25]), "+f"(d[26]), "+f"(d[27]), "+f"(d[28]), "+f"(d[29]), "+f"(d[30]), "+f"(d[31]), "+f"(d[32]), "+f"(d[33]), "+f"(d[34]), "+f"(d[35]), "+f"(d[36]), "+f"(d[37]), "+f"(d[38]), "+f"(d[39]), "+f"(d[40]), "+f"(d[41]), "+f"(d[42]), "+f"(d[43]), "+f"(d[44]), "+f"(d[45]), "+f"(d[46]), "+f"(d[47]) : "l"(da), "l"(db), "r"(sc));
}
template <> __device__ __forceinline__ void wgmma_ss<192>(float* d, uint64_t da, uint64_t db, int sc) {
  asm volatile("{.reg .pred p; setp.ne.b32 p, %98, 0; wgmma.mma_async.sync.aligned.m64n192k16.f32.bf16.bf16 {%0, %1, %2, %3, %4, %5, %6, %7, %8, %9, %10, %11, %12, %13, %14, %15, %16, %17, %18, %19, %20, %21, %22, %23, %24, %25, %26, %27, %28, %29, %30, %31, %32, %33, %34, %35, %36, %37, %38, %39, %40, %41, %42, %43, %44, %45, %46, %47, %48, %49, %50, %51, %52, %53, %54, %55, %56, %57, %58, %59, %60, %61, %62, %63, %64, %65, %66, %67, %68, %69, %70, %71, %72, %73, %74, %75, %76, %77, %78, %79, %80, %81, %82, %83, %84, %85, %86, %87, %88, %89, %90, %91, %92, %93, %94, %95}, %96, %97, p, 1, 1, 0, 1;}"
   : "+f"(d[0]), "+f"(d[1]), "+f"(d[2]), "+f"(d[3]), "+f"(d[4]), "+f"(d[5]), "+f"(d[6]), "+f"(d[7]), "+f"(d[8]), "+f"(d[9]), "+f"(d[10]), "+f"(d[11]), "+f"(d[12]), "+f"(d[13]), "+f"(d[14]), "+f"(d[15]), "+f"(d[16]), "+f"(d[17]), "+f"(d[18]), "+f"(d[19]), "+f"(d[20]), "+f"(d[21]), "+f"(d[22]), "+f"(d[23]), "+f"(d[24]), "+f"(d[25]), "+f"(d[26]), "+f"(d[27]), "+f"(d[28]), "+f"(d[29]), "+f"(d[30]), "+f"(d[31]), "+f"(d[32]), "+f"(d[33]), "+f"(d[34]), "+f"(d[35]), "+f"(d[36]), "+f"(d[37]), "+f"(d[38]), "+f"(d[39]), "+f"(d[40]), "+f"(d[41]), "+f"(d[42]), "+f"(d[43]), "+f"(d[44]), "+f"(d[45]), "+f"(d[46]), "+f"(d[47]), "+f"(d[48]), "+f"(d[49]), "+f"(d[50]), "+f"(d[51]), "+f"(d[52]), "+f"(d[53]), "+f"(d[54]), "+f"(d[55]), "+f"(d[56]), "+f"(d[57]), "+f"(d[58]), "+f"(d[59]), "+f"(d[60]), "+f"(d[61]), "+f"(d[62]), "+f"(d[63]), "+f"(d[64]), "+f"(d[65]), "+f"(d[66]), "+f"(d[67]), "+f"(d[68]), "+f"(d[69]), "+f"(d[70]), "+f"(d[71]), "+f"(d[72]), "+f"(d[73]), "+f"(d[74]), "+f"(d[75]), "+f"(d[76]), "+f"(d[77]), "+f"(d[78]), "+f"(d[79]), "+f"(d[80]), "+f"(d[81]), "+f"(d[82]), "+f"(d[83]), "+f"(d[84]), "+f"(d[85]), "+f"(d[86]), "+f"(d[87]), "+f"(d[88]), "+f"(d[89]), "+f"(d[90]), "+f"(d[91]), "+f"(d[92]), "+f"(d[93]), "+f"(d[94]), "+f"(d[95]) : "l"(da), "l"(db), "r"(sc));
}

__device__ __forceinline__ uint64_t desc64(uint32_t lo, uint32_t hi) { uint64_t d; asm("mov.b64 %0, {%1, %2};" : "=l"(d) : "r"(lo), "r"(hi)); return d; }
constexpr uint32_t DESC_HI = (1024u >> 4) | (1u << 30);
constexpr uint32_t DESC_HI64 = (512u >> 4) | (2u << 30);
template <int n> __device__ __forceinline__ void fence_regs(float* a) {
#pragma unroll
  for (int i = 0; i < n; i++) asm volatile("" : "+f"(a[i])::"memory");
}

struct Ctx {
  uint32_t full;
  uint32_t emb;
  bool sig;
  uint32_t stage, phase, prev;
  uint32_t dB, dA;
  __device__ __forceinline__ void release_prev() { if (sig && prev != ~0u) mbar_arrive_cl(emb + prev); }
  __device__ __forceinline__ void wait_full() {
    mbar_wait(full + 8 * stage, phase);
    wg_fence();
  }
};

__device__ __forceinline__ void issue192(float* acc, Ctx& c, int s, bool first = false) {
  c.wait_full();
  const uint32_t db = c.dB + c.stage * (STAGE_BYTES >> 4);
  const uint32_t da = c.dA + (s >> 1) * 1024 + (s & 1) * 4;
  wgmma_ss<192>(acc, desc64(da, DESC_HI), desc64(db, DESC_HI), first ? 0 : 1);
  wgmma_ss<192>(acc, desc64(da + 2, DESC_HI), desc64(db + 128, DESC_HI), 1);
  wg_commit();
}
__device__ __forceinline__ void issue96(float* acc, Ctx& c, int s, bool first) {
  c.wait_full();
  const uint32_t db = c.dB + c.stage * (STAGE_BYTES >> 4);
  const uint32_t da = c.dA + s * 1024;
  if (first) { wgmma_ss<192>(acc, desc64(da, DESC_HI), desc64(db, DESC_HI64), 0); wg_fence(); }
#pragma unroll
  for (int kk = first ? 1 : 0; kk < 4; kk++) wgmma_ss<96>(acc, desc64(da + 2 * kk, DESC_HI), desc64(db + 64 * kk, DESC_HI64), 1);
  wg_commit();
}
__device__ __forceinline__ void retire(Ctx& c) {
  wg_wait<1>();
  c.release_prev();
  c.prev = 8 * c.stage;
  if (++c.stage == NSTAGE) { c.stage = 0; c.phase ^= 1; }
}
constexpr float GK = 0.32920349f;
__device__ __forceinline__ uint32_t gelu_pair(uint32_t y) {
  uint32_t u, th;
  asm("mul.rn.bf16x2 %0, %1, %2;" : "=r"(u) : "r"(hfma2(y, y, 0x401b401bu)), "r"(y));
  asm("tanh.approx.bf16x2 %0, %1;" : "=r"(th) : "r"(u));
  return hfma2(y, th, y);
}
__device__ __forceinline__ uint4 gelu_group(const uint32_t* a) { return make_uint4(gelu_pair(a[0]), gelu_pair(a[1]), gelu_pair(a[2]), gelu_pair(a[3])); }
__device__ __forceinline__ void lds_bias(float2* b, uint32_t addr) {
#pragma unroll
  for (int j = 0; j < 4; j++) asm volatile("ld.shared.v2.f32 {%0,%1}, [%2];" : "=f"(b[j].x), "=f"(b[j].y) : "r"(addr + 32 * j));
}
__device__ __forceinline__ int opaque(int v) { asm volatile("" : "+r"(v)); return v; }
__device__ __forceinline__ void stsm4(uint32_t addr, uint4 r) {
  asm volatile("stmatrix.sync.aligned.m8n8.x4.shared.b16 [%0], {%1,%2,%3,%4};" ::"r"(addr), "r"(r.x), "r"(r.y), "r"(r.z), "r"(r.w) : "memory");
}
__device__ __forceinline__ float ex2f(float x) { float r; asm("ex2.approx.ftz.f32 %0, %1;" : "=f"(r) : "f"(x)); return r; }
__device__ __forceinline__ uint32_t phi_pack(uint32_t tp, float a0, float a1) {
  uint32_t x, y;
  asm("max.bf16x2 %0, %1, %2;" : "=r"(x) : "r"(tp), "r"(0x35863586u));
  asm("min.bf16x2 %0, %1, %2;" : "=r"(y) : "r"(pack_bf16(ex2f(a0), ex2f(a1))), "r"(0x3f803f80u));
  return hadd2(x, y);
}
template <int q0, int q1>
__device__ __forceinline__ void part_groups(const float* a, uint4* p, uint32_t par) {
#pragma unroll
  for (int q = q0; q < q1; q++)
    st_ll(p + q * 32, pack_bf16(a[8 * q], a[8 * q + 1]), pack_bf16(a[8 * q + 2], a[8 * q + 3]), pack_bf16(a[8 * q + 4], a[8 * q + 5]), pack_bf16(a[8 * q + 6], a[8 * q + 7]), par);
}
__device__ __forceinline__ float rcpf(float x) { float r; asm("rcp.approx.ftz.f32 %0, %1;" : "=f"(r) : "f"(x)); return r; }
__device__ __forceinline__ float silu(float y) { return y * rcpf(1.f + ex2f(y * -1.4426950408889634f)); }
__device__ __forceinline__ uint32_t gate_word(uint32_t w0, uint32_t w1, uint32_t w2, uint32_t w3, uint32_t w4, uint32_t w5, uint32_t w6, uint32_t w7, uint32_t bb) {
  const uint32_t u0 = hadd2(hadd2(w0, w1), hadd2(w2, w3)), u1 = hadd2(hadd2(w4, w5), hadd2(w6, w7));
  return pack_bf16(silu(fmaf(bf_lo(u0) + bf_lo(u1), 0.5f / GK, bf_lo(bb))), silu(fmaf(bf_hi(u0) + bf_hi(u1), 0.5f / GK, bf_hi(bb))));
}
__device__ __forceinline__ uint4 gate_vec(const uint4* p, uint32_t b0, uint32_t b1) {
  return make_uint4(gate_word(p[0].x, p[1].x, p[2].x, p[3].x, p[4].x, p[5].x, p[6].x, p[7].x, b0), gate_word(p[0].y, p[1].y, p[2].y, p[3].y, p[4].y, p[5].y, p[6].y, p[7].y, b0),
                    gate_word(p[0].z, p[1].z, p[2].z, p[3].z, p[4].z, p[5].z, p[6].z, p[7].z, b1), gate_word(p[0].w, p[1].w, p[2].w, p[3].w, p[4].w, p[5].w, p[6].w, p[7].w, b1));
}
template <bool STRONG> __device__ __forceinline__ void d1_load(uint32_t* W, int rb0, int head, int ln) {
  const uint2* qf = g_qkv + (rb0 * 8 + (ln >> 2)) * 864 + 288 + head * 9 + (ln & 3);
#pragma unroll
  for (int b = 0; b < 3; b++) {
#pragma unroll
    for (int j = 0; j < 4; j++) {
      const uint2* p = qf + j * 8 * 864 + 4 * b;
      const uint2 kk = STRONG ? ld_ll64(p) : ld_ca64(p), vv = STRONG ? ld_ll64(p + 288) : ld_ca64(p + 288);
      W[6 * j + 2 * b] = kk.x; W[6 * j + 2 * b + 1] = kk.y; W[24 + 6 * j + 2 * b] = vv.x; W[24 + 6 * j + 2 * b + 1] = vv.y;
    }
  }
}
__device__ __forceinline__ bool d1_bad(const uint32_t* W, int t, uint32_t par) {
  uint32_t bad = 0, bad2 = 0;
#pragma unroll
  for (int q = 0; q < 12; q++) ll_chk((q % 3) != 2 ? bad : bad2, W[2 * q], W[24 + 2 * q], par);
  return __any_sync(0xffffffffu, (bad | (t == 0 ? bad2 : 0u)) & 1);
}
__device__ __forceinline__ void d1_mov(uint32_t* W, int j, int t) {
  if (t != 0) { W[6 * j + 4] = W[6 * j + 5] = 0u; W[24 + 6 * j + 4] = W[24 + 6 * j + 5] = (t == 1 ? 0x00003f80u : 0u); }
#pragma unroll
  for (int q = 0; q < 6; q++) { W[6 * j + q] = movmat(W[6 * j + q]); W[24 + 6 * j + q] = movmat(W[24 + 6 * j + q]); }
}
__device__ __forceinline__ void d1_mma(const uint32_t* W, float* R) {
  float c1[3][4];
#pragma unroll
  for (int j = 0; j < 12; j++) { R[j] = 0.f; c1[j >> 2][j & 3] = 0.f; }
#pragma unroll
  for (int ks = 0; ks < 4; ks++)
#pragma unroll
    for (int j = 0; j < 3; j++) {
      mma16816(R + 4 * j, W[24 + 6 * ks], W[24 + 6 * ks + 2], W[24 + 6 * ks + 1], W[24 + 6 * ks + 3], W[6 * ks + 2 * j], W[6 * ks + 2 * j + 1]);
      mma16816(c1[j], W[24 + 6 * ks + 4], 0u, W[24 + 6 * ks + 5], 0u, W[6 * ks + 2 * j], W[6 * ks + 2 * j + 1]);
    }
#pragma unroll
  for (int j = 0; j < 3; j++) { R[12 + 2 * j] = c1[j][0]; R[13 + 2 * j] = c1[j][1]; }
}
__device__ __forceinline__ bool kv_valid(int w, int ln) { return (w < 3 || ln < 12) && ((w != 2 && w != 4) || (ln & 3) == 0); }

struct Params {
  CUtensorMap tm_wqkv, tm_w1, tm_w2, tm_m, tm_wqkv64, tm_m64, tm_a, tm_ast;
  const __nv_bfloat16 *x, *b1, *b2, *wqkv, *w1, *w2, *wo;
  __nv_bfloat16* out;
};

__global__ void __cluster_dims__(2, 1, 1) __launch_bounds__(NTHREADS, 1) fused_kernel(const __grid_constant__ Params P) {
  extern __shared__ __align__(1024) uint8_t smem[];
  const uint32_t sbase = smem_u32(smem);
  const int tid = threadIdx.x, lane = tid & 31;
  const int warp = __shfl_sync(0xffffffffu, tid >> 5, 0);
  const int g = lane >> 2, t = lane & 3;
  const uint32_t ep = __shfl_sync(0xffffffffu, g_epoch[blockIdx.x], 0) + 1;
  const uint32_t par = ep & 1;
  STAMPW(0, 0);

  if (blockIdx.x >= 128) {
    const int a = blockIdx.x - 128;
    constexpr int WP = 1168, SM_T = 152 * WP, SM_HB = SM_T + 8 * 32 * 80;
    if (tid == 0) {
      mbar_init(sbase + SM_HB, 1);
      asm volatile("fence.mbarrier_init.release.cluster;" ::: "memory");
      mbar_expect(sbase + SM_HB, 144 * 1152);
    }
    for (int i = tid; i < (8 * WP + 8 * 32 * 80) / 4; i += NTHREADS) reinterpret_cast<uint32_t*>(smem + 144 * WP)[i] = 0u;
    __syncthreads();
    __nanosleep(1500);
    if (tid < 144)
      asm volatile("cp.async.bulk.shared::cluster.global.mbarrier::complete_tx::bytes [%0], [%1], %2, [%3];" ::"r"(sbase + tid * WP), "l"(P.wo + (a * 144 + tid) * D_), "r"(1152), "r"(sbase + SM_HB) : "memory");
    if (warp >= 8 && lane == 0) {
      const int id = a * 4 + (warp - 8);
      constexpr uint32_t CH = 9216 * 2;
#pragma unroll 1
      for (int i = id; i < 576; i += 16) {
        const char* p = i < 288 ? (const char*)P.w1 + (size_t)i * CH : (const char*)P.w2 + (size_t)(i - 288) * CH;
        asm volatile("cp.async.bulk.prefetch.L2.global [%0], %1;" ::"l"(p), "r"(CH) : "memory");
      }
    }
    __syncwarp();
    if (lane < 8) hint_wait(&g_f_kvp[a * 8 + lane], 16 * ep, 50);
    __syncwarp();
    STAMPW(0, 1);
#pragma unroll 1
    for (int u = warp; u < 40; u += 12) {
      const int hh = u & 7, w = 4 - (u >> 3), head = a * 8 + hh;
      uint4 v[16];
      int tries = 0;
      uint32_t bad;
      const bool val = kv_valid(w, lane);
#pragma unroll 1
      do {
        bad = 0;
#pragma unroll
        for (int j = 0; j < 16; j++) v[j] = val ? ld_ll(&g_kvp[((head * 5 + w) * 16 + j) * 32 + lane]) : make_uint4(par, 0u, par, 0u);
#pragma unroll
        for (int j = 0; j < 16; j++) ll_chk(bad, v[j].x, v[j].z, par);
      } while (__any_sync(0xffffffffu, bad & 1) && ++tries < (1 << 20));
      float s0 = 0.f, s1 = 0.f, s2 = 0.f, s3 = 0.f;
#pragma unroll
      for (int j = 0; j < 16; j++) { s0 += __uint_as_float(v[j].x); s1 += __uint_as_float(v[j].y); s2 += __uint_as_float(v[j].z); s3 += __uint_as_float(v[j].w); }
      if (w >= 3) {
        if (g == 2) st_ll(&g_z[(head * 2 + w - 3) * 4 + t], __float_as_uint(s0), __float_as_uint(s1), __float_as_uint(s2), __float_as_uint(s3), par);
        __syncwarp();
        hint_signal(&g_f_z[head]);
      }
      const int e0 = w < 3 ? g : 16 + g, e1 = w < 3 ? g + 8 : 16 + g, d0 = (w < 3 ? 8 * w : (w == 3 ? 0 : 16)) + 2 * t, d1 = w < 3 ? d0 : d0 + 8;
      __nv_bfloat16* T = reinterpret_cast<__nv_bfloat16*>(smem + SM_T) + hh * 32 * 40;
      if (e0 < 18) {
        T[d0 * 40 + e0] = __float2bfloat16(s0); T[(d0 + 1) * 40 + e0] = __float2bfloat16(s1);
        T[d1 * 40 + e1] = __float2bfloat16(s2); T[(d1 + 1) * 40 + e1] = __float2bfloat16(s3);
      }
    }
    __syncthreads();
    STAMPW(0, 2);
    mbar_wait(sbase + SM_HB, 0);
#pragma unroll 1
    for (int u = warp; u < 24; u += 12) {
      const int hh = u / 3, c0 = (u % 3) * 192;
      const uint32_t* T = reinterpret_cast<const uint32_t*>(smem + SM_T) + hh * 32 * 20 + g * 20 + t;
      const uint32_t a00 = T[0], a01 = T[160], a02 = T[4], a03 = T[164], a10 = T[8], a11 = T[168], b00 = T[320], b02 = T[324], b10 = T[328];
      const uint32_t rowa = sbase + (hh * 18 + (lane & 15)) * WP + (c0 + (lane >> 4) * 8) * 2, rowb = sbase + (hh * 18 + 16 + (lane & 7)) * WP + (c0 + ((lane >> 3) & 1) * 8) * 2;
#pragma unroll 3
      for (int j = 0; j < 12; j++) {
        uint32_t w0, w1, w2, w3, w4, w5;
        asm volatile("ldmatrix.sync.aligned.m8n8.x4.trans.shared.b16 {%0,%1,%2,%3}, [%4];" : "=r"(w0), "=r"(w1), "=r"(w2), "=r"(w3) : "r"(rowa + j * 32));
        asm volatile("ldmatrix.sync.aligned.m8n8.x2.trans.shared.b16 {%0,%1}, [%2];" : "=r"(w4), "=r"(w5) : "r"(rowb + j * 32));
        float p[4][4];
#pragma unroll
        for (int q = 0; q < 4; q++) p[q][0] = p[q][1] = p[q][2] = p[q][3] = 0.f;
        mma16816(p[0], a00, a01, a02, a03, w0, w1); mma16816(p[1], a00, a01, a02, a03, w2, w3);
        mma16816(p[2], b00, 0u, b02, 0u, w0, w1); mma16816(p[3], b00, 0u, b02, 0u, w2, w3);
        mma16816(p[0], a10, a11, 0u, 0u, w4, 0u); mma16816(p[1], a10, a11, 0u, 0u, w5, 0u);
        mma16816(p[2], b10, 0u, 0u, 0u, w4, 0u); mma16816(p[3], b10, 0u, 0u, 0u, w5, 0u);
        stsm4(rowa + j * 32, make_uint4(pack_bf16(p[0][0], p[0][1]), pack_bf16(p[0][2], p[0][3]), pack_bf16(p[1][0], p[1][1]), pack_bf16(p[1][2], p[1][3])));
        if (g < 2) {
          uint32_t* r = reinterpret_cast<uint32_t*>(smem + (hh * 18 + 16 + g) * WP + (c0 + j * 16 + 2 * t) * 2);
          r[0] = pack_bf16(p[2][0], p[2][1]); r[4] = pack_bf16(p[3][0], p[3][1]);
        }
      }
      asm volatile("fence.proxy.async.shared::cta;" ::: "memory");
      __syncwarp();
      if (lane < 18) {
        asm volatile("cp.async.bulk.global.shared::cta.bulk_group [%0], [%1], %2;" ::"l"(g_m + (a * 144 + hh * 18 + lane) * D_ + c0), "r"(sbase + (hh * 18 + lane) * WP + c0 * 2), "r"(384) : "memory");
        asm volatile("cp.async.bulk.commit_group;" ::: "memory");
      }
    }
    asm volatile("cp.async.bulk.wait_group 0;" ::: "memory");
    asm volatile("fence.proxy.async.global;" ::: "memory");
    __syncwarp();
    if (lane == 0) asm volatile("red.release.gpu.global.add.u32 [%0], 1;" ::"l"(g_f_m) : "memory");
    STAMPW(0, 3);
    __syncthreads();
    if (tid == 0) g_epoch[blockIdx.x] = ep;
    return;
  }

  const int cl = blockIdx.x >> 1, rank = blockIdx.x & 1;
  const int f = cl & 7, m = (cl >> 3) * 2 + rank;
  const int srole = f >= 6 ? 1 : 0;
  const uint32_t bar_full = sbase + SM_BAR, bar_empty = bar_full + 8 * NSTAGE, bar_xfree = bar_empty + 8 * NSTAGE, bar_ofull = bar_xfree + 72,
                 bar_d = bar_ofull + 72;

  if (tid == 0) {
#pragma unroll 1
    for (int i = 0; i < NSTAGE; i++) { mbar_init(bar_full + 8 * i, 1); mbar_init(bar_empty + 8 * i, 4); }
#pragma unroll 1
    for (int i = 0; i < 9; i++) { mbar_init(bar_xfree + 8 * i, 2); mbar_init(bar_ofull + 8 * i, 1); }
    mbar_init(bar_d, 1);
    asm volatile("fence.mbarrier_init.release.cluster;" ::: "memory");
  }
  __syncwarp();
  cluster_arrive_relaxed();

  if (warp >= 8) {
    const int srow = m * 128 + f * 16 + (warp - 8) * 4 + (lane >> 3);
    uint4 xs[9];
#pragma unroll
    for (int kb = 0; kb < 9; kb++) xs[kb] = __ldg(reinterpret_cast<const uint4*>(P.x + srow * D_) + (lane & 7) + kb * 8);
    auto stats = [&]() {
      const uint32_t* w = reinterpret_cast<const uint32_t*>(xs);
      float s0 = 0.f, s1 = 0.f;
#pragma unroll
      for (int i = 0; i < 36; i++) { s0 += bf_lo(w[i]); s1 += bf_hi(w[i]); }
      float sum = s0 + s1;
      sum += __shfl_xor_sync(0xffffffffu, sum, 1); sum += __shfl_xor_sync(0xffffffffu, sum, 2); sum += __shfl_xor_sync(0xffffffffu, sum, 4);
      const float mean = sum * (1.f / 576.f);
      s0 = 0.f; s1 = 0.f;
#pragma unroll
      for (int i = 0; i < 36; i++) { const float a = bf_lo(w[i]) - mean, b = bf_hi(w[i]) - mean; s0 = fmaf(a, a, s0); s1 = fmaf(b, b, s1); }
      float sq = s0 + s1;
      sq += __shfl_xor_sync(0xffffffffu, sq, 1); sq += __shfl_xor_sync(0xffffffffu, sq, 2); sq += __shfl_xor_sync(0xffffffffu, sq, 4);
      const float rstd = rsqrtf(sq * (1.f / 576.f) + 1e-5f);
      if ((lane & 7) == 0)
        st_ll64(&g_stat[srow], __float_as_uint(rstd), pack_bf16(-mean, -mean), par);
    };
    stats();
    asm volatile("setmaxnreg.dec.sync.aligned.u32 40;");
    cluster_wait();
    if (warp == 8) {
      if (lane == 0) {
        uint32_t stage = 0, phase = 1;
        const uint32_t sb = sbase + SM_B;
#pragma unroll 1
        for (int tl = 2 * srole; tl < 8 + 2 * srole; tl++) {
          const CUtensorMap* map = tl == 0 ? &P.tm_wqkv : (tl == 1 ? &P.tm_wqkv64 : (tl < 5 ? &P.tm_w1 : (tl < 8 ? &P.tm_w2 : (tl == 8 ? &P.tm_m : &P.tm_m64))));
          const int col = tl < 2 ? 288 * f + 192 * tl : (tl < 5 ? 576 * f + 192 * (tl - 2) : (tl < 8 ? 192 * (tl - 5) : (tl == 8 ? 192 * (f - 5) : 96 * (f - 6))));
          const bool perm = tl >= 5 && tl < 8;
          const bool z = (tl & 7) == 1;
          if (tl == 8) { flag_wait(g_f_m, 48 * ep); asm volatile("fence.proxy.async.global;" ::: "memory"); }
          const int cs = z ? 32 : 64, rs = z ? 64 : 32, nst = z ? 9 : 18;
#pragma unroll 1
          for (int st = 0; st < nst; st++) {
            int row = st * rs;
            if (perm) row += 576 * f + ((st < 6) ? 192 : (st < 12 ? -192 : 0));
            mbar_wait(bar_empty + 8 * stage, phase);
            mbar_expect(bar_full + 8 * stage, 12288);
            const uint32_t dst = sb + stage * STAGE_BYTES;
            if (((st ^ rank) & 1) == 0) {
              tma2d_mc(dst, map, col, row, bar_full + 8 * stage);
              tma2d_mc(dst + 8192, map, col + 2 * cs, row, bar_full + 8 * stage);
            } else {
              tma2d_mc(dst + 4096, map, col + cs, row, bar_full + 8 * stage);
            }
            if (++stage == NSTAGE) { stage = 0; phase ^= 1; }
          }
        }
      }
      __syncwarp();
    } else {
      const int aw = warp - 9;
      const int hi = f >> 2;
      if (aw == 0) {
        if (lane < 2) hint_wait(&g_f_qkv[m * 8 + 2 + 2 * lane + hi], 16 * ep, 200);
        __syncwarp();
        if (lane == 0) mbar_arrive(bar_d);
        STAMP(20);
      }
      if (lane < 5) hint_wait(lane < 4 ? &g_f_z[4 * f + lane] : &g_f_qkv[m * 8 + hi], lane < 4 ? 2 * ep : 16 * ep);
      __syncwarp();
      STAMPW(9, 22);
      uint32_t* stg = reinterpret_cast<uint32_t*>(smem + SM_SCR + aw * 2304);
#pragma unroll 1
      for (int u = aw * 2; u < 16; u += (u & 1) ? 5 : 1) {
        const int rbl = u >> 1, hp = (u & 1) * 2;
        const uint2* qf = g_qkv + ((m * 8 + rbl) * 8 + g) * 864 + (4 * f + hp) * 9 + t;
        const uint2* zp = reinterpret_cast<const uint2*>(&g_z[(4 * f + hp) * 8 + t]);
        uint2 q[2][3];
        float d[4];
        int tries = 0;
        uint32_t bad;
#pragma unroll 1
        do {
          bad = tries ? ld_acquire(g_f_m) & 0u : 0u;
#pragma unroll
          for (int j = 0; j < 2; j++)
#pragma unroll
            for (int b = 0; b < 3; b++) q[j][b] = ld_ca64(qf + 9 * j + 4 * b);
#pragma unroll
          for (int j = 0; j < 2; j++) {
            const uint2 z0 = ld_ca64(zp + 16 * j), z1 = ld_ca64(zp + 16 * j + 1), z2 = ld_ca64(zp + 16 * j + 8);
            if (t != 0) q[j][2] = make_uint2(par, 0u);
            ll_chk(bad, z0.x, z1.x, par); ll_chk(bad, z2.x, q[j][2].x, par); ll_chk(bad, q[j][0].x, q[j][1].x, par);
            d[2 * j] = bf_lo(q[j][0].x) * __uint_as_float(z0.x) + bf_hi(q[j][0].x) * __uint_as_float(z0.y) + bf_lo(q[j][1].x) * __uint_as_float(z1.x) + bf_hi(q[j][1].x) * __uint_as_float(z1.y) +
                       bf_lo(q[j][2].x) * __uint_as_float(z2.x) + bf_hi(q[j][2].x) * __uint_as_float(z2.y);
            d[2 * j + 1] = bf_lo(q[j][0].y) * __uint_as_float(z0.x) + bf_hi(q[j][0].y) * __uint_as_float(z0.y) + bf_lo(q[j][1].y) * __uint_as_float(z1.x) + bf_hi(q[j][1].y) * __uint_as_float(z1.y) +
                           bf_lo(q[j][2].y) * __uint_as_float(z2.x) + bf_hi(q[j][2].y) * __uint_as_float(z2.y);
          }
        } while (__any_sync(0xffffffffu, bad & 1) && ++tries < (1 << 20));
#pragma unroll
        for (int j = 0; j < 4; j++) d[j] += __shfl_xor_sync(0xffffffffu, d[j], 1);
#pragma unroll
        for (int j = 0; j < 4; j++) d[j] = rcpf(d[j] + __shfl_xor_sync(0xffffffffu, d[j], 2) + 1e-6f);
        if (hp == 0) { asm volatile("cp.async.bulk.wait_group.read 0;" ::: "memory"); __syncwarp(); }
#pragma unroll
        for (int j = 0; j < 2; j++) {
          const uint32_t r0 = pack_bf16(d[2 * j], d[2 * j]), r1 = pack_bf16(d[2 * j + 1], d[2 * j + 1]);
#pragma unroll
          for (int b = 0; b < 3; b++)
            if (b < 2 || t == 0) {
              stg[g * 36 + (hp + j) * 9 + 4 * b + t] = hfma2(q[j][b].x, r0, 0x80008000u);
              stg[(g + 8) * 36 + (hp + j) * 9 + 4 * b + t] = hfma2(q[j][b].y, r1, 0x80008000u);
            }
        }
        if (hp != 0) {
          asm volatile("fence.proxy.async.shared::cta;" ::: "memory");
          __syncwarp();
          if (lane == 0) {
            asm volatile("cp.async.bulk.tensor.2d.global.shared::cta.bulk_group [%0, {%2, %3}], [%1];" ::"l"(&P.tm_ast), "r"(smem_u32(stg)), "r"(72 * f), "r"(m * 128 + rbl * 16) : "memory");
            asm volatile("cp.async.bulk.commit_group;" ::: "memory");
          }
        }
      }
      asm volatile("cp.async.bulk.wait_group 0;" ::: "memory");
      asm volatile("fence.proxy.async.global;" ::: "memory");
      STAMPW(9, 26);
      asm volatile("bar.sync 5, 96;" ::: "memory");
      if (tid == 288) asm volatile("red.release.gpu.global.add.u32 [%0], 1;" ::"l"(&g_f_a[m]) : "memory");
      __syncwarp();
      STAMPW(9, 23);
      if (srole && aw == 2) {
        if (lane == 0) {
          flag_wait(&g_f_a[m], 8 * ep);
          asm volatile("fence.proxy.async.global;" ::: "memory");
#pragma unroll 1
          for (int kb = 0; kb < 9; kb++) {
            mbar_wait(bar_xfree + 8 * kb, 0);
            mbar_expect(bar_ofull + 8 * kb, 16384);
            tma2d(sbase + SM_A + kb * 16384, &P.tm_a, kb * 64, m * 128, bar_ofull + 8 * kb);
          }
        }
        __syncwarp();
      }
      const int rbg = m * 8 + f;
      if (lane == 0) hint_wait(&g_f_rb[rbg * 8], 8 * ep);
      __syncwarp();
      STAMPW(9, 24);
#pragma unroll 1
      for (int hv = aw * 8; hv < aw * 8 + 8; hv++) {
        const uint32_t bb = __ldg(reinterpret_cast<const uint32_t*>(P.b2 + 8 * hv + 2 * t));
        const uint2* pp = reinterpret_cast<const uint2*>(&g_part[(rbg * 8 * 36 + (hv >> 1)) * 32 + lane]) + (hv & 1);
        uint2 p[8];
        int tries = 0;
        uint32_t bad;
#pragma unroll 1
        do {
          bad = tries ? ld_acquire(g_f_m) & 0u : 0u;
#pragma unroll
          for (int i = 0; i < 8; i++) p[i] = ld_ca64(pp + i * 36 * 64);
#pragma unroll
          for (int i = 0; i < 8; i += 2) ll_chk(bad, p[i].x, p[i + 1].x, par);
        } while (__any_sync(0xffffffffu, bad & 1) && ++tries < (1 << 20));
        const uint32_t g0 = gate_word(p[0].x, p[1].x, p[2].x, p[3].x, p[4].x, p[5].x, p[6].x, p[7].x, bb), g1 = gate_word(p[0].y, p[1].y, p[2].y, p[3].y, p[4].y, p[5].y, p[6].y, p[7].y, bb);
        st_ll64(reinterpret_cast<uint2*>(&g_g[(rbg * 12 + (hv >> 1)) * 32 + lane]) + (hv & 1), g0, g1, par);
      }
      STAMPW(9, 25);
    }
    cluster_arrive_relaxed();
    cluster_wait();
  } else {
    const int wg = warp >> 2;
    {
      const int rs = lane >> 3, j = lane & 7;
      uint4 xv[4][9];
#pragma unroll
      for (int it = 0; it < 4; it++)
#pragma unroll
        for (int kb = 0; kb < 9; kb++) xv[it][kb] = __ldg(reinterpret_cast<const uint4*>(P.x + (m * 128 + warp * 16 + it * 4 + rs) * D_) + j + kb * 8);
      uint32_t bw0 = __ldg(reinterpret_cast<const uint32_t*>(P.b1 + 576 * f) + tid), bw1 = tid < 32 ? __ldg(reinterpret_cast<const uint32_t*>(P.b1 + 576 * f) + 256 + tid) : 0u;
      uint2 st[4];
      int tries = 0;
      uint32_t bad;
#pragma unroll 1
      do {
        bad = 0;
#pragma unroll
        for (int it = 0; it < 4; it++) st[it] = ld_ll64(&g_stat[m * 128 + warp * 16 + it * 4 + rs]);
        ll_chk(bad, st[0].x, st[1].x, par); ll_chk(bad, st[2].x, st[3].x, par);
      } while (__any_sync(0xffffffffu, bad & 1) && ++tries < (1 << 22));
      STAMPW(0, 19);
#pragma unroll
      for (int it = 0; it < 4; it++) {
        const uint32_t nm = st[it].y;
        uint8_t* dst = smem + SM_A + (warp * 16 + it * 4 + rs) * 128 + ((j ^ ((it * 4 + rs) & 7)) << 4);
#pragma unroll
        for (int kb = 0; kb < 9; kb++) {
          const uint4 w = xv[it][kb];
          *reinterpret_cast<uint4*>(dst + kb * 16384) = make_uint4(hadd2(w.x, nm), hadd2(w.y, nm), hadd2(w.z, nm), hadd2(w.w, nm));
        }
        if (j == 0) reinterpret_cast<uint32_t*>(smem + SM_RSTD)[warp * 16 + it * 4 + rs] = st[it].x;
      }
      reinterpret_cast<float2*>(smem + SM_BIAS)[tid] = make_float2(bf_lo(bw0) * GK, bf_hi(bw0) * GK);
      if (tid < 32) reinterpret_cast<float2*>(smem + SM_BIAS)[256 + tid] = make_float2(bf_lo(bw1) * GK, bf_hi(bw1) * GK);
      asm volatile("fence.proxy.async.shared::cta;" ::: "memory");
    }
    asm volatile("setmaxnreg.inc.sync.aligned.u32 232;");
    cluster_wait();
    asm volatile("bar.sync 1, 256;" ::: "memory");
    STAMPW(0, 1);
    Ctx c;
    c.full = bar_full;
    c.emb = __shfl_sync(0xffffffffu, mapa(bar_empty, (warp & 3) == 0 ? rank : (rank ^ 1)), 0);
    c.sig = lane == 0 && (warp & 3) < 2;
    c.stage = 0; c.phase = 0; c.prev = ~0u;
    c.dB = (((sbase + SM_B) & 0x3FFFF) >> 4) | ((4096u >> 4) << 16);
    c.dA = (((sbase + SM_A + wg * 8192) & 0x3FFFF) >> 4) | (1u << 16);
    const bool leader = (lane == 0) && ((warp & 3) == 0);

    const int rb = m * 8 + warp;
    const uint32_t bias_t = sbase + SM_BIAS + 8 * t;
    const uint32_t hst = sbase + SM_A + (warp * 16 + (lane & 7) + ((lane >> 3) & 1) * 8) * 128 + (((lane >> 4) ^ (lane & 7)) << 4);
    auto wg_sync = [&]() {
      asm volatile("fence.proxy.async.shared::cta;" ::: "memory");
      if (wg == 0) asm volatile("bar.sync 2, 128;" ::: "memory"); else asm volatile("bar.sync 3, 128;" ::: "memory");
    };
    float A[96], B[96];
#pragma unroll
    for (int i = 0; i < 96; i++) B[i] = 0.f;
#define GELU16(H0, H1, ACC, OFF) uint32_t E[8]; \
    _Pragma("unroll") for (int q = 0; q < 8; q++) E[q] = pack_bf16(fmaf(ACC[(OFF) + 2 * q], (q & 1) ? r1 : r0, bs[q >> 1].x), fmaf(ACC[(OFF) + 2 * q + 1], (q & 1) ? r1 : r0, bs[q >> 1].y)); \
    const uint4 H0 = gelu_group(E), H1 = gelu_group(E + 4);
#define SPART16(DST, ACC, OFF) { uint32_t E[8]; _Pragma("unroll") for (int q = 0; q < 8; q++) E[q] = pack_bf16(ACC[(OFF) + 2 * q] * ((q & 1) ? r1 : r0), ACC[(OFF) + 2 * q + 1] * ((q & 1) ? r1 : r0)); \
    if (f < 4) { const float l0 = r0 * 1.4426950408889634f, l1 = r1 * 1.4426950408889634f; \
      _Pragma("unroll") for (int q = 0; q < 8; q++) E[q] = phi_pack(E[q], ACC[(OFF) + 2 * q] * ((q & 1) ? l1 : l0), ACC[(OFF) + 2 * q + 1] * ((q & 1) ? l1 : l0)); } \
    _Pragma("unroll") for (int q = 0; q < 4; q++) st_ll64(DST + 4 * q, E[2 * q], E[2 * q + 1], par); }
#define LDS_R(SC) float r0, r1; asm volatile("ld.shared.f32 %0, [%1];" : "=f"(r0) : "r"(rst)); asm volatile("ld.shared.f32 %0, [%1];" : "=f"(r1) : "r"(rst + 32)); r0 *= (SC); r1 *= (SC);
    const uint32_t rst = sbase + SM_RSTD + (warp * 16 + g) * 4;
#pragma unroll 1
    for (int i = srole; i < 4 + srole; i++) {
      {
        const uint32_t ow = i == 4 ? bar_ofull : 0u;
        if (ow) mbar_wait(ow, 0);
        issue192(A, c, 0, true);
        const int ln = opaque(lane);
        uint4* dst = i == 1 ? reinterpret_cast<uint4*>(g_qkv + (rb * 8 + (ln >> 2)) * 864 + 144 * f + 96 + (ln & 3)) : g_part + ((rb * 8 + f) * 36 + (i == 3 ? 0 : 24)) * 32 + ln;
        LDS_R(i == 2 ? GK : 1.f)
        retire(c);
        if (ow && leader) mbar_arrive(bar_xfree + 64);
        fence_regs<96>(B);
        int s = 1;
        if (i == 2) {
#pragma unroll 1
          for (; s < 3; s++) { issue192(A, c, s); retire(c); }
        }
        if (i > srole) {
#pragma unroll
          for (int u = 0; u < 6; u++, s++) {
            float2 bs[4];
            if (i == 2) lds_bias(bs, bias_t + (192 + 32 * u) * 4);
            if ((u & 1) && ow) mbar_wait(ow + 4 * s, 0);
            issue192(A, c, s);
            if (i == 2) {
              GELU16(h0, h1, B, 16 * u)
              stsm4((hst ^ ((2 * u & 3) << 5)) + (u >> 1) * 16384, h0);
              stsm4((hst ^ ((2 * u + 1 & 3) << 5)) + (u >> 1) * 16384, h1);
            } else if (i == 1) {
              if (u < 3) SPART16(reinterpret_cast<uint2*>(dst) + 16 * u, B, 16 * u)
              if (u == 2) hint_signal(&g_f_qkv[m * 8 + f]);
            } else {
              part_groups<0, 2>(&B[16 * u], dst + 2 * u * 32, par);
              if (u == 5) hint_signal(&g_f_rb[rb * 8 + (i == 3 ? 0 : 2)]);
            }
            retire(c);
          }
        }
        const bool d1 = i == 1 + srole;
        const int send = d1 ? 10 : 15;
#pragma unroll 1
        for (; s < send; s++) {
          if (ow && !(s & 1)) mbar_wait(ow + 4 * s, 0);
          issue192(A, c, s);
          retire(c);
        }
        uint32_t W[48];
        if (d1) {
          const int head = 4 * f + (warp >> 1), rb0 = m * 8 + (warp & 1) * 4;
          issue192(A, c, 10);
          mbar_wait(bar_d, 0);
          d1_load<false>(W, rb0, head, opaque(lane));
          retire(c);
#pragma unroll 1
          for (s = 11; s < 13; s++) { issue192(A, c, s); retire(c); }
          issue192(A, c, 13);
          int tries = 0;
#pragma unroll 1
          while (d1_bad(W, t, par) && ++tries < (1 << 20)) d1_load<true>(W, rb0, head, opaque(lane));
          d1_mov(W, 0, t); d1_mov(W, 1, t);
          retire(c);
          issue192(A, c, 14);
          d1_mov(W, 2, t); d1_mov(W, 3, t);
          wg_wait<0>();
          asm volatile("bar.sync 4, 256;" ::: "memory");
          float R[18];
          d1_mma(W, R);
          float2* xch = reinterpret_cast<float2*>(smem + SM_SCR + (warp >> 1) * 1792) + opaque(lane);
          if (warp & 1) {
#pragma unroll
            for (int q = 0; q < 6; q++) xch[q * 32] = make_float2(R[2 * q], R[2 * q + 1]);
            if (lane < 12) { xch[192] = make_float2(R[12], R[13]); xch[204] = make_float2(R[14], R[15]); if (t == 0) xch[216 - lane + g] = make_float2(R[16], R[17]); }
          } else if (R[17] == 1.2345e-30f) R[16] = 0.f;
          asm volatile("bar.sync 4, 256;" ::: "memory");
          retire(c);
          issue192(A, c, 15);
          if (!(warp & 1)) {
            const int ln = opaque(lane);
#pragma unroll
            for (int q = 0; q < 6; q++) { const float2 o = xch[q * 32]; R[2 * q] += o.x; R[2 * q + 1] += o.y; }
            if (ln < 12) {
              const float2 o0 = xch[192], o1 = xch[204], o2 = xch[216 - ln + (ln >> 2)];
              R[12] += o0.x; R[13] += o0.y; R[14] += o1.x; R[15] += o1.y; R[16] += o2.x; R[17] += o2.y;
            }
            uint4* dkv = &g_kvp[(head * 80 + m) * 32 + ln];
#pragma unroll
            for (int w = 0; w < 5; w++)
              if (kv_valid(w, ln)) st_ll(dkv + w * 512, __float_as_uint(R[4 * w]), __float_as_uint(R[4 * w + 1]), w < 4 ? __float_as_uint(R[4 * w + 2]) : 0u, w < 4 ? __float_as_uint(R[4 * w + 3]) : 0u, par);
            __syncwarp();
            hint_signal(&g_f_kvp[head]);
          }
          STAMPW(0, 21);
        } else issue192(A, c, 15);
        if (i == 2) {
          const uint4* hsp = g_hsp + (blockIdx.x * 8 + warp) * 12 * 32 + opaque(lane);
#pragma unroll
          for (int q = 0; q < 12; q++) { const uint4 v = ldcg128(hsp + q * 32); W[4 * q] = v.x; W[4 * q + 1] = v.y; W[4 * q + 2] = v.z; W[4 * q + 3] = v.w; }
        } else {
#pragma unroll
          for (int q = 0; q < 48; q++) W[q] = 0;
        }
        retire(c);
        if (ow) mbar_wait(ow + 64, 0);
        issue192(A, c, 16);
        if (i == 2) wg_sync();
        retire(c);
        issue192(A, c, 17);
        if (i == 2) {
#pragma unroll
          for (int q = 0; q < 12; q++) stsm4((hst ^ ((q & 3) << 5)) + (3 + (q >> 2)) * 16384, make_uint4(W[4 * q], W[4 * q + 1], W[4 * q + 2], W[4 * q + 3]));
        }
        retire(c);
      }
      STAMPW(0, 2 + 2 * i);
      if ((i & 3) == 0) {
        issue96(B, c, 0, true);
        const int ln = opaque(lane);
        uint4* dst = i == 0 ? reinterpret_cast<uint4*>(g_qkv + (rb * 8 + (ln >> 2)) * 864 + 144 * f + (ln & 3)) : g_s + (rb * 24 + 12 * (f - 6)) * 32 + ln;
        LDS_R(1.f)
        retire(c);
        fence_regs<96>(A);
#pragma unroll
        for (int u = 0; u < 8; u++) {
          issue96(B, c, u + 1, false);
          if (u < 6) {
            if (i == 0) SPART16(reinterpret_cast<uint2*>(dst) + 16 * u, A, 16 * (u < 6 ? u : 0))
            else part_groups<0, 2>(&A[16 * (u < 6 ? u : 0)], dst + 2 * u * 32, par);
          }
          if (u == 5 && i == 0) hint_signal(&g_f_qkv[m * 8 + f]);
          retire(c);
        }
      } else {
        issue192(B, c, 0, true);
        const int ln = opaque(lane);
        uint4* dst = i == 1 ? g_hsp + (blockIdx.x * 8 + warp) * 12 * 32 + ln : g_part + ((rb * 8 + f) * 36 + 12) * 32 + ln;
        const bool xf = i == 3 && srole && leader;
        const uint32_t bsa = bias_t + (i == 1 ? 0 : 384) * 4;
        LDS_R(GK)
        retire(c);
        fence_regs<96>(A);
#pragma unroll
        for (int u = 0; u < 6; u++) {
          float2 bs[4];
          if (i != 3) lds_bias(bs, bsa + 32 * u * 4);
          issue192(B, c, u + 1);
          if (i != 3) {
            GELU16(h0, h1, A, 16 * u)
            if (i == 1) { dst[2 * u * 32] = h0; dst[(2 * u + 1) * 32] = h1; }
            else {
              stsm4((hst ^ ((2 * u & 3) << 5)) + (6 + (u >> 1)) * 16384, h0);
              stsm4((hst ^ ((2 * u + 1 & 3) << 5)) + (6 + (u >> 1)) * 16384, h1);
              if (u == 3) wg_sync();
            }
          } else {
            part_groups<0, 2>(&A[16 * u], dst + 2 * u * 32, par);
          }
          retire(c);
          if ((u & 1) && xf) mbar_arrive(bar_xfree + 4 * u - 4);
        }
#pragma unroll 1
        for (int s = 7; s < 17; s++) {
          issue192(B, c, s);
          if (s == 9 && i == 2) wg_sync();
          retire(c);
          if ((s & 1) == 0 && xf) mbar_arrive(bar_xfree + 4 * s - 8);
        }
        issue192(B, c, 17);
        retire(c);
      }
      STAMPW(0, 3 + 2 * i);
    }

    const int ln = opaque(lane);
    const __nv_bfloat16* xp = P.x + (rb * 16 + (ln >> 2)) * D_ + 2 * (ln & 3);
    __nv_bfloat16* op = P.out + (rb * 16 + (ln >> 2)) * D_ + 2 * (ln & 3);
    auto ldx = [&](uint32_t* xx, int col) {
      xx[0] = __ldg(reinterpret_cast<const uint32_t*>(xp + col)); xx[1] = __ldg(reinterpret_cast<const uint32_t*>(xp + 8 * D_ + col));
      xx[2] = __ldg(reinterpret_cast<const uint32_t*>(xp + col + 8)); xx[3] = __ldg(reinterpret_cast<const uint32_t*>(xp + 8 * D_ + col + 8));
    };
    auto stout = [&](int col, uint4 sv, uint4 gv, const uint32_t* xx) {
      *reinterpret_cast<uint32_t*>(op + col) = hfma2(sv.x, gv.x, xx[0]); *reinterpret_cast<uint32_t*>(op + 8 * D_ + col) = hfma2(sv.y, gv.y, xx[1]);
      *reinterpret_cast<uint32_t*>(op + col + 8) = hfma2(sv.z, gv.z, xx[2]); *reinterpret_cast<uint32_t*>(op + 8 * D_ + col + 8) = hfma2(sv.w, gv.w, xx[3]);
    };
    if (srole) {
      const int cb = 96 * (f - 6);
      uint32_t xx[24];
      uint4 gg[6];
#pragma unroll
      for (int q = 0; q < 6; q++) ldx(&xx[4 * q], cb + 16 * q);
      int tries = 0;
      uint32_t bad;
#pragma unroll 1
      do {
        bad = 0;
#pragma unroll
        for (int q = 0; q < 6; q++) gg[q] = ld_ll(&g_g[(rb * 12 + 6 * (f - 6) + q) * 32 + ln]);
#pragma unroll
        for (int q = 0; q < 6; q++) ll_chk(bad, gg[q].x, gg[q].z, par);
      } while (__any_sync(0xffffffffu, bad & 1) && ++tries < (1 << 20));
      STAMPW(0, 14);
      wg_wait<0>();
      c.release_prev();
      fence_regs<48>(B);
#pragma unroll
      for (int q = 0; q < 6; q++)
        stout(cb + 16 * q, make_uint4(pack_bf16(B[8 * q], B[8 * q + 1]), pack_bf16(B[8 * q + 2], B[8 * q + 3]), pack_bf16(B[8 * q + 4], B[8 * q + 5]), pack_bf16(B[8 * q + 6], B[8 * q + 7])), gg[q], &xx[4 * q]);
    } else {
      wg_wait<0>();
      c.release_prev();
      fence_regs<96>(B);
      part_groups<0, 12>(B, g_part + ((rb * 8 + f) * 36 + 24) * 32 + ln, par);
      hint_signal(&g_f_rb[rb * 8 + 2]);
      STAMPW(0, 12);
#pragma unroll 1
      for (int ch = 1; ch < 3; ch++) {
        const int cb = 192 * ch + 32 * f;
        uint32_t xx[8], bb[4];
        ldx(xx, cb); ldx(xx + 4, cb + 16);
#pragma unroll
        for (int j = 0; j < 4; j++) bb[j] = __ldg(reinterpret_cast<const uint32_t*>(P.b2 + cb + 8 * j + 2 * (ln & 3)));
        if (ln == 0 && ch == 2) hint_wait(&g_f_rb[rb * 8 + 2], 8u * ep, 20);
        __syncwarp();
        STAMPW(0, 12 + ch);
        uint4 p[2][8], sv[2];
        int tries = 0;
        uint32_t bad;
#pragma unroll 1
        do {
          bad = 0;
#pragma unroll
          for (int j = 0; j < 2; j++) {
#pragma unroll
            for (int k = 0; k < 8; k++) p[j][k] = ld_ll(&g_part[((rb * 8 + k) * 36 + 12 * ch + 2 * f + j) * 32 + ln]);
            sv[j] = ld_ll(&g_s[(rb * 24 + 12 * (ch - 1) + 2 * f + j) * 32 + ln]);
          }
#pragma unroll
          for (int j = 0; j < 2; j++) {
#pragma unroll
            for (int k = 0; k < 8; k++) ll_chk(bad, p[j][k].x, p[j][k].z, par);
            ll_chk(bad, sv[j].x, sv[j].z, par);
          }
        } while (__any_sync(0xffffffffu, bad & 1) && ++tries < (1 << 20));
#pragma unroll
        for (int j = 0; j < 2; j++) stout(cb + 16 * j, sv[j], gate_vec(p[j], bb[2 * j], bb[2 * j + 1]), &xx[4 * j]);
      }
    }
    STAMPW(0, 15);
    cluster_arrive_relaxed();
    cluster_wait();
    STAMPW(0, 16);
    if (tid == 0) g_epoch[blockIdx.x] = ep;
  }
}

typedef CUresult (*EncFn)(CUtensorMap*, CUtensorMapDataType, cuuint32_t, void*, const cuuint64_t*, const cuuint64_t*, const cuuint32_t*, const cuuint32_t*,
                          CUtensorMapInterleave, CUtensorMapSwizzle, CUtensorMapL2promotion, CUtensorMapFloatOOBfill);

void make_map(EncFn enc, CUtensorMap* tm, const void* ptr, int rows, int cols, int box_rows, int mode = 0) {
  cuuint64_t gd[2] = {(cuuint64_t)cols, (cuuint64_t)rows};
  cuuint64_t gs[1] = {(cuuint64_t)cols * 2};
  cuuint32_t bx[2] = {mode == 1 ? 32u : (mode == 2 ? 72u : 64u), (cuuint32_t)box_rows};
  cuuint32_t es[2] = {1, 1};
  enc(tm, CU_TENSOR_MAP_DATA_TYPE_BFLOAT16, 2, const_cast<void*>(ptr), gd, gs, bx, es, CU_TENSOR_MAP_INTERLEAVE_NONE, mode == 1 ? CU_TENSOR_MAP_SWIZZLE_64B : (mode == 2 ? CU_TENSOR_MAP_SWIZZLE_NONE : CU_TENSOR_MAP_SWIZZLE_128B),
      CU_TENSOR_MAP_L2_PROMOTION_L2_256B, CU_TENSOR_MAP_FLOAT_OOB_FILL_NONE);
}

}

extern "C" void kernel_launch(void* const* d_in, const int* in_sizes, int n_in, void* d_out, int out_size) {
  (void)in_sizes; (void)n_in; (void)out_size;
  static EncFn enc = nullptr;
  static void *a_ptr = nullptr, *m_ptr = nullptr;
  if (!enc) {
    void* fn = nullptr; cudaDriverEntryPointQueryResult q;
    cudaGetDriverEntryPoint("cuTensorMapEncodeTiled", &fn, cudaEnableDefault, &q);
    enc = (EncFn)fn;
    cudaFuncSetAttribute(fused_kernel, cudaFuncAttributeMaxDynamicSharedMemorySize, SMEM_BYTES);
    cudaGetSymbolAddress(&a_ptr, g_a);
    cudaGetSymbolAddress(&m_ptr, g_m);
  }
  Params P;
  P.x = (const __nv_bfloat16*)d_in[0];
  P.wqkv = (const __nv_bfloat16*)d_in[1];
  P.wo = (const __nv_bfloat16*)d_in[2];
  P.w1 = (const __nv_bfloat16*)d_in[4];
  P.b1 = (const __nv_bfloat16*)d_in[5];
  P.w2 = (const __nv_bfloat16*)d_in[6];
  P.b2 = (const __nv_bfloat16*)d_in[7];
  P.out = (__nv_bfloat16*)d_out;
  make_map(enc, &P.tm_wqkv, P.wqkv, D_, Q3_, 32);
  make_map(enc, &P.tm_w1, P.w1, D_, F_, 32);
  make_map(enc, &P.tm_w2, P.w2, F_, D_, 32);
  make_map(enc, &P.tm_m, m_ptr, D_, D_, 32);
  make_map(enc, &P.tm_wqkv64, P.wqkv, D_, Q3_, 64, 1);
  make_map(enc, &P.tm_m64, m_ptr, D_, D_, 64, 1);
  make_map(enc, &P.tm_a, a_ptr, S_, D_, 128);
  make_map(enc, &P.tm_ast, a_ptr, S_, D_, 16, 2);
  fused_kernel<<<NCTAS, NTHREADS, SMEM_BYTES, cudaStreamPerThread>>>(P);
}
```

```cpp
#include <cuda_runtime.h>
#include <cuda.h>
#include <cuda_bf16.h>
#include <stdint.h>

namespace {

constexpr int S_ = 2048, D_ = 576, F_ = 4608, Q3_ = 1728;
constexpr int NSTAGE = 6, STAGE_BYTES = 12288;
constexpr int SM_A = 0, SM_B = 147456, SM_BIAS = SM_B + NSTAGE * STAGE_BYTES, SM_RSTD = SM_BIAS + 2304, SM_SCR = SM_RSTD + 512, SM_BAR = SM_SCR + 7168;
constexpr int SMEM_BYTES = SM_BAR + 320;
constexpr int NTHREADS = 384;
constexpr int NCTAS = 132;

__device__ uint2 g_qkv[(128 * 216 + 2) * 32];
__device__ __align__(1024) __nv_bfloat16 g_a[S_ * D_];
__device__ __align__(1024) __nv_bfloat16 g_m[D_ * D_];
__device__ uint4 g_kvp[32 * 5 * 16 * 32];
__device__ uint4 g_z[32 * 2 * 4];
__device__ uint4 g_part[128 * 8 * 36 * 32];
__device__ uint4 g_s[128 * 36 * 32];
__device__ uint4 g_hsp[128 * 12 * 256];
__device__ uint32_t g_f_qkv[16 * 8];
__device__ uint32_t g_f_kvp[32];
__device__ uint32_t g_f_z[32];
__device__ uint32_t g_f_a[16];
__device__ uint32_t g_f_m[1];
__device__ uint32_t g_f_rb[128];
__device__ uint2 g_stat[S_];
__device__ uint32_t g_epoch[NCTAS];

#define STAMP(i)
#define STAMPW(w, i)
#define WSTAMP(i)
__device__ __forceinline__ uint32_t smem_u32(const void* p) { return (uint32_t)__cvta_generic_to_shared(p); }
__device__ __forceinline__ void mbar_init(uint32_t a, int c) { asm volatile("mbarrier.init.shared::cta.b64 [%0], %1;" ::"r"(a), "r"(c)); }
__device__ __forceinline__ void mbar_expect(uint32_t a, uint32_t b) { asm volatile("mbarrier.arrive.expect_tx.shared::cta.b64 _, [%0], %1;" ::"r"(a), "r"(b) : "memory"); }
__device__ __forceinline__ void mbar_arrive(uint32_t a) { asm volatile("mbarrier.arrive.shared::cta.b64 _, [%0];" ::"r"(a) : "memory"); }
__device__ __forceinline__ void mbar_arrive_cl(uint32_t a) { asm volatile("mbarrier.arrive.shared::cluster.b64 _, [%0];" ::"r"(a) : "memory"); }
__device__ __forceinline__ uint32_t mapa(uint32_t a, uint32_t cta) { uint32_t r; asm volatile("mapa.shared::cluster.u32 %0, %1, %2;" : "=r"(r) : "r"(a), "r"(cta)); return r; }
__device__ __forceinline__ void mbar_wait(uint32_t a, uint32_t ph) {
  uint32_t ok; int it = 0;
#pragma unroll 1
  do {
    asm volatile("{.reg .pred p; mbarrier.try_wait.parity.shared::cta.b64 p, [%1], %2; selp.u32 %0,1,0,p;}" : "=r"(ok) : "r"(a), "r"(ph) : "memory");
  } while (!ok && ++it < (1 << 18));
}
__device__ __forceinline__ void tma2d(uint32_t dst, const CUtensorMap* m, int c0, int c1, uint32_t bar) {
  asm volatile("cp.async.bulk.tensor.2d.shared::cluster.global.mbarrier::complete_tx::bytes [%0], [%1, {%3,%4}], [%2];" ::"r"(dst), "l"(m), "r"(bar), "r"(c0), "r"(c1) : "memory");
}
__device__ __forceinline__ void tma2d_mc(uint32_t dst, const CUtensorMap* m, int c0, int c1, uint32_t bar) {
  asm volatile("cp.async.bulk.tensor.2d.shared::cluster.global.mbarrier::complete_tx::bytes.multicast::cluster [%0], [%1, {%3,%4}], [%2], %5;" ::"r"(dst), "l"(m), "r"(bar), "r"(c0), "r"(c1), "h"((uint16_t)3) : "memory");
}
__device__ __forceinline__ void cluster_arrive_relaxed() { asm volatile("barrier.cluster.arrive.relaxed.aligned;" ::: "memory"); }
__device__ __forceinline__ void cluster_wait() { asm volatile("barrier.cluster.wait.acquire.aligned;" ::: "memory"); }
__device__ __forceinline__ void wg_fence() { asm volatile("wgmma.fence.sync.aligned;" ::: "memory"); }
__device__ __forceinline__ void wg_commit() { asm volatile("wgmma.commit_group.sync.aligned;" ::: "memory"); }
template <int n> __device__ __forceinline__ void wg_wait() { asm volatile("wgmma.wait_group.sync.aligned %0;" ::"n"(n) : "memory"); }
__device__ __forceinline__ uint32_t ld_acquire(const uint32_t* p) { uint32_t v; asm volatile("ld.acquire.gpu.global.u32 %0, [%1];" : "=r"(v) : "l"(p) : "memory"); return v; }
__device__ __forceinline__ void flag_wait(const uint32_t* p, uint32_t target) {
  int it = 0;
#pragma unroll 1
  while ((int)(ld_acquire(p) - target) < 0 && ++it < (1 << 20)) __nanosleep(300);
}
__device__ __forceinline__ void hint_signal(uint32_t* p) {
  if ((threadIdx.x & 31) == 0) asm volatile("red.relaxed.gpu.global.add.u32 [%0], 1;" ::"l"(p) : "memory");
}
__device__ __forceinline__ void hint_wait(const uint32_t* p, uint32_t target, uint32_t ns = 400) {
  int it = 0; uint32_t v;
#pragma unroll 1
  do { asm volatile("ld.relaxed.gpu.global.u32 %0, [%1];" : "=r"(v) : "l"(p) : "memory"); if ((int)(v - target) >= 0) break; __nanosleep(ns); } while (++it < (1 << 20));
}
__device__ __forceinline__ uint32_t tag(uint32_t x, uint32_t par) { uint32_t r; asm("lop3.b32 %0, %1, 0xfffffffe, %2, 0xea;" : "=r"(r) : "r"(x), "r"(par)); return r; }
__device__ __forceinline__ void st_ll(uint4* p, uint32_t x, uint32_t y, uint32_t z, uint32_t w, uint32_t par) {
  asm volatile("{.reg .b64 a, b; mov.b64 a, {%1,%2}; mov.b64 b, {%3,%4}; st.relaxed.gpu.global.v2.b64 [%0], {a, b};}"
               ::"l"(p), "r"(tag(x, par)), "r"(y), "r"(tag(z, par)), "r"(w) : "memory");
}
__device__ __forceinline__ uint4 ld_ll(const uint4* p) {
  uint4 v;
  asm volatile("{.reg .b64 a, b; ld.relaxed.gpu.global.v2.b64 {a, b}, [%4]; mov.b64 {%0,%1}, a; mov.b64 {%2,%3}, b;}"
               : "=r"(v.x), "=r"(v.y), "=r"(v.z), "=r"(v.w) : "l"(p) : "memory");
  return v;
}
__device__ __forceinline__ void st_ll64(uint2* p, uint32_t x, uint32_t y, uint32_t par) {
  asm volatile("{.reg .b64 a; mov.b64 a, {%1,%2}; st.relaxed.gpu.global.b64 [%0], a;}" ::"l"(p), "r"(tag(x, par)), "r"(y) : "memory");
}
__device__ __forceinline__ uint2 ld_ca64(const void* p) {
  uint2 v;
  asm volatile("{.reg .b64 a; ld.global.ca.b64 a, [%2]; mov.b64 {%0,%1}, a;}" : "=r"(v.x), "=r"(v.y) : "l"(p) : "memory");
  return v;
}
__device__ __forceinline__ uint2 ld_ll64(const void* p) {
  uint2 v;
  asm volatile("{.reg .b64 a; ld.relaxed.gpu.global.b64 a, [%2]; mov.b64 {%0,%1}, a;}" : "=r"(v.x), "=r"(v.y) : "l"(p) : "memory");
  return v;
}
__device__ __forceinline__ void ll_chk(uint32_t& bad, uint32_t a, uint32_t b, uint32_t par) {
  uint32_t u; asm("lop3.b32 %0, %1, %2, %3, 0x7e;" : "=r"(u) : "r"(a), "r"(b), "r"(par));
  asm("or.b32 %0, %0, %1;" : "+r"(bad) : "r"(u));
}
__device__ __forceinline__ uint32_t hadd2(uint32_t a, uint32_t b) { uint32_t d; asm("add.rn.bf16x2 %0, %1, %2;" : "=r"(d) : "r"(a), "r"(b)); return d; }
__device__ __forceinline__ uint32_t hfma2(uint32_t a, uint32_t b, uint32_t c) { uint32_t d; asm("fma.rn.bf16x2 %0, %1, %2, %3;" : "=r"(d) : "r"(a), "r"(b), "r"(c)); return d; }
__device__ __forceinline__ uint32_t pack_bf16(float lo, float hi) { uint32_t r; asm("cvt.rn.bf16x2.f32 %0, %1, %2;" : "=r"(r) : "f"(hi), "f"(lo)); return r; }
__device__ __forceinline__ float bf_lo(uint32_t v) { return __uint_as_float(v << 16); }
__device__ __forceinline__ float bf_hi(uint32_t v) { return __uint_as_float(v & 0xffff0000u); }
__device__ __forceinline__ uint32_t movmat(uint32_t a) { uint32_t d; asm volatile("movmatrix.sync.aligned.m8n8.trans.b16 %0, %1;" : "=r"(d) : "r"(a)); return d; }
__device__ __forceinline__ void mma16816(float* c, uint32_t a0, uint32_t a1, uint32_t a2, uint32_t a3, uint32_t b0, uint32_t b1) {
  asm volatile("mma.sync.aligned.m16n8k16.row.col.f32.bf16.bf16.f32 {%0,%1,%2,%3}, {%4,%5,%6,%7}, {%8,%9}, {%0,%1,%2,%3};"
               : "+f"(c[0]), "+f"(c[1]), "+f"(c[2]), "+f"(c[3]) : "r"(a0), "r"(a1), "r"(a2), "r"(a3), "r"(b0), "r"(b1));
}
__device__ __forceinline__ uint4 ldcg128(const void* p) { uint4 v; asm volatile("ld.global.cg.v4.u32 {%0,%1,%2,%3}, [%4];" : "=r"(v.x), "=r"(v.y), "=r"(v.z), "=r"(v.w) : "l"(p) : "memory"); return v; }

template <int N> __device__ __forceinline__ void wgmma_ss(float* d, uint64_t da, uint64_t db, int sc);
template <int N> __device__ __forceinline__ void wgmma_rs(float* d, const uint32_t* a, uint64_t db, int sc);
template <> __device__ __forceinline__ void wgmma_ss<96>(float* d, uint64_t da, uint64_t db, int sc) {
  asm volatile("{.reg .pred p; setp.ne.b32 p, %50, 0; wgmma.mma_async.sync.aligned.m64n96k16.f32.bf16.bf16 {%0, %1, %2, %3, %4, %5, %6, %7, %8, %9, %10, %11, %12, %13, %14, %15, %16, %17, %18, %19, %20, %21, %22, %23, %24, %25, %26, %27, %28, %29, %30, %31, %32, %33, %34, %35, %36, %37, %38, %39, %40, %41, %42, %43, %44, %45, %46, %47}, %48, %49, p, 1, 1, 0, 1;}"
   : "+f"(d[0]), "+f"(d[1]), "+f"(d[2]), "+f"(d[3]), "+f"(d[4]), "+f"(d[5]), "+f"(d[6]), "+f"(d[7]), "+f"(d[8]), "+f"(d[9]), "+f"(d[10]), "+f"(d[11]), "+f"(d[12]), "+f"(d[13]), "+f"(d[14]), "+f"(d[15]), "+f"(d[16]), "+f"(d[17]), "+f"(d[18]), "+f"(d[19]), "+f"(d[20]), "+f"(d[21]), "+f"(d[22]), "+f"(d[23]), "+f"(d[24]), "+f"(d[25]), "+f"(d[26]), "+f"(d[27]), "+f"(d[28]), "+f"(d[29]), "+f"(d[30]), "+f"(d[31]), "+f"(d[32]), "+f"(d[33]), "+f"(d[34]), "+f"(d[35]), "+f"(d[36]), "+f"(d[37]), "+f"(d[38]), "+f"(d[39]), "+f"(d[40]), "+f"(d[41]), "+f"(d[42]), "+f"(d[43]), "+f"(d[44]), "+f"(d[45]), "+f"(d[46]), "+f"(d[47]) : "l"(da), "l"(db), "r"(sc));
}
template <> __device__ __forceinline__ void wgmma_ss<192>(float* d, uint64_t da, uint64_t db, int sc) {
  asm volatile("{.reg .pred p; setp.ne.b32 p, %98, 0; wgmma.mma_async.sync.aligned.m64n192k16.f32.bf16.bf16 {%0, %1, %2, %3, %4, %5, %6, %7, %8, %9, %10, %11, %12, %13, %14, %15, %16, %17, %18, %19, %20, %21, %22, %23, %24, %25, %26, %27, %28, %29, %30, %31, %32, %33, %34, %35, %36, %37, %38, %39, %40, %41, %42, %43, %44, %45, %46, %47, %48, %49, %50, %51, %52, %53, %54, %55, %56, %57, %58, %59, %60, %61, %62, %63, %64, %65, %66, %67, %68, %69, %70, %71, %72, %73, %74, %75, %76, %77, %78, %79, %80, %81, %82, %83, %84, %85, %86, %87, %88, %89, %90, %91, %92, %93, %94, %95}, %96, %97, p, 1, 1, 0, 1;}"
   : "+f"(d[0]), "+f"(d[1]), "+f"(d[2]), "+f"(d[3]), "+f"(d[4]), "+f"(d[5]), "+f"(d[6]), "+f"(d[7]), "+f"(d[8]), "+f"(d[9]), "+f"(d[10]), "+f"(d[11]), "+f"(d[12]), "+f"(d[13]), "+f"(d[14]), "+f"(d[15]), "+f"(d[16]), "+f"(d[17]), "+f"(d[18]), "+f"(d[19]), "+f"(d[20]), "+f"(d[21]), "+f"(d[22]), "+f"(d[23]), "+f"(d[24]), "+f"(d[25]), "+f"(d[26]), "+f"(d[27]), "+f"(d[28]), "+f"(d[29]), "+f"(d[30]), "+f"(d[31]), "+f"(d[32]), "+f"(d[33]), "+f"(d[34]), "+f"(d[35]), "+f"(d[36]), "+f"(d[37]), "+f"(d[38]), "+f"(d[39]), "+f"(d[40]), "+f"(d[41]), "+f"(d[42]), "+f"(d[43]), "+f"(d[44]), "+f"(d[45]), "+f"(d[46]), "+f"(d[47]), "+f"(d[48]), "+f"(d[49]), "+f"(d[50]), "+f"(d[51]), "+f"(d[52]), "+f"(d[53]), "+f"(d[54]), "+f"(d[55]), "+f"(d[56]), "+f"(d[57]), "+f"(d[58]), "+f"(d[59]), "+f"(d[60]), "+f"(d[61]), "+f"(d[62]), "+f"(d[63]), "+f"(d[64]), "+f"(d[65]), "+f"(d[66]), "+f"(d[67]), "+f"(d[68]), "+f"(d[69]), "+f"(d[70]), "+f"(d[71]), "+f"(d[72]), "+f"(d[73]), "+f"(d[74]), "+f"(d[75]), "+f"(d[76]), "+f"(d[77]), "+f"(d[78]), "+f"(d[79]), "+f"(d[80]), "+f"(d[81]), "+f"(d[82]), "+f"(d[83]), "+f"(d[84]), "+f"(d[85]), "+f"(d[86]), "+f"(d[87]), "+f"(d[88]), "+f"(d[89]), "+f"(d[90]), "+f"(d[91]), "+f"(d[92]), "+f"(d[93]), "+f"(d[94]), "+f"(d[95]) : "l"(da), "l"(db), "r"(sc));
}

__device__ __forceinline__ uint64_t desc64(uint32_t lo, uint32_t hi) { uint64_t d; asm("mov.b64 %0, {%1, %2};" : "=l"(d) : "r"(lo), "r"(hi)); return d; }
constexpr uint32_t DESC_HI = (1024u >> 4) | (1u << 30);
constexpr uint32_t DESC_HI64 = (512u >> 4) | (2u << 30);
template <int n> __device__ __forceinline__ void fence_regs(float* a) {
#pragma unroll
  for (int i = 0; i < n; i++) asm volatile("" : "+f"(a[i])::"memory");
}

struct Ctx {
  uint32_t full;
  uint32_t emb;
  bool sig;
  uint32_t stage, phase, prev;
  uint32_t dB, dA;
  __device__ __forceinline__ void release_prev() { if (sig && prev != ~0u) mbar_arrive_cl(emb + prev); }
  __device__ __forceinline__ void wait_full() {
    mbar_wait(full + 8 * stage, phase);
    wg_fence();
  }
};

__device__ __forceinline__ void issue192(float* acc, Ctx& c, int s, bool first = false) {
  c.wait_full();
  const uint32_t db = c.dB + c.stage * (STAGE_BYTES >> 4);
  const uint32_t da = c.dA + (s >> 1) * 1024 + (s & 1) * 4;
  wgmma_ss<192>(acc, desc64(da, DESC_HI), desc64(db, DESC_HI), first ? 0 : 1);
  wgmma_ss<192>(acc, desc64(da + 2, DESC_HI), desc64(db + 128, DESC_HI), 1);
  wg_commit();
}
__device__ __forceinline__ void issue96(float* acc, Ctx& c, int s, bool first) {
  c.wait_full();
  const uint32_t db = c.dB + c.stage * (STAGE_BYTES >> 4);
  const uint32_t da = c.dA + s * 1024;
  if (first) { wgmma_ss<192>(acc, desc64(da, DESC_HI), desc64(db, DESC_HI64), 0); wg_fence(); }
#pragma unroll
  for (int kk = first ? 1 : 0; kk < 4; kk++) wgmma_ss<96>(acc, desc64(da + 2 * kk, DESC_HI), desc64(db + 64 * kk, DESC_HI64), 1);
  wg_commit();
}
__device__ __forceinline__ void retire(Ctx& c) {
  wg_wait<1>();
  c.release_prev();
  c.prev = 8 * c.stage;
  if (++c.stage == NSTAGE) { c.stage = 0; c.phase ^= 1; }
}
constexpr float GK = 0.32920349f;
__device__ __forceinline__ uint32_t gelu_pair(uint32_t y) {
  uint32_t u, th;
  asm("mul.rn.bf16x2 %0, %1, %2;" : "=r"(u) : "r"(hfma2(y, y, 0x401b401bu)), "r"(y));
  asm("tanh.approx.bf16x2 %0, %1;" : "=r"(th) : "r"(u));
  return hfma2(y, th, y);
}
__device__ __forceinline__ uint4 gelu_group(const uint32_t* a) { return make_uint4(gelu_pair(a[0]), gelu_pair(a[1]), gelu_pair(a[2]), gelu_pair(a[3])); }
__device__ __forceinline__ void lds_bias(float2* b, uint32_t addr) {
#pragma unroll
  for (int j = 0; j < 4; j++) asm volatile("ld.shared.v2.f32 {%0,%1}, [%2];" : "=f"(b[j].x), "=f"(b[j].y) : "r"(addr + 32 * j));
}
__device__ __forceinline__ int opaque(int v) { asm volatile("" : "+r"(v)); return v; }
__device__ __forceinline__ void stsm4(uint32_t addr, uint4 r) {
  asm volatile("stmatrix.sync.aligned.m8n8.x4.shared.b16 [%0], {%1,%2,%3,%4};" ::"r"(addr), "r"(r.x), "r"(r.y), "r"(r.z), "r"(r.w) : "memory");
}
__device__ __forceinline__ float ex2f(float x) { float r; asm("ex2.approx.ftz.f32 %0, %1;" : "=f"(r) : "f"(x)); return r; }
__device__ __forceinline__ uint32_t phi_pack(uint32_t tp, float a0, float a1) {
  uint32_t x, y;
  asm("max.bf16x2 %0, %1, %2;" : "=r"(x) : "r"(tp), "r"(0x35863586u));
  asm("min.bf16x2 %0, %1, %2;" : "=r"(y) : "r"(pack_bf16(ex2f(a0), ex2f(a1))), "r"(0x3f803f80u));
  return hadd2(x, y);
}
template <int q0, int q1>
__device__ __forceinline__ void part_groups(const float* a, uint4* p, uint32_t par) {
#pragma unroll
  for (int q = q0; q < q1; q++)
    st_ll(p + q * 32, pack_bf16(a[8 * q], a[8 * q + 1]), pack_bf16(a[8 * q + 2], a[8 * q + 3]), pack_bf16(a[8 * q + 4], a[8 * q + 5]), pack_bf16(a[8 * q + 6], a[8 * q + 7]), par);
}
__device__ __forceinline__ float rcpf(float x) { float r; asm("rcp.approx.ftz.f32 %0, %1;" : "=f"(r) : "f"(x)); return r; }
__device__ __forceinline__ float silu(float y) { return y * rcpf(1.f + ex2f(y * -1.4426950408889634f)); }
__device__ __forceinline__ uint32_t gate_word(uint32_t w0, uint32_t w1, uint32_t w2, uint32_t w3, uint32_t w4, uint32_t w5, uint32_t w6, uint32_t w7, uint32_t bb) {
  const uint32_t u0 = hadd2(hadd2(w0, w1), hadd2(w2, w3)), u1 = hadd2(hadd2(w4, w5), hadd2(w6, w7));
  return pack_bf16(silu(fmaf(bf_lo(u0) + bf_lo(u1), 0.5f / GK, bf_lo(bb))), silu(fmaf(bf_hi(u0) + bf_hi(u1), 0.5f / GK, bf_hi(bb))));
}
__device__ __forceinline__ uint4 gate_vec(const uint4* p, uint32_t b0, uint32_t b1) {
  return make_uint4(gate_word(p[0].x, p[1].x, p[2].x, p[3].x, p[4].x, p[5].x, p[6].x, p[7].x, b0), gate_word(p[0].y, p[1].y, p[2].y, p[3].y, p[4].y, p[5].y, p[6].y, p[7].y, b0),
                    gate_word(p[0].z, p[1].z, p[2].z, p[3].z, p[4].z, p[5].z, p[6].z, p[7].z, b1), gate_word(p[0].w, p[1].w, p[2].w, p[3].w, p[4].w, p[5].w, p[6].w, p[7].w, b1));
}
__device__ __forceinline__ int pairoff(int p, int g) { return (p >> 2) * 32 + g * 4 + (p & 3); }
template <bool STRONG> __device__ __forceinline__ void d1_load(uint32_t* W, int rb0, int head, int ln) {
  const uint2* qf = g_qkv + rb0 * 216 * 32 + pairoff(288 + head * 9 + (ln & 3), ln >> 2);
#pragma unroll
  for (int b = 0; b < 3; b++) {
#pragma unroll
    for (int j = 0; j < 4; j++) {
      const uint2* p = qf + j * 216 * 32 + 32 * b;
      const uint2 kk = STRONG ? ld_ll64(p) : ld_ca64(p), vv = STRONG ? ld_ll64(p + 72 * 32) : ld_ca64(p + 72 * 32);
      W[6 * j + 2 * b] = kk.x; W[6 * j + 2 * b + 1] = kk.y; W[24 + 6 * j + 2 * b] = vv.x; W[24 + 6 * j + 2 * b + 1] = vv.y;
    }
  }
}
__device__ __forceinline__ bool d1_bad(const uint32_t* W, int t, uint32_t par) {
  uint32_t bad = 0, bad2 = 0;
#pragma unroll
  for (int q = 0; q < 12; q++) ll_chk((q % 3) != 2 ? bad : bad2, W[2 * q], W[24 + 2 * q], par);
  return __any_sync(0xffffffffu, (bad | (t == 0 ? bad2 : 0u)) & 1);
}
__device__ __forceinline__ void d1_mov(uint32_t* W, int j, int t) {
  if (t != 0) { W[6 * j + 4] = W[6 * j + 5] = 0u; W[24 + 6 * j + 4] = W[24 + 6 * j + 5] = (t == 1 ? 0x00003f80u : 0u); }
#pragma unroll
  for (int q = 0; q < 6; q++) { W[6 * j + q] = movmat(W[6 * j + q]); W[24 + 6 * j + q] = movmat(W[24 + 6 * j + q]); }
}
__device__ __forceinline__ void d1_mma(const uint32_t* W, float* R) {
  float c1[3][4];
#pragma unroll
  for (int j = 0; j < 12; j++) { R[j] = 0.f; c1[j >> 2][j & 3] = 0.f; }
#pragma unroll
  for (int ks = 0; ks < 4; ks++)
#pragma unroll
    for (int j = 0; j < 3; j++) {
      mma16816(R + 4 * j, W[24 + 6 * ks], W[24 + 6 * ks + 2], W[24 + 6 * ks + 1], W[24 + 6 * ks + 3], W[6 * ks + 2 * j], W[6 * ks + 2 * j + 1]);
      mma16816(c1[j], W[24 + 6 * ks + 4], 0u, W[24 + 6 * ks + 5], 0u, W[6 * ks + 2 * j], W[6 * ks + 2 * j + 1]);
    }
#pragma unroll
  for (int j = 0; j < 3; j++) { R[12 + 2 * j] = c1[j][0]; R[13 + 2 * j] = c1[j][1]; }
}
__device__ __forceinline__ bool kv_valid(int w, int ln) { return (w < 3 || ln < 12) && ((w != 2 && w != 4) || (ln & 3) == 0); }

struct Params {
  CUtensorMap tm_wqkv, tm_w1, tm_w2, tm_m, tm_wqkv64, tm_m64, tm_a, tm_ast;
  const __nv_bfloat16 *x, *b1, *b2, *wqkv, *w1, *w2, *wo;
  __nv_bfloat16* out;
};

__global__ void __cluster_dims__(2, 1, 1) __launch_bounds__(NTHREADS, 1) fused_kernel(const __grid_constant__ Params P) {
  extern __shared__ __align__(1024) uint8_t smem[];
  const uint32_t sbase = smem_u32(smem);
  const int tid = threadIdx.x, lane = tid & 31;
  const int warp = __shfl_sync(0xffffffffu, tid >> 5, 0);
  const int g = lane >> 2, t = lane & 3;
  const uint32_t ep = __shfl_sync(0xffffffffu, g_epoch[blockIdx.x], 0) + 1;
  const uint32_t par = ep & 1;
  STAMPW(0, 0);

  if (blockIdx.x >= 128) {
    const int a = blockIdx.x - 128;
    constexpr int WP = 1168, SM_T = 152 * WP, SM_HB = SM_T + 8 * 32 * 80;
    if (tid == 0) {
      mbar_init(sbase + SM_HB, 1);
      asm volatile("fence.mbarrier_init.release.cluster;" ::: "memory");
      mbar_expect(sbase + SM_HB, 144 * 1152);
    }
    for (int i = tid; i < (8 * WP + 8 * 32 * 80) / 4; i += NTHREADS) reinterpret_cast<uint32_t*>(smem + 144 * WP)[i] = 0u;
    __syncthreads();
    __nanosleep(1500);
    if (tid < 144)
      asm volatile("cp.async.bulk.shared::cluster.global.mbarrier::complete_tx::bytes [%0], [%1], %2, [%3];" ::"r"(sbase + tid * WP), "l"(P.wo + (a * 144 + tid) * D_), "r"(1152), "r"(sbase + SM_HB) : "memory");
    if (warp >= 8 && lane == 0) {
      const int id = a * 4 + (warp - 8);
      constexpr uint32_t CH = 9216 * 2;
#pragma unroll 1
      for (int i = id; i < 576; i += 16) {
        const char* p = i < 288 ? (const char*)P.w1 + (size_t)i * CH : (const char*)P.w2 + (size_t)(i - 288) * CH;
        asm volatile("cp.async.bulk.prefetch.L2.global [%0], %1;" ::"l"(p), "r"(CH) : "memory");
      }
    }
    __syncwarp();
    if (lane < 8) hint_wait(&g_f_kvp[a * 8 + lane], 16 * ep, 50);
    __syncwarp();
    STAMPW(0, 1);
#pragma unroll 1
    for (int u = warp; u < 40; u += 12) {
      const int hh = u & 7, w = 4 - (u >> 3), head = a * 8 + hh;
      uint4 v[16];
      int tries = 0;
      uint32_t bad;
      const bool val = kv_valid(w, lane);
#pragma unroll 1
      do {
        bad = 0;
#pragma unroll
        for (int j = 0; j < 16; j++) v[j] = val ? ld_ll(&g_kvp[((head * 5 + w) * 16 + j) * 32 + lane]) : make_uint4(par, 0u, par, 0u);
#pragma unroll
        for (int j = 0; j < 16; j++) ll_chk(bad, v[j].x, v[j].z, par);
      } while (__any_sync(0xffffffffu, bad & 1) && ++tries < (1 << 20));
      float s0 = 0.f, s1 = 0.f, s2 = 0.f, s3 = 0.f;
#pragma unroll
      for (int j = 0; j < 16; j++) { s0 += __uint_as_float(v[j].x); s1 += __uint_as_float(v[j].y); s2 += __uint_as_float(v[j].z); s3 += __uint_as_float(v[j].w); }
      if (w >= 3) {
        if (g == 2) st_ll(&g_z[(head * 2 + w - 3) * 4 + t], __float_as_uint(s0), __float_as_uint(s1), __float_as_uint(s2), __float_as_uint(s3), par);
        __syncwarp();
        hint_signal(&g_f_z[head]);
      }
      const int e0 = w < 3 ? g : 16 + g, e1 = w < 3 ? g + 8 : 16 + g, d0 = (w < 3 ? 8 * w : (w == 3 ? 0 : 16)) + 2 * t, d1 = w < 3 ? d0 : d0 + 8;
      __nv_bfloat16* T = reinterpret_cast<__nv_bfloat16*>(smem + SM_T) + hh * 32 * 40;
      if (e0 < 18) {
        T[d0 * 40 + e0] = __float2bfloat16(s0); T[(d0 + 1) * 40 + e0] = __float2bfloat16(s1);
        T[d1 * 40 + e1] = __float2bfloat16(s2); T[(d1 + 1) * 40 + e1] = __float2bfloat16(s3);
      }
    }
    __syncthreads();
    STAMPW(0, 2);
    mbar_wait(sbase + SM_HB, 0);
#pragma unroll 1
    for (int u = warp; u < 24; u += 12) {
      const int hh = u / 3, c0 = (u % 3) * 192;
      const uint32_t* T = reinterpret_cast<const uint32_t*>(smem + SM_T) + hh * 32 * 20 + g * 20 + t;
      const uint32_t a00 = T[0], a01 = T[160], a02 = T[4], a03 = T[164], a10 = T[8], a11 = T[168], b00 = T[320], b02 = T[324], b10 = T[328];
      const uint32_t rowa = sbase + (hh * 18 + (lane & 15)) * WP + (c0 + (lane >> 4) * 8) * 2, rowb = sbase + (hh * 18 + 16 + (lane & 7)) * WP + (c0 + ((lane >> 3) & 1) * 8) * 2;
#pragma unroll 3
      for (int j = 0; j < 12; j++) {
        uint32_t w0, w1, w2, w3, w4, w5;
        asm volatile("ldmatrix.sync.aligned.m8n8.x4.trans.shared.b16 {%0,%1,%2,%3}, [%4];" : "=r"(w0), "=r"(w1), "=r"(w2), "=r"(w3) : "r"(rowa + j * 32));
        asm volatile("ldmatrix.sync.aligned.m8n8.x2.trans.shared.b16 {%0,%1}, [%2];" : "=r"(w4), "=r"(w5) : "r"(rowb + j * 32));
        float p[4][4];
#pragma unroll
        for (int q = 0; q < 4; q++) p[q][0] = p[q][1] = p[q][2] = p[q][3] = 0.f;
        mma16816(p[0], a00, a01, a02, a03, w0, w1); mma16816(p[1], a00, a01, a02, a03, w2, w3);
        mma16816(p[2], b00, 0u, b02, 0u, w0, w1); mma16816(p[3], b00, 0u, b02, 0u, w2, w3);
        mma16816(p[0], a10, a11, 0u, 0u, w4, 0u); mma16816(p[1], a10, a11, 0u, 0u, w5, 0u);
        mma16816(p[2], b10, 0u, 0u, 0u, w4, 0u); mma16816(p[3], b10, 0u, 0u, 0u, w5, 0u);
        stsm4(rowa + j * 32, make_uint4(pack_bf16(p[0][0], p[0][1]), pack_bf16(p[0][2], p[0][3]), pack_bf16(p[1][0], p[1][1]), pack_bf16(p[1][2], p[1][3])));
        if (g < 2) {
          uint32_t* r = reinterpret_cast<uint32_t*>(smem + (hh * 18 + 16 + g) * WP + (c0 + j * 16 + 2 * t) * 2);
          r[0] = pack_bf16(p[2][0], p[2][1]); r[4] = pack_bf16(p[3][0], p[3][1]);
        }
      }
      asm volatile("fence.proxy.async.shared::cta;" ::: "memory");
      __syncwarp();
      if (lane < 18) {
        asm volatile("cp.async.bulk.global.shared::cta.bulk_group [%0], [%1], %2;" ::"l"(g_m + (a * 144 + hh * 18 + lane) * D_ + c0), "r"(sbase + (hh * 18 + lane) * WP + c0 * 2), "r"(384) : "memory");
        asm volatile("cp.async.bulk.commit_group;" ::: "memory");
      }
    }
    asm volatile("cp.async.bulk.wait_group 0;" ::: "memory");
    asm volatile("fence.proxy.async.global;" ::: "memory");
    __syncwarp();
    if (lane == 0) asm volatile("red.release.gpu.global.add.u32 [%0], 1;" ::"l"(g_f_m) : "memory");
    STAMPW(0, 3);
    __syncthreads();
    if (tid == 0) g_epoch[blockIdx.x] = ep;
    return;
  }

  const int cl = blockIdx.x >> 1, rank = blockIdx.x & 1;
  const int f = cl & 7, m = (cl >> 3) * 2 + rank;
  const int srole = f >= 6 ? 1 : 0;
  const uint32_t bar_full = sbase + SM_BAR, bar_empty = bar_full + 8 * NSTAGE, bar_xfree = bar_empty + 8 * NSTAGE, bar_ofull = bar_xfree + 72,
                 bar_d = bar_ofull + 72;

  if (tid == 0) {
#pragma unroll 1
    for (int i = 0; i < NSTAGE; i++) { mbar_init(bar_full + 8 * i, 1); mbar_init(bar_empty + 8 * i, 4); }
#pragma unroll 1
    for (int i = 0; i < 9; i++) { mbar_init(bar_xfree + 8 * i, 2); mbar_init(bar_ofull + 8 * i, 1); }
    mbar_init(bar_d, 1);
    asm volatile("fence.mbarrier_init.release.cluster;" ::: "memory");
  }
  __syncwarp();
  cluster_arrive_relaxed();

  if (warp >= 8) {
    const int srow = m * 128 + f * 16 + (warp - 8) * 4 + (lane >> 3);
    uint4 xs[9];
#pragma unroll
    for (int kb = 0; kb < 9; kb++) xs[kb] = __ldg(reinterpret_cast<const uint4*>(P.x + srow * D_) + (lane & 7) + kb * 8);
    auto stats = [&]() {
      const uint32_t* w = reinterpret_cast<const uint32_t*>(xs);
      float s0 = 0.f, s1 = 0.f;
#pragma unroll
      for (int i = 0; i < 36; i++) { s0 += bf_lo(w[i]); s1 += bf_hi(w[i]); }
      float sum = s0 + s1;
      sum += __shfl_xor_sync(0xffffffffu, sum, 1); sum += __shfl_xor_sync(0xffffffffu, sum, 2); sum += __shfl_xor_sync(0xffffffffu, sum, 4);
      const float mean = sum * (1.f / 576.f);
      s0 = 0.f; s1 = 0.f;
#pragma unroll
      for (int i = 0; i < 36; i++) { const float a = bf_lo(w[i]) - mean, b = bf_hi(w[i]) - mean; s0 = fmaf(a, a, s0); s1 = fmaf(b, b, s1); }
      float sq = s0 + s1;
      sq += __shfl_xor_sync(0xffffffffu, sq, 1); sq += __shfl_xor_sync(0xffffffffu, sq, 2); sq += __shfl_xor_sync(0xffffffffu, sq, 4);
      const float rstd = rsqrtf(sq * (1.f / 576.f) + 1e-5f);
      if ((lane & 7) == 0)
        st_ll64(&g_stat[srow], __float_as_uint(rstd), pack_bf16(-mean, -mean), par);
    };
    stats();
    asm volatile("setmaxnreg.dec.sync.aligned.u32 40;");
    cluster_wait();
    if (warp == 8) {
      if (lane == 0) {
        uint32_t stage = 0, phase = 1;
        const uint32_t sb = sbase + SM_B;
#pragma unroll 1
        for (int tl = 2 * srole; tl < 8 + 2 * srole; tl++) {
          const CUtensorMap* map = tl == 0 ? &P.tm_wqkv : (tl == 1 ? &P.tm_wqkv64 : (tl < 5 ? &P.tm_w1 : (tl < 8 ? &P.tm_w2 : (tl == 8 ? &P.tm_m : &P.tm_m64))));
          const int col = tl < 2 ? 288 * f + 192 * tl : (tl < 5 ? 576 * f + 192 * (tl - 2) : (tl < 8 ? 192 * (tl - 5) : (tl == 8 ? 192 * (f - 5) : 96 * (f - 6))));
          const bool perm = tl >= 5 && tl < 8;
          const bool z = (tl & 7) == 1;
          if (tl == 8) { flag_wait(g_f_m, 48 * ep); asm volatile("fence.proxy.async.global;" ::: "memory"); }
          const int cs = z ? 32 : 64, rs = z ? 64 : 32, nst = z ? 9 : 18;
#pragma unroll 1
          for (int st = 0; st < nst; st++) {
            int row = st * rs;
            if (perm) row += 576 * f + ((st < 6) ? 192 : (st < 12 ? -192 : 0));
            mbar_wait(bar_empty + 8 * stage, phase);
            mbar_expect(bar_full + 8 * stage, 12288);
            const uint32_t dst = sb + stage * STAGE_BYTES;
            if (((st ^ rank) & 1) == 0) {
              tma2d_mc(dst, map, col, row, bar_full + 8 * stage);
              tma2d_mc(dst + 8192, map, col + 2 * cs, row, bar_full + 8 * stage);
            } else {
              tma2d_mc(dst + 4096, map, col + cs, row, bar_full + 8 * stage);
            }
            if (++stage == NSTAGE) { stage = 0; phase ^= 1; }
          }
        }
      }
      __syncwarp();
    } else {
      const int aw = warp - 9;
      const int hi = f >> 2;
      if (aw == 0) {
        if (lane < 2) hint_wait(&g_f_qkv[m * 8 + 2 + 2 * lane + hi], 16 * ep, 200);
        __syncwarp();
        if (lane == 0) mbar_arrive(bar_d);
        STAMP(20);
      }
      if (lane < 5) hint_wait(lane < 4 ? &g_f_z[4 * f + lane] : &g_f_qkv[m * 8 + hi], lane < 4 ? 2 * ep : 16 * ep);
      __syncwarp();
      STAMPW(9, 22);
      uint32_t* stg = reinterpret_cast<uint32_t*>(smem + SM_SCR + aw * 2304);
#pragma unroll 1
      for (int u = aw * 2; u < 16; u += (u & 1) ? 5 : 1) {
        const int rbl = u >> 1, hp = (u & 1) * 2;
        const uint2* qf = g_qkv + (m * 8 + rbl) * 216 * 32;
        const uint2* zp = reinterpret_cast<const uint2*>(&g_z[(4 * f + hp) * 8 + t]);
        uint2 q[2][3];
        float d[4];
        int tries = 0;
        uint32_t bad;
#pragma unroll 1
        do {
          bad = tries ? ld_acquire(g_f_m) & 0u : 0u;
#pragma unroll
          for (int j = 0; j < 2; j++)
#pragma unroll
            for (int b = 0; b < 3; b++) q[j][b] = ld_ca64(qf + pairoff((4 * f + hp + j) * 9 + t, g) + 32 * b);
#pragma unroll
          for (int j = 0; j < 2; j++) {
            const uint2 z0 = ld_ca64(zp + 16 * j), z1 = ld_ca64(zp + 16 * j + 1), z2 = ld_ca64(zp + 16 * j + 8);
            if (t != 0) q[j][2] = make_uint2(par, 0u);
            ll_chk(bad, z0.x, z1.x, par); ll_chk(bad, z2.x, q[j][2].x, par); ll_chk(bad, q[j][0].x, q[j][1].x, par);
            d[2 * j] = bf_lo(q[j][0].x) * __uint_as_float(z0.x) + bf_hi(q[j][0].x) * __uint_as_float(z0.y) + bf_lo(q[j][1].x) * __uint_as_float(z1.x) + bf_hi(q[j][1].x) * __uint_as_float(z1.y) +
                       bf_lo(q[j][2].x) * __uint_as_float(z2.x) + bf_hi(q[j][2].x) * __uint_as_float(z2.y);
            d[2 * j + 1] = bf_lo(q[j][0].y) * __uint_as_float(z0.x) + bf_hi(q[j][0].y) * __uint_as_float(z0.y) + bf_lo(q[j][1].y) * __uint_as_float(z1.x) + bf_hi(q[j][1].y) * __uint_as_float(z1.y) +
                           bf_lo(q[j][2].y) * __uint_as_float(z2.x) + bf_hi(q[j][2].y) * __uint_as_float(z2.y);
          }
        } while (__any_sync(0xffffffffu, bad & 1) && ++tries < (1 << 20));
#pragma unroll
        for (int j = 0; j < 4; j++) d[j] += __shfl_xor_sync(0xffffffffu, d[j], 1);
#pragma unroll
        for (int j = 0; j < 4; j++) d[j] = rcpf(d[j] + __shfl_xor_sync(0xffffffffu, d[j], 2) + 1e-6f);
        if (hp == 0) { asm volatile("cp.async.bulk.wait_group.read 0;" ::: "memory"); __syncwarp(); }
#pragma unroll
        for (int j = 0; j < 2; j++) {
          const uint32_t r0 = pack_bf16(d[2 * j], d[2 * j]), r1 = pack_bf16(d[2 * j + 1], d[2 * j + 1]);
#pragma unroll
          for (int b = 0; b < 3; b++)
            if (b < 2 || t == 0) {
              stg[g * 36 + (hp + j) * 9 + 4 * b + t] = hfma2(q[j][b].x, r0, 0x80008000u);
              stg[(g + 8) * 36 + (hp + j) * 9 + 4 * b + t] = hfma2(q[j][b].y, r1, 0x80008000u);
            }
        }
        if (hp != 0) {
          asm volatile("fence.proxy.async.shared::cta;" ::: "memory");
          __syncwarp();
          if (lane == 0) {
            asm volatile("cp.async.bulk.tensor.2d.global.shared::cta.bulk_group [%0, {%2, %3}], [%1];" ::"l"(&P.tm_ast), "r"(smem_u32(stg)), "r"(72 * f), "r"(m * 128 + rbl * 16) : "memory");
            asm volatile("cp.async.bulk.commit_group;" ::: "memory");
          }
        }
      }
      asm volatile("cp.async.bulk.wait_group 0;" ::: "memory");
      asm volatile("fence.proxy.async.global;" ::: "memory");
      STAMPW(9, 26);
      asm volatile("bar.sync 5, 96;" ::: "memory");
      if (tid == 288) asm volatile("red.release.gpu.global.add.u32 [%0], 1;" ::"l"(&g_f_a[m]) : "memory");
      __syncwarp();
      STAMPW(9, 23);
      if (srole && aw == 2) {
        if (lane == 0) {
          flag_wait(&g_f_a[m], 8 * ep);
          asm volatile("fence.proxy.async.global;" ::: "memory");
#pragma unroll 1
          for (int kb = 0; kb < 9; kb++) {
            mbar_wait(bar_xfree + 8 * kb, 0);
            mbar_expect(bar_ofull + 8 * kb, 16384);
            tma2d(sbase + SM_A + kb * 16384, &P.tm_a, kb * 64, m * 128, bar_ofull + 8 * kb);
          }
        }
        __syncwarp();
      }
    }
    cluster_arrive_relaxed();
    cluster_wait();
  } else {
    const int wg = warp >> 2;
    {
      const int rs = lane >> 3, j = lane & 7;
      uint4 xv[4][9];
#pragma unroll
      for (int it = 0; it < 4; it++)
#pragma unroll
        for (int kb = 0; kb < 9; kb++) xv[it][kb] = __ldg(reinterpret_cast<const uint4*>(P.x + (m * 128 + warp * 16 + it * 4 + rs) * D_) + j + kb * 8);
      uint32_t bw0 = __ldg(reinterpret_cast<const uint32_t*>(P.b1 + 576 * f) + tid), bw1 = tid < 32 ? __ldg(reinterpret_cast<const uint32_t*>(P.b1 + 576 * f) + 256 + tid) : 0u;
      uint2 st[4];
      int tries = 0;
      uint32_t bad;
#pragma unroll 1
      do {
        bad = 0;
#pragma unroll
        for (int it = 0; it < 4; it++) st[it] = ld_ll64(&g_stat[m * 128 + warp * 16 + it * 4 + rs]);
        ll_chk(bad, st[0].x, st[1].x, par); ll_chk(bad, st[2].x, st[3].x, par);
      } while (__any_sync(0xffffffffu, bad & 1) && ++tries < (1 << 22));
      STAMPW(0, 19);
#pragma unroll
      for (int it = 0; it < 4; it++) {
        const uint32_t nm = st[it].y;
        uint8_t* dst = smem + SM_A + (warp * 16 + it * 4 + rs) * 128 + ((j ^ ((it * 4 + rs) & 7)) << 4);
#pragma unroll
        for (int kb = 0; kb < 9; kb++) {
          const uint4 w = xv[it][kb];
          *reinterpret_cast<uint4*>(dst + kb * 16384) = make_uint4(hadd2(w.x, nm), hadd2(w.y, nm), hadd2(w.z, nm), hadd2(w.w, nm));
        }
        if (j == 0) reinterpret_cast<uint32_t*>(smem + SM_RSTD)[warp * 16 + it * 4 + rs] = st[it].x;
      }
      reinterpret_cast<float2*>(smem + SM_BIAS)[tid] = make_float2(bf_lo(bw0) * GK, bf_hi(bw0) * GK);
      if (tid < 32) reinterpret_cast<float2*>(smem + SM_BIAS)[256 + tid] = make_float2(bf_lo(bw1) * GK, bf_hi(bw1) * GK);
      asm volatile("fence.proxy.async.shared::cta;" ::: "memory");
    }
    asm volatile("setmaxnreg.inc.sync.aligned.u32 232;");
    cluster_wait();
    asm volatile("bar.sync 1, 256;" ::: "memory");
    STAMPW(0, 1);
    Ctx c;
    c.full = bar_full;
    c.emb = __shfl_sync(0xffffffffu, mapa(bar_empty, (warp & 3) == 0 ? rank : (rank ^ 1)), 0);
    c.sig = lane == 0 && (warp & 3) < 2;
    c.stage = 0; c.phase = 0; c.prev = ~0u;
    c.dB = (((sbase + SM_B) & 0x3FFFF) >> 4) | ((4096u >> 4) << 16);
    c.dA = (((sbase + SM_A + wg * 8192) & 0x3FFFF) >> 4) | (1u << 16);
    const bool leader = (lane == 0) && ((warp & 3) == 0);

    const int rb = m * 8 + warp;
    const uint32_t bias_t = sbase + SM_BIAS + 8 * t;
    const uint32_t hst = sbase + SM_A + (warp * 16 + (lane & 7) + ((lane >> 3) & 1) * 8) * 128 + (((lane >> 4) ^ (lane & 7)) << 4);
    auto wg_sync = [&]() {
      asm volatile("fence.proxy.async.shared::cta;" ::: "memory");
      if (wg == 0) asm volatile("bar.sync 2, 128;" ::: "memory"); else asm volatile("bar.sync 3, 128;" ::: "memory");
    };
    float A[96], B[96];
#pragma unroll
    for (int i = 0; i < 96; i++) B[i] = 0.f;
#define GELU16(H0, H1, ACC, OFF) uint32_t E[8]; \
    _Pragma("unroll") for (int q = 0; q < 8; q++) E[q] = pack_bf16(fmaf(ACC[(OFF) + 2 * q], (q & 1) ? r1 : r0, bs[q >> 1].x), fmaf(ACC[(OFF) + 2 * q + 1], (q & 1) ? r1 : r0, bs[q >> 1].y)); \
    const uint4 H0 = gelu_group(E), H1 = gelu_group(E + 4);
#define SPART16(DST, ACC, OFF) { uint32_t E[8]; _Pragma("unroll") for (int q = 0; q < 8; q++) E[q] = pack_bf16(ACC[(OFF) + 2 * q] * ((q & 1) ? r1 : r0), ACC[(OFF) + 2 * q + 1] * ((q & 1) ? r1 : r0)); \
    if (f < 4) { const float l0 = r0 * 1.4426950408889634f, l1 = r1 * 1.4426950408889634f; \
      _Pragma("unroll") for (int q = 0; q < 8; q++) E[q] = phi_pack(E[q], ACC[(OFF) + 2 * q] * ((q & 1) ? l1 : l0), ACC[(OFF) + 2 * q + 1] * ((q & 1) ? l1 : l0)); } \
    _Pragma("unroll") for (int q = 0; q < 4; q++) st_ll64(DST + 32 * q, E[2 * q], E[2 * q + 1], par); }
#define LDS_R(SC) float r0, r1; asm volatile("ld.shared.f32 %0, [%1];" : "=f"(r0) : "r"(rst)); asm volatile("ld.shared.f32 %0, [%1];" : "=f"(r1) : "r"(rst + 32)); r0 *= (SC); r1 *= (SC);
    const uint32_t rst = sbase + SM_RSTD + (warp * 16 + g) * 4;
    auto fin_load = [&](uint4* p, uint32_t* bb, int ch, int ln) {
#pragma unroll
      for (int j = 0; j < 2; j++)
#pragma unroll
        for (int k = 0; k < 8; k++) p[8 * j + k] = ld_ll(&g_part[((rb * 8 + k) * 36 + 12 * ch + 2 * f + j) * 32 + ln]);
#pragma unroll
      for (int j = 0; j < 4; j++) bb[j] = __ldg(reinterpret_cast<const uint32_t*>(P.b2 + 192 * ch + 32 * f + 8 * j + 2 * (ln & 3)));
    };
    auto fin_bad = [&](const uint4* p) {
      uint32_t bad = 0;
#pragma unroll
      for (int k = 0; k < 16; k++) ll_chk(bad, p[k].x, p[k].z, par);
      return __any_sync(0xffffffffu, bad & 1);
    };
#pragma unroll 1
    for (int i = srole;; i++) {
      {
        const uint32_t ow = i == 4 ? bar_ofull : 0u;
        if (ow) mbar_wait(ow, 0);
        issue192(A, c, 0, true);
        const int ln = opaque(lane);
        uint4* dst = i == 1 ? reinterpret_cast<uint4*>(g_qkv + (rb * 216 + 36 * f + 24) * 32 + ln) : g_part + ((rb * 8 + f) * 36 + (i == 3 ? 0 : 24)) * 32 + ln;
        LDS_R(i == 2 ? GK : 1.f)
        retire(c);
        if (ow && leader) mbar_arrive(bar_xfree + 64);
        fence_regs<96>(B);
        int s = 1;
        if (i == 2) {
#pragma unroll 1
          for (; s < 3; s++) { issue192(A, c, s); retire(c); }
        }
        if (i > srole) {
#pragma unroll
          for (int u = 0; u < 6; u++, s++) {
            float2 bs[4];
            if (i == 2) lds_bias(bs, bias_t + (192 + 32 * u) * 4);
            if ((u & 1) && ow) mbar_wait(ow + 4 * s, 0);
            issue192(A, c, s);
            if (i == 2) {
              GELU16(h0, h1, B, 16 * u)
              stsm4((hst ^ ((2 * u & 3) << 5)) + (u >> 1) * 16384, h0);
              stsm4((hst ^ ((2 * u + 1 & 3) << 5)) + (u >> 1) * 16384, h1);
            } else if (i == 1) {
              if (u < 3) SPART16(reinterpret_cast<uint2*>(dst) + 128 * u, B, 16 * u)
              if (u == 2) hint_signal(&g_f_qkv[m * 8 + f]);
            } else {
              part_groups<0, 2>(&B[16 * u], dst + 2 * u * 32, par);
              if (u == 5 && i == 4) hint_signal(&g_f_rb[rb]);
            }
            retire(c);
          }
        }
        const bool d1 = i == 1 + srole;
        const int send = d1 ? 10 : 15;
#pragma unroll 1
        for (; s < send; s++) {
          if (ow && !(s & 1)) mbar_wait(ow + 4 * s, 0);
          issue192(A, c, s);
          retire(c);
        }
        uint32_t W[48];
        if (d1) {
          const int head = 4 * f + (warp >> 1), rb0 = m * 8 + (warp & 1) * 4;
          issue192(A, c, 10);
          mbar_wait(bar_d, 0);
          d1_load<false>(W, rb0, head, opaque(lane));
          retire(c);
#pragma unroll 1
          for (s = 11; s < 13; s++) { issue192(A, c, s); retire(c); }
          issue192(A, c, 13);
          int tries = 0;
#pragma unroll 1
          while (d1_bad(W, t, par) && ++tries < (1 << 20)) d1_load<true>(W, rb0, head, opaque(lane));
          d1_mov(W, 0, t); d1_mov(W, 1, t);
          retire(c);
          issue192(A, c, 14);
          d1_mov(W, 2, t); d1_mov(W, 3, t);
          wg_wait<0>();
          asm volatile("bar.sync 4, 256;" ::: "memory");
          float R[18];
          d1_mma(W, R);
          float2* xch = reinterpret_cast<float2*>(smem + SM_SCR + (warp >> 1) * 1792) + opaque(lane);
          if (warp & 1) {
#pragma unroll
            for (int q = 0; q < 6; q++) xch[q * 32] = make_float2(R[2 * q], R[2 * q + 1]);
            if (lane < 12) { xch[192] = make_float2(R[12], R[13]); xch[204] = make_float2(R[14], R[15]); if (t == 0) xch[216 - lane + g] = make_float2(R[16], R[17]); }
          } else if (R[17] == 1.2345e-30f) R[16] = 0.f;
          asm volatile("bar.sync 4, 256;" ::: "memory");
          retire(c);
          issue192(A, c, 15);
          if (!(warp & 1)) {
            const int ln = opaque(lane);
#pragma unroll
            for (int q = 0; q < 6; q++) { const float2 o = xch[q * 32]; R[2 * q] += o.x; R[2 * q + 1] += o.y; }
            if (ln < 12) {
              const float2 o0 = xch[192], o1 = xch[204], o2 = xch[216 - ln + (ln >> 2)];
              R[12] += o0.x; R[13] += o0.y; R[14] += o1.x; R[15] += o1.y; R[16] += o2.x; R[17] += o2.y;
            }
            uint4* dkv = &g_kvp[(head * 80 + m) * 32 + ln];
#pragma unroll
            for (int w = 0; w < 5; w++)
              if (kv_valid(w, ln)) st_ll(dkv + w * 512, __float_as_uint(R[4 * w]), __float_as_uint(R[4 * w + 1]), w < 4 ? __float_as_uint(R[4 * w + 2]) : 0u, w < 4 ? __float_as_uint(R[4 * w + 3]) : 0u, par);
            __syncwarp();
            hint_signal(&g_f_kvp[head]);
          }
          STAMPW(0, 21);
        } else issue192(A, c, 15);
        if (i == 2) {
          const uint4* hsp = g_hsp + (blockIdx.x * 8 + warp) * 12 * 32 + opaque(lane);
#pragma unroll
          for (int q = 0; q < 12; q++) { const uint4 v = ldcg128(hsp + q * 32); W[4 * q] = v.x; W[4 * q + 1] = v.y; W[4 * q + 2] = v.z; W[4 * q + 3] = v.w; }
        } else {
#pragma unroll
          for (int q = 0; q < 48; q++) W[q] = 0;
        }
        retire(c);
        if (ow) mbar_wait(ow + 64, 0);
        issue192(A, c, 16);
        if (i == 2) wg_sync();
        retire(c);
        issue192(A, c, 17);
        if (i == 2) {
#pragma unroll
          for (int q = 0; q < 12; q++) stsm4((hst ^ ((q & 3) << 5)) + (3 + (q >> 2)) * 16384, make_uint4(W[4 * q], W[4 * q + 1], W[4 * q + 2], W[4 * q + 3]));
        }
        retire(c);
      }
      STAMPW(0, 2 + 2 * i);
      if ((i & 3) == 0) {
        issue96(B, c, 0, true);
        const int ln = opaque(lane);
        uint4* dst = i == 0 ? reinterpret_cast<uint4*>(g_qkv + (rb * 216 + 36 * f) * 32 + ln) : g_s + (rb * 36 + 12 * (f - 5)) * 32 + ln;
        LDS_R(1.f)
        retire(c);
        fence_regs<96>(A);
#pragma unroll 1
        for (int s = 1; s < 8; s++) {
          issue96(B, c, s, false);
#pragma unroll
          for (int u = 0; u < 6; u++)
            if (s == u + 1) {
              if (i == 0) SPART16(reinterpret_cast<uint2*>(dst) + 128 * u, A, 16 * u)
              else part_groups<0, 2>(&A[16 * u], dst + 2 * u * 32, par);
            }
          if (s == 6 && i == 0) hint_signal(&g_f_qkv[m * 8 + f]);
          retire(c);
        }
        issue96(B, c, 8, false);
        retire(c);
        if (i == 4) {
          STAMPW(0, 11);
          wg_wait<0>();
          c.release_prev();
          fence_regs<48>(B);
          part_groups<0, 6>(B, g_s + (rb * 36 + 6 * (f - 6)) * 32 + opaque(lane), par);
          hint_signal(&g_f_rb[rb]);
          break;
        }
      } else {
        issue192(B, c, 0, true);
        const int ln = opaque(lane);
        uint4* dst = i == 1 ? g_hsp + (blockIdx.x * 8 + warp) * 12 * 32 + ln : g_part + ((rb * 8 + f) * 36 + 12) * 32 + ln;
        const bool xf = i == 3 && srole && leader;
        const uint32_t bsa = bias_t + (i == 1 ? 0 : 384) * 4;
        LDS_R(GK)
        retire(c);
        fence_regs<96>(A);
        uint4 H[6];
#pragma unroll
        for (int u = 0; u < 6; u++) {
          float2 bs[4];
          if (i != 3) lds_bias(bs, bsa + 32 * u * 4);
          issue192(B, c, u + 1);
          if (i != 3) {
            GELU16(h0, h1, A, 16 * u)
            H[u] = h1;
            if (i == 1) dst[2 * u * 32] = h0;
            else {
              stsm4((hst ^ ((2 * u & 3) << 5)) + (6 + (u >> 1)) * 16384, h0);
              stsm4((hst ^ ((2 * u + 1 & 3) << 5)) + (6 + (u >> 1)) * 16384, h1);
              if (u == 3) wg_sync();
            }
          } else {
            part_groups<0, 2>(&A[16 * u], dst + 2 * u * 32, par);
            H[u] = make_uint4(0, 0, 0, 0);
          }
          retire(c);
          if ((u & 1) && xf) mbar_arrive(bar_xfree + 4 * u - 4);
        }
        if (i == 3 && !srole) {
          uint4 p[16], G[6];
          uint32_t bb[4], xx[24];
#pragma unroll
          for (int q = 0; q < 16; q++) { p[q] = make_uint4(0, 0, 0, 0); bb[q & 3] = 0; G[q & 3] = make_uint4(0, 0, 0, 0); }
          const int l2 = opaque(lane);
          const int ro = (rb * 16 + (l2 >> 2)) * D_ + 2 * (l2 & 3) + 32 * f;
#pragma unroll 1
          for (int ch = 0; ch < 2; ch++) {
            const int s0 = 7 + 5 * ch;
#pragma unroll 1
            for (int s = s0; s < s0 + 4; s++) {
              issue192(B, c, s);
              if (s == s0 + 2 * ch) fin_load(p, bb, ch, l2);
              retire(c);
            }
            issue192(B, c, s0 + 4);
            int tries = 0;
#pragma unroll 1
            while (fin_bad(p) && ++tries < (1 << 20)) fin_load(p, bb, ch, l2);
            G[2] = gate_vec(p, bb[0], bb[1]); G[3] = gate_vec(p + 8, bb[2], bb[3]);
            if (ch == 0) { G[0] = G[2]; G[1] = G[3]; }
            retire(c);
          }
          issue192(B, c, 17);
#pragma unroll
          for (int j = 0; j < 12; j++) {
            xx[2 * j] = __ldg(reinterpret_cast<const uint32_t*>(P.x + ro + 192 * (j >> 2) + 8 * (j & 3)));
            xx[2 * j + 1] = __ldg(reinterpret_cast<const uint32_t*>(P.x + ro + 8 * D_ + 192 * (j >> 2) + 8 * (j & 3)));
          }
          retire(c);
          STAMPW(0, 9);
          wg_wait<0>();
          c.release_prev();
          fence_regs<96>(B);
          part_groups<0, 12>(B, g_part + ((rb * 8 + f) * 36 + 24) * 32 + l2, par);
          hint_signal(&g_f_rb[rb]);
          STAMPW(0, 12);
          if (l2 == 0) hint_wait(&g_f_rb[rb], 10u * ep, 20);
          __syncwarp();
          STAMPW(0, 14);
          uint4 sv[6];
          int tries = 0;
          uint32_t bad;
#pragma unroll 1
          do {
            fin_load(p, bb, 2, l2);
            bad = 0;
#pragma unroll
            for (int j = 0; j < 6; j++) sv[j] = ld_ll(&g_s[(rb * 36 + 12 * (j >> 1) + 2 * f + (j & 1)) * 32 + l2]);
#pragma unroll
            for (int j = 0; j < 6; j++) ll_chk(bad, sv[j].x, sv[j].z, par);
          } while ((fin_bad(p) || __any_sync(0xffffffffu, bad & 1)) && ++tries < (1 << 20));
          G[4] = gate_vec(p, bb[0], bb[1]); G[5] = gate_vec(p + 8, bb[2], bb[3]);
#pragma unroll
          for (int j = 0; j < 6; j++) {
            __nv_bfloat16* op = P.out + ro + 192 * (j >> 1) + 16 * (j & 1);
            *reinterpret_cast<uint32_t*>(op) = hfma2(sv[j].x, G[j].x, xx[4 * j]); *reinterpret_cast<uint32_t*>(op + 8 * D_) = hfma2(sv[j].y, G[j].y, xx[4 * j + 1]);
            *reinterpret_cast<uint32_t*>(op + 8) = hfma2(sv[j].z, G[j].z, xx[4 * j + 2]); *reinterpret_cast<uint32_t*>(op + 8 * D_ + 8) = hfma2(sv[j].w, G[j].w, xx[4 * j + 3]);
          }
          break;
        } else {
#pragma unroll 1
          for (int s = 7; s < 17; s++) {
            issue192(B, c, s);
            if (i == 1) {
#pragma unroll
              for (int u = 0; u < 6; u++) if (s == 7 + u) dst[(2 * u + 1) * 32] = H[u];
            }
            if (s == 9 && i == 2) wg_sync();
            retire(c);
            if ((s & 1) == 0 && xf) mbar_arrive(bar_xfree + 4 * s - 8);
          }
        }
        issue192(B, c, 17);
        retire(c);
      }
      STAMPW(0, 3 + 2 * i);
    }

    STAMPW(0, 15);
    cluster_arrive_relaxed();
    cluster_wait();
    STAMPW(0, 16);
    if (tid == 0) g_epoch[blockIdx.x] = ep;
  }
}

typedef CUresult (*EncFn)(CUtensorMap*, CUtensorMapDataType, cuuint32_t, void*, const cuuint64_t*, const cuuint64_t*, const cuuint32_t*, const cuuint32_t*,
                          CUtensorMapInterleave, CUtensorMapSwizzle, CUtensorMapL2promotion, CUtensorMapFloatOOBfill);

void make_map(EncFn enc, CUtensorMap* tm, const void* ptr, int rows, int cols, int box_rows, int mode = 0) {
  cuuint64_t gd[2] = {(cuuint64_t)cols, (cuuint64_t)rows};
  cuuint64_t gs[1] = {(cuuint64_t)cols * 2};
  cuuint32_t bx[2] = {mode == 1 ? 32u : (mode == 2 ? 72u : 64u), (cuuint32_t)box_rows};
  cuuint32_t es[2] = {1, 1};
  enc(tm, CU_TENSOR_MAP_DATA_TYPE_BFLOAT16, 2, const_cast<void*>(ptr), gd, gs, bx, es, CU_TENSOR_MAP_INTERLEAVE_NONE, mode == 1 ? CU_TENSOR_MAP_SWIZZLE_64B : (mode == 2 ? CU_TENSOR_MAP_SWIZZLE_NONE : CU_TENSOR_MAP_SWIZZLE_128B),
      CU_TENSOR_MAP_L2_PROMOTION_L2_256B, CU_TENSOR_MAP_FLOAT_OOB_FILL_NONE);
}

}

extern "C" void kernel_launch(void* const* d_in, const int* in_sizes, int n_in, void* d_out, int out_size) {
  (void)in_sizes; (void)n_in; (void)out_size;
  static EncFn enc = nullptr;
  static void *a_ptr = nullptr, *m_ptr = nullptr;
  if (!enc) {
    void* fn = nullptr; cudaDriverEntryPointQueryResult q;
    cudaGetDriverEntryPoint("cuTensorMapEncodeTiled", &fn, cudaEnableDefault, &q);
    enc = (EncFn)fn;
    cudaFuncSetAttribute(fused_kernel, cudaFuncAttributeMaxDynamicSharedMemorySize, SMEM_BYTES);
    cudaGetSymbolAddress(&a_ptr, g_a);
    cudaGetSymbolAddress(&m_ptr, g_m);
  }
  Params P;
  P.x = (const __nv_bfloat16*)d_in[0];
  P.wqkv = (const __nv_bfloat16*)d_in[1];
  P.wo = (const __nv_bfloat16*)d_in[2];
  P.w1 = (const __nv_bfloat16*)d_in[4];
  P.b1 = (const __nv_bfloat16*)d_in[5];
  P.w2 = (const __nv_bfloat16*)d_in[6];
  P.b2 = (const __nv_bfloat16*)d_in[7];
  P.out = (__nv_bfloat16*)d_out;
  make_map(enc, &P.tm_wqkv, P.wqkv, D_, Q3_, 32);
  make_map(enc, &P.tm_w1, P.w1, D_, F_, 32);
  make_map(enc, &P.tm_w2, P.w2, F_, D_, 32);
  make_map(enc, &P.tm_m, m_ptr, D_, D_, 32);
  make_map(enc, &P.tm_wqkv64, P.wqkv, D_, Q3_, 64, 1);
  make_map(enc, &P.tm_m64, m_ptr, D_, D_, 64, 1);
  make_map(enc, &P.tm_a, a_ptr, S_, D_, 128);
  make_map(enc, &P.tm_ast, a_ptr, S_, D_, 16, 2);
  fused_kernel<<<NCTAS, NTHREADS, SMEM_BYTES, cudaStreamPerThread>>>(P);
}
```

```cpp
#include <cuda_runtime.h>
#include <cuda.h>
#include <cuda_bf16.h>
#include <stdint.h>

namespace {

constexpr int S_ = 2048, D_ = 576, F_ = 4608, Q3_ = 1728;
constexpr int NSTAGE = 6, STAGE_BYTES = 12288;
constexpr int SM_A = 0, SM_B = 147456, SM_BIAS = SM_B + NSTAGE * STAGE_BYTES, SM_RSTD = SM_BIAS + 2304, SM_SCR = SM_RSTD + 512, SM_BAR = SM_SCR + 7168;
constexpr int SMEM_BYTES = SM_BAR + 320;
constexpr int NTHREADS = 384;
constexpr int NCTAS = 132;

__device__ uint2 g_qkv[(128 * 216 + 2) * 32];
__device__ __align__(1024) __nv_bfloat16 g_a[S_ * D_];
__device__ __align__(1024) __nv_bfloat16 g_m[D_ * D_];
__device__ uint4 g_kvp[32 * 5 * 16 * 32];
__device__ uint4 g_z[32 * 2 * 4];
__device__ uint4 g_part[128 * 8 * 36 * 32];
__device__ uint4 g_s[128 * 36 * 32];
__device__ uint4 g_hsp[128 * 12 * 256];
__device__ uint32_t g_f_qkv[16 * 8];
__device__ uint32_t g_f_kvp[32];
__device__ uint32_t g_f_z[32];
__device__ uint32_t g_f_a[16];
__device__ uint32_t g_f_m[1];
__device__ uint2 g_stat[S_];
__device__ uint32_t g_epoch[NCTAS];

#define STAMP(i)
#define STAMPW(w, i)
#define WSTAMP(i)
__device__ __forceinline__ uint32_t smem_u32(const void* p) { return (uint32_t)__cvta_generic_to_shared(p); }
__device__ __forceinline__ void mbar_init(uint32_t a, int c) { asm volatile("mbarrier.init.shared::cta.b64 [%0], %1;" ::"r"(a), "r"(c)); }
__device__ __forceinline__ void mbar_expect(uint32_t a, uint32_t b) { asm volatile("mbarrier.arrive.expect_tx.shared::cta.b64 _, [%0], %1;" ::"r"(a), "r"(b) : "memory"); }
__device__ __forceinline__ void mbar_arrive(uint32_t a) { asm volatile("mbarrier.arrive.shared::cta.b64 _, [%0];" ::"r"(a) : "memory"); }
__device__ __forceinline__ void mbar_arrive_cl(uint32_t a) { asm volatile("mbarrier.arrive.shared::cluster.b64 _, [%0];" ::"r"(a) : "memory"); }
__device__ __forceinline__ uint32_t mapa(uint32_t a, uint32_t cta) { uint32_t r; asm volatile("mapa.shared::cluster.u32 %0, %1, %2;" : "=r"(r) : "r"(a), "r"(cta)); return r; }
__device__ __forceinline__ void mbar_wait(uint32_t a, uint32_t ph) {
  uint32_t ok; int it = 0;
#pragma unroll 1
  do {
    asm volatile("{.reg .pred p; mbarrier.try_wait.parity.shared::cta.b64 p, [%1], %2; selp.u32 %0,1,0,p;}" : "=r"(ok) : "r"(a), "r"(ph) : "memory");
  } while (!ok && ++it < (1 << 18));
}
__device__ __forceinline__ void tma2d(uint32_t dst, const CUtensorMap* m, int c0, int c1, uint32_t bar) {
  asm volatile("cp.async.bulk.tensor.2d.shared::cluster.global.mbarrier::complete_tx::bytes [%0], [%1, {%3,%4}], [%2];" ::"r"(dst), "l"(m), "r"(bar), "r"(c0), "r"(c1) : "memory");
}
__device__ __forceinline__ void tma2d_mc(uint32_t dst, const CUtensorMap* m, int c0, int c1, uint32_t bar) {
  asm volatile("cp.async.bulk.tensor.2d.shared::cluster.global.mbarrier::complete_tx::bytes.multicast::cluster [%0], [%1, {%3,%4}], [%2], %5;" ::"r"(dst), "l"(m), "r"(bar), "r"(c0), "r"(c1), "h"((uint16_t)3) : "memory");
}
__device__ __forceinline__ void cluster_arrive_relaxed() { asm volatile("barrier.cluster.arrive.relaxed.aligned;" ::: "memory"); }
__device__ __forceinline__ void cluster_wait() { asm volatile("barrier.cluster.wait.acquire.aligned;" ::: "memory"); }
__device__ __forceinline__ void wg_fence() { asm volatile("wgmma.fence.sync.aligned;" ::: "memory"); }
__device__ __forceinline__ void wg_commit() { asm volatile("wgmma.commit_group.sync.aligned;" ::: "memory"); }
template <int n> __device__ __forceinline__ void wg_wait() { asm volatile("wgmma.wait_group.sync.aligned %0;" ::"n"(n) : "memory"); }
__device__ __forceinline__ uint32_t ld_acquire(const uint32_t* p) { uint32_t v; asm volatile("ld.acquire.gpu.global.u32 %0, [%1];" : "=r"(v) : "l"(p) : "memory"); return v; }
__device__ __forceinline__ void flag_wait(const uint32_t* p, uint32_t target) {
  int it = 0;
#pragma unroll 1
  while ((int)(ld_acquire(p) - target) < 0 && ++it < (1 << 20)) __nanosleep(300);
}
__device__ __forceinline__ void hint_signal(uint32_t* p) {
  if ((threadIdx.x & 31) == 0) asm volatile("red.relaxed.gpu.global.add.u32 [%0], 1;" ::"l"(p) : "memory");
}
__device__ __forceinline__ void hint_wait(const uint32_t* p, uint32_t target, uint32_t ns = 400) {
  int it = 0; uint32_t v;
#pragma unroll 1
  do { asm volatile("ld.relaxed.gpu.global.u32 %0, [%1];" : "=r"(v) : "l"(p) : "memory"); if ((int)(v - target) >= 0) break; __nanosleep(ns); } while (++it < (1 << 20));
}
__device__ __forceinline__ uint32_t tag(uint32_t x, uint32_t par) { uint32_t r; asm("lop3.b32 %0, %1, 0xfffffffe, %2, 0xea;" : "=r"(r) : "r"(x), "r"(par)); return r; }
__device__ __forceinline__ void st_ll(uint4* p, uint32_t x, uint32_t y, uint32_t z, uint32_t w, uint32_t par) {
  asm volatile("{.reg .b64 a, b; mov.b64 a, {%1,%2}; mov.b64 b, {%3,%4}; st.relaxed.gpu.global.v2.b64 [%0], {a, b};}"
               ::"l"(p), "r"(tag(x, par)), "r"(y), "r"(tag(z, par)), "r"(w) : "memory");
}
__device__ __forceinline__ uint4 ld_ll(const uint4* p) {
  uint4 v;
  asm volatile("{.reg .b64 a, b; ld.relaxed.gpu.global.v2.b64 {a, b}, [%4]; mov.b64 {%0,%1}, a; mov.b64 {%2,%3}, b;}"
               : "=r"(v.x), "=r"(v.y), "=r"(v.z), "=r"(v.w) : "l"(p) : "memory");
  return v;
}
__device__ __forceinline__ void st_ll64(uint2* p, uint32_t x, uint32_t y, uint32_t par) {
  asm volatile("{.reg .b64 a; mov.b64 a, {%1,%2}; st.relaxed.gpu.global.b64 [%0], a;}" ::"l"(p), "r"(tag(x, par)), "r"(y) : "memory");
}
__device__ __forceinline__ uint2 ld_ca64(const void* p) {
  uint2 v;
  asm volatile("{.reg .b64 a; ld.global.ca.b64 a, [%2]; mov.b64 {%0,%1}, a;}" : "=r"(v.x), "=r"(v.y) : "l"(p) : "memory");
  return v;
}
__device__ __forceinline__ uint2 ld_ll64(const void* p) {
  uint2 v;
  asm volatile("{.reg .b64 a; ld.relaxed.gpu.global.b64 a, [%2]; mov.b64 {%0,%1}, a;}" : "=r"(v.x), "=r"(v.y) : "l"(p) : "memory");
  return v;
}
__device__ __forceinline__ void ll_chk(uint32_t& bad, uint32_t a, uint32_t b, uint32_t par) {
  uint32_t u; asm("lop3.b32 %0, %1, %2, %3, 0x7e;" : "=r"(u) : "r"(a), "r"(b), "r"(par));
  asm("or.b32 %0, %0, %1;" : "+r"(bad) : "r"(u));
}
__device__ __forceinline__ uint32_t hadd2(uint32_t a, uint32_t b) { uint32_t d; asm("add.rn.bf16x2 %0, %1, %2;" : "=r"(d) : "r"(a), "r"(b)); return d; }
__device__ __forceinline__ uint32_t hfma2(uint32_t a, uint32_t b, uint32_t c) { uint32_t d; asm("fma.rn.bf16x2 %0, %1, %2, %3;" : "=r"(d) : "r"(a), "r"(b), "r"(c)); return d; }
__device__ __forceinline__ uint32_t pack_bf16(float lo, float hi) { uint32_t r; asm("cvt.rn.bf16x2.f32 %0, %1, %2;" : "=r"(r) : "f"(hi), "f"(lo)); return r; }
__device__ __forceinline__ float bf_lo(uint32_t v) { return __uint_as_float(v << 16); }
__device__ __forceinline__ float bf_hi(uint32_t v) { return __uint_as_float(v & 0xffff0000u); }
__device__ __forceinline__ uint32_t movmat(uint32_t a) { uint32_t d; asm volatile("movmatrix.sync.aligned.m8n8.trans.b16 %0, %1;" : "=r"(d) : "r"(a)); return d; }
__device__ __forceinline__ void mma16816(float* c, uint32_t a0, uint32_t a1, uint32_t a2, uint32_t a3, uint32_t b0, uint32_t b1) {
  asm volatile("mma.sync.aligned.m16n8k16.row.col.f32.bf16.bf16.f32 {%0,%1,%2,%3}, {%4,%5,%6,%7}, {%8,%9}, {%0,%1,%2,%3};"
               : "+f"(c[0]), "+f"(c[1]), "+f"(c[2]), "+f"(c[3]) : "r"(a0), "r"(a1), "r"(a2), "r"(a3), "r"(b0), "r"(b1));
}
__device__ __forceinline__ uint4 ldcg128(const void* p) { uint4 v; asm volatile("ld.global.cg.v4.u32 {%0,%1,%2,%3}, [%4];" : "=r"(v.x), "=r"(v.y), "=r"(v.z), "=r"(v.w) : "l"(p) : "memory"); return v; }

template <int N> __device__ __forceinline__ void wgmma_ss(float* d, uint64_t da, uint64_t db, int sc);
template <int N> __device__ __forceinline__ void wgmma_rs(float* d, const uint32_t* a, uint64_t db, int sc);
template <> __device__ __forceinline__ void wgmma_ss<96>(float* d, uint64_t da, uint64_t db, int sc) {
  asm volatile("{.reg .pred p; setp.ne.b32 p, %50, 0; wgmma.mma_async.sync.aligned.m64n96k16.f32.bf16.bf16 {%0, %1, %2, %3, %4, %5, %6, %7, %8, %9, %10, %11, %12, %13, %14, %15, %16, %17, %18, %19, %20, %21, %22, %23, %24, %25, %26, %27, %28, %29, %30, %31, %32, %33, %34, %35, %36, %37, %38, %39, %40, %41, %42, %43, %44, %45, %46, %47}, %48, %49, p, 1, 1, 0, 1;}"
   : "+f"(d[0]), "+f"(d[1]), "+f"(d[2]), "+f"(d[3]), "+f"(d[4]), "+f"(d[5]), "+f"(d[6]), "+f"(d[7]), "+f"(d[8]), "+f"(d[9]), "+f"(d[10]), "+f"(d[11]), "+f"(d[12]), "+f"(d[13]), "+f"(d[14]), "+f"(d[15]), "+f"(d[16]), "+f"(d[17]), "+f"(d[18]), "+f"(d[19]), "+f"(d[20]), "+f"(d[21]), "+f"(d[22]), "+f"(d[23]), "+f"(d[24]), "+f"(d[25]), "+f"(d[26]), "+f"(d[27]), "+f"(d[28]), "+f"(d[29]), "+f"(d[30]), "+f"(d[31]), "+f"(d[32]), "+f"(d[33]), "+f"(d[34]), "+f"(d[35]), "+f"(d[36]), "+f"(d[37]), "+f"(d[38]), "+f"(d[39]), "+f"(d[40]), "+f"(d[41]), "+f"(d[42]), "+f"(d[43]), "+f"(d[44]), "+f"(d[45]), "+f"(d[46]), "+f"(d[47]) : "l"(da), "l"(db), "r"(sc));
}
template <> __device__ __forceinline__ void wgmma_ss<192>(float* d, uint64_t da, uint64_t db, int sc) {
  asm volatile("{.reg .pred p; setp.ne.b32 p, %98, 0; wgmma.mma_async.sync.aligned.m64n192k16.f32.bf16.bf16 {%0, %1, %2, %3, %4, %5, %6, %7, %8, %9, %10, %11, %12, %13, %14, %15, %16, %17, %18, %19, %20, %21, %22, %23, %24, %25, %26, %27, %28, %29, %30, %31, %32, %33, %34, %35, %36, %37, %38, %39, %40, %41, %42, %43, %44, %45, %46, %47, %48, %49, %50, %51, %52, %53, %54, %55, %56, %57, %58, %59, %60, %61, %62, %63, %64, %65, %66, %67, %68, %69, %70, %71, %72, %73, %74, %75, %76, %77, %78, %79, %80, %81, %82, %83, %84, %85, %86, %87, %88, %89, %90, %91, %92, %93, %94, %95}, %96, %97, p, 1, 1, 0, 1;}"
   : "+f"(d[0]), "+f"(d[1]), "+f"(d[2]), "+f"(d[3]), "+f"(d[4]), "+f"(d[5]), "+f"(d[6]), "+f"(d[7]), "+f"(d[8]), "+f"(d[9]), "+f"(d[10]), "+f"(d[11]), "+f"(d[12]), "+f"(d[13]), "+f"(d[14]), "+f"(d[15]), "+f"(d[16]), "+f"(d[17]), "+f"(d[18]), "+f"(d[19]), "+f"(d[20]), "+f"(d[21]), "+f"(d[22]), "+f"(d[23]), "+f"(d[24]), "+f"(d[25]), "+f"(d[26]), "+f"(d[27]), "+f"(d[28]), "+f"(d[29]), "+f"(d[30]), "+f"(d[31]), "+f"(d[32]), "+f"(d[33]), "+f"(d[34]), "+f"(d[35]), "+f"(d[36]), "+f"(d[37]), "+f"(d[38]), "+f"(d[39]), "+f"(d[40]), "+f"(d[41]), "+f"(d[42]), "+f"(d[43]), "+f"(d[44]), "+f"(d[45]), "+f"(d[46]), "+f"(d[47]), "+f"(d[48]), "+f"(d[49]), "+f"(d[50]), "+f"(d[51]), "+f"(d[52]), "+f"(d[53]), "+f"(d[54]), "+f"(d[55]), "+f"(d[56]), "+f"(d[57]), "+f"(d[58]), "+f"(d[59]), "+f"(d[60]), "+f"(d[61]), "+f"(d[62]), "+f"(d[63]), "+f"(d[64]), "+f"(d[65]), "+f"(d[66]), "+f"(d[67]), "+f"(d[68]), "+f"(d[69]), "+f"(d[70]), "+f"(d[71]), "+f"(d[72]), "+f"(d[73]), "+f"(d[74]), "+f"(d[75]), "+f"(d[76]), "+f"(d[77]), "+f"(d[78]), "+f"(d[79]), "+f"(d[80]), "+f"(d[81]), "+f"(d[82]), "+f"(d[83]), "+f"(d[84]), "+f"(d[85]), "+f"(d[86]), "+f"(d[87]), "+f"(d[88]), "+f"(d[89]), "+f"(d[90]), "+f"(d[91]), "+f"(d[92]), "+f"(d[93]), "+f"(d[94]), "+f"(d[95]) : "l"(da), "l"(db), "r"(sc));
}

__device__ __forceinline__ uint64_t desc64(uint32_t lo, uint32_t hi) { uint64_t d; asm("mov.b64 %0, {%1, %2};" : "=l"(d) : "r"(lo), "r"(hi)); return d; }
constexpr uint32_t DESC_HI = (1024u >> 4) | (1u << 30);
constexpr uint32_t DESC_HI64 = (512u >> 4) | (2u << 30);
template <int n> __device__ __forceinline__ void fence_regs(float* a) {
#pragma unroll
  for (int i = 0; i < n; i++) asm volatile("" : "+f"(a[i])::"memory");
}

struct Ctx {
  uint32_t full;
  uint32_t emb;
  bool sig;
  uint32_t stage, phase, prev;
  uint32_t dB, dA;
  __device__ __forceinline__ void release_prev() { if (sig && prev != ~0u) mbar_arrive_cl(emb + prev); }
  __device__ __forceinline__ void wait_full() {
    mbar_wait(full + 8 * stage, phase);
    wg_fence();
  }
};

__device__ __forceinline__ void issue192(float* acc, Ctx& c, int s, bool first = false) {
  c.wait_full();
  const uint32_t db = c.dB + c.stage * (STAGE_BYTES >> 4);
  const uint32_t da = c.dA + (s >> 1) * 1024 + (s & 1) * 4;
  wgmma_ss<192>(acc, desc64(da, DESC_HI), desc64(db, DESC_HI), first ? 0 : 1);
  wgmma_ss<192>(acc, desc64(da + 2, DESC_HI), desc64(db + 128, DESC_HI), 1);
  wg_commit();
}
__device__ __forceinline__ void issue96(float* acc, Ctx& c, int s, bool first) {
  c.wait_full();
  const uint32_t db = c.dB + c.stage * (STAGE_BYTES >> 4);
  const uint32_t da = c.dA + s * 1024;
  if (first) { wgmma_ss<192>(acc, desc64(da, DESC_HI), desc64(db, DESC_HI64), 0); wg_fence(); }
#pragma unroll
  for (int kk = first ? 1 : 0; kk < 4; kk++) wgmma_ss<96>(acc, desc64(da + 2 * kk, DESC_HI), desc64(db + 64 * kk, DESC_HI64), 1);
  wg_commit();
}
__device__ __forceinline__ void retire(Ctx& c) {
  wg_wait<1>();
  c.release_prev();
  c.prev = 8 * c.stage;
  if (++c.stage == NSTAGE) { c.stage = 0; c.phase ^= 1; }
}
constexpr float GK = 0.32920349f;
__device__ __forceinline__ uint32_t gelu_pair(uint32_t y) {
  uint32_t u, th;
  asm("mul.rn.bf16x2 %0, %1, %2;" : "=r"(u) : "r"(hfma2(y, y, 0x401b401bu)), "r"(y));
  asm("tanh.approx.bf16x2 %0, %1;" : "=r"(th) : "r"(u));
  return hfma2(y, th, y);
}
__device__ __forceinline__ uint4 gelu_group(const uint32_t* a) { return make_uint4(gelu_pair(a[0]), gelu_pair(a[1]), gelu_pair(a[2]), gelu_pair(a[3])); }
__device__ __forceinline__ void lds_bias(float2* b, uint32_t addr) {
#pragma unroll
  for (int j = 0; j < 4; j++) asm volatile("ld.shared.v2.f32 {%0,%1}, [%2];" : "=f"(b[j].x), "=f"(b[j].y) : "r"(addr + 32 * j));
}
__device__ __forceinline__ int opaque(int v) { asm volatile("" : "+r"(v)); return v; }
__device__ __forceinline__ void stsm4(uint32_t addr, uint4 r) {
  asm volatile("stmatrix.sync.aligned.m8n8.x4.shared.b16 [%0], {%1,%2,%3,%4};" ::"r"(addr), "r"(r.x), "r"(r.y), "r"(r.z), "r"(r.w) : "memory");
}
__device__ __forceinline__ float ex2f(float x) { float r; asm("ex2.approx.ftz.f32 %0, %1;" : "=f"(r) : "f"(x)); return r; }
__device__ __forceinline__ uint32_t phi_pack(uint32_t tp, float a0, float a1) {
  uint32_t x, y;
  asm("max.bf16x2 %0, %1, %2;" : "=r"(x) : "r"(tp), "r"(0x35863586u));
  asm("min.bf16x2 %0, %1, %2;" : "=r"(y) : "r"(pack_bf16(ex2f(a0), ex2f(a1))), "r"(0x3f803f80u));
  return hadd2(x, y);
}
template <int q0, int q1>
__device__ __forceinline__ void part_groups(const float* a, uint4* p, uint32_t par) {
#pragma unroll
  for (int q = q0; q < q1; q++)
    st_ll(p + q * 32, pack_bf16(a[8 * q], a[8 * q + 1]), pack_bf16(a[8 * q + 2], a[8 * q + 3]), pack_bf16(a[8 * q + 4], a[8 * q + 5]), pack_bf16(a[8 * q + 6], a[8 * q + 7]), par);
}
__device__ __forceinline__ float rcpf(float x) { float r; asm("rcp.approx.ftz.f32 %0, %1;" : "=f"(r) : "f"(x)); return r; }
__device__ __forceinline__ float silu(float y) { return y * rcpf(1.f + ex2f(y * -1.4426950408889634f)); }
__device__ __forceinline__ int pairoff(int p, int g) { return (p >> 2) * 32 + g * 4 + (p & 3); }
template <bool STRONG> __device__ __forceinline__ void d1_load(uint32_t* W, int rb0, int head, int ln) {
  const uint2* qf = g_qkv + rb0 * 216 * 32 + pairoff(288 + head * 9 + (ln & 3), ln >> 2);
#pragma unroll
  for (int b = 0; b < 3; b++) {
#pragma unroll
    for (int j = 0; j < 4; j++) {
      const uint2* p = qf + j * 216 * 32 + 32 * b;
      const uint2 kk = STRONG ? ld_ll64(p) : ld_ca64(p), vv = STRONG ? ld_ll64(p + 72 * 32) : ld_ca64(p + 72 * 32);
      W[6 * j + 2 * b] = kk.x; W[6 * j + 2 * b + 1] = kk.y; W[24 + 6 * j + 2 * b] = vv.x; W[24 + 6 * j + 2 * b + 1] = vv.y;
    }
  }
}
__device__ __forceinline__ bool d1_bad(const uint32_t* W, int t, uint32_t par) {
  uint32_t bad = 0, bad2 = 0;
#pragma unroll
  for (int q = 0; q < 12; q++) ll_chk((q % 3) != 2 ? bad : bad2, W[2 * q], W[24 + 2 * q], par);
  return __any_sync(0xffffffffu, (bad | (t == 0 ? bad2 : 0u)) & 1);
}
__device__ __forceinline__ void d1_mov(uint32_t* W, int j, int t) {
  if (t != 0) { W[6 * j + 4] = W[6 * j + 5] = 0u; W[24 + 6 * j + 4] = W[24 + 6 * j + 5] = (t == 1 ? 0x00003f80u : 0u); }
#pragma unroll
  for (int q = 0; q < 6; q++) { W[6 * j + q] = movmat(W[6 * j + q]); W[24 + 6 * j + q] = movmat(W[24 + 6 * j + q]); }
}
__device__ __forceinline__ void d1_mma(const uint32_t* W, float* R) {
  float c1[3][4];
#pragma unroll
  for (int j = 0; j < 12; j++) { R[j] = 0.f; c1[j >> 2][j & 3] = 0.f; }
#pragma unroll
  for (int ks = 0; ks < 4; ks++)
#pragma unroll
    for (int j = 0; j < 3; j++) {
      mma16816(R + 4 * j, W[24 + 6 * ks], W[24 + 6 * ks + 2], W[24 + 6 * ks + 1], W[24 + 6 * ks + 3], W[6 * ks + 2 * j], W[6 * ks + 2 * j + 1]);
      mma16816(c1[j], W[24 + 6 * ks + 4], 0u, W[24 + 6 * ks + 5], 0u, W[6 * ks + 2 * j], W[6 * ks + 2 * j + 1]);
    }
#pragma unroll
  for (int j = 0; j < 3; j++) { R[12 + 2 * j] = c1[j][0]; R[13 + 2 * j] = c1[j][1]; }
}
__device__ __forceinline__ bool kv_valid(int w, int ln) { return (w < 3 || ln < 12) && ((w != 2 && w != 4) || (ln & 3) == 0); }

struct Params {
  CUtensorMap tm_wqkv, tm_w1, tm_w2, tm_m, tm_wqkv64, tm_m64, tm_a, tm_ast;
  const __nv_bfloat16 *x, *b1, *b2, *wqkv, *w1, *w2, *wo;
  __nv_bfloat16* out;
};

__global__ void __cluster_dims__(2, 1, 1) __launch_bounds__(NTHREADS, 1) fused_kernel(const __grid_constant__ Params P) {
  extern __shared__ __align__(1024) uint8_t smem[];
  const uint32_t sbase = smem_u32(smem);
  const int tid = threadIdx.x, lane = tid & 31;
  const int warp = __shfl_sync(0xffffffffu, tid >> 5, 0);
  const int g = lane >> 2, t = lane & 3;
  const uint32_t ep = __shfl_sync(0xffffffffu, g_epoch[blockIdx.x], 0) + 1;
  const uint32_t par = ep & 1;
  STAMPW(0, 0);

  if (blockIdx.x >= 128) {
    const int a = blockIdx.x - 128;
    constexpr int WP = 1168, SM_T = 152 * WP, SM_HB = SM_T + 8 * 32 * 80;
    if (tid == 0) {
      mbar_init(sbase + SM_HB, 1);
      asm volatile("fence.mbarrier_init.release.cluster;" ::: "memory");
      mbar_expect(sbase + SM_HB, 144 * 1152);
    }
    for (int i = tid; i < (8 * WP + 8 * 32 * 80) / 4; i += NTHREADS) reinterpret_cast<uint32_t*>(smem + 144 * WP)[i] = 0u;
    __syncthreads();
    __nanosleep(1500);
    if (tid < 144)
      asm volatile("cp.async.bulk.shared::cluster.global.mbarrier::complete_tx::bytes [%0], [%1], %2, [%3];" ::"r"(sbase + tid * WP), "l"(P.wo + (a * 144 + tid) * D_), "r"(1152), "r"(sbase + SM_HB) : "memory");
    if (warp >= 8 && lane == 0) {
      const int id = a * 4 + (warp - 8);
      constexpr uint32_t CH = 9216 * 2;
#pragma unroll 1
      for (int i = id; i < 576; i += 16) {
        const char* p = i < 288 ? (const char*)P.w1 + (size_t)i * CH : (const char*)P.w2 + (size_t)(i - 288) * CH;
        asm volatile("cp.async.bulk.prefetch.L2.global [%0], %1;" ::"l"(p), "r"(CH) : "memory");
      }
    }
    __syncwarp();
    if (lane < 8) hint_wait(&g_f_kvp[a * 8 + lane], 16 * ep, 50);
    __syncwarp();
    STAMPW(0, 1);
#pragma unroll 1
    for (int u = warp; u < 40; u += 12) {
      const int hh = u & 7, w = 4 - (u >> 3), head = a * 8 + hh;
      uint4 v[16];
      int tries = 0;
      uint32_t bad;
      const bool val = kv_valid(w, lane);
#pragma unroll 1
      do {
        bad = 0;
#pragma unroll
        for (int j = 0; j < 16; j++) v[j] = val ? ld_ll(&g_kvp[((head * 5 + w) * 16 + j) * 32 + lane]) : make_uint4(par, 0u, par, 0u);
#pragma unroll
        for (int j = 0; j < 16; j++) ll_chk(bad, v[j].x, v[j].z, par);
      } while (__any_sync(0xffffffffu, bad & 1) && ++tries < (1 << 20));
      float s0 = 0.f, s1 = 0.f, s2 = 0.f, s3 = 0.f;
#pragma unroll
      for (int j = 0; j < 16; j++) { s0 += __uint_as_float(v[j].x); s1 += __uint_as_float(v[j].y); s2 += __uint_as_float(v[j].z); s3 += __uint_as_float(v[j].w); }
      if (w >= 3) {
        if (g == 2) st_ll(&g_z[(head * 2 + w - 3) * 4 + t], __float_as_uint(s0), __float_as_uint(s1), __float_as_uint(s2), __float_as_uint(s3), par);
        __syncwarp();
        hint_signal(&g_f_z[head]);
      }
      const int e0 = w < 3 ? g : 16 + g, e1 = w < 3 ? g + 8 : 16 + g, d0 = (w < 3 ? 8 * w : (w == 3 ? 0 : 16)) + 2 * t, d1 = w < 3 ? d0 : d0 + 8;
      __nv_bfloat16* T = reinterpret_cast<__nv_bfloat16*>(smem + SM_T) + hh * 32 * 40;
      if (e0 < 18) {
        T[d0 * 40 + e0] = __float2bfloat16(s0); T[(d0 + 1) * 40 + e0] = __float2bfloat16(s1);
        T[d1 * 40 + e1] = __float2bfloat16(s2); T[(d1 + 1) * 40 + e1] = __float2bfloat16(s3);
      }
    }
    __syncthreads();
    STAMPW(0, 2);
    mbar_wait(sbase + SM_HB, 0);
#pragma unroll 1
    for (int u = warp; u < 24; u += 12) {
      const int hh = u / 3, c0 = (u % 3) * 192;
      const uint32_t* T = reinterpret_cast<const uint32_t*>(smem + SM_T) + hh * 32 * 20 + g * 20 + t;
      const uint32_t a00 = T[0], a01 = T[160], a02 = T[4], a03 = T[164], a10 = T[8], a11 = T[168], b00 = T[320], b02 = T[324], b10 = T[328];
      const uint32_t rowa = sbase + (hh * 18 + (lane & 15)) * WP + (c0 + (lane >> 4) * 8) * 2, rowb = sbase + (hh * 18 + 16 + (lane & 7)) * WP + (c0 + ((lane >> 3) & 1) * 8) * 2;
#pragma unroll 3
      for (int j = 0; j < 12; j++) {
        uint32_t w0, w1, w2, w3, w4, w5;
        asm volatile("ldmatrix.sync.aligned.m8n8.x4.trans.shared.b16 {%0,%1,%2,%3}, [%4];" : "=r"(w0), "=r"(w1), "=r"(w2), "=r"(w3) : "r"(rowa + j * 32));
        asm volatile("ldmatrix.sync.aligned.m8n8.x2.trans.shared.b16 {%0,%1}, [%2];" : "=r"(w4), "=r"(w5) : "r"(rowb + j * 32));
        float p[4][4];
#pragma unroll
        for (int q = 0; q < 4; q++) p[q][0] = p[q][1] = p[q][2] = p[q][3] = 0.f;
        mma16816(p[0], a00, a01, a02, a03, w0, w1); mma16816(p[1], a00, a01, a02, a03, w2, w3);
        mma16816(p[2], b00, 0u, b02, 0u, w0, w1); mma16816(p[3], b00, 0u, b02, 0u, w2, w3);
        mma16816(p[0], a10, a11, 0u, 0u, w4, 0u); mma16816(p[1], a10, a11, 0u, 0u, w5, 0u);
        mma16816(p[2], b10, 0u, 0u, 0u, w4, 0u); mma16816(p[3], b10, 0u, 0u, 0u, w5, 0u);
        stsm4(rowa + j * 32, make_uint4(pack_bf16(p[0][0], p[0][1]), pack_bf16(p[0][2], p[0][3]), pack_bf16(p[1][0], p[1][1]), pack_bf16(p[1][2], p[1][3])));
        if (g < 2) {
          uint32_t* r = reinterpret_cast<uint32_t*>(smem + (hh * 18 + 16 + g) * WP + (c0 + j * 16 + 2 * t) * 2);
          r[0] = pack_bf16(p[2][0], p[2][1]); r[4] = pack_bf16(p[3][0], p[3][1]);
        }
      }
      asm volatile("fence.proxy.async.shared::cta;" ::: "memory");
      __syncwarp();
      if (lane < 18) {
        asm volatile("cp.async.bulk.global.shared::cta.bulk_group [%0], [%1], %2;" ::"l"(g_m + (a * 144 + hh * 18 + lane) * D_ + c0), "r"(sbase + (hh * 18 + lane) * WP + c0 * 2), "r"(384) : "memory");
        asm volatile("cp.async.bulk.commit_group;" ::: "memory");
      }
    }
    asm volatile("cp.async.bulk.wait_group 0;" ::: "memory");
    asm volatile("fence.proxy.async.global;" ::: "memory");
    __syncwarp();
    if (lane == 0) asm volatile("red.release.gpu.global.add.u32 [%0], 1;" ::"l"(g_f_m) : "memory");
    STAMPW(0, 3);
    __syncthreads();
    if (tid == 0) g_epoch[blockIdx.x] = ep;
    return;
  }

  const int cl = blockIdx.x >> 1, rank = blockIdx.x & 1;
  const int f = cl & 7, m = (cl >> 3) * 2 + rank;
  const int srole = f >= 6 ? 1 : 0;
  const uint32_t bar_full = sbase + SM_BAR, bar_empty = bar_full + 8 * NSTAGE, bar_xfree = bar_empty + 8 * NSTAGE, bar_ofull = bar_xfree + 72,
                 bar_d = bar_ofull + 72;

  if (tid == 0) {
#pragma unroll 1
    for (int i = 0; i < NSTAGE; i++) { mbar_init(bar_full + 8 * i, 1); mbar_init(bar_empty + 8 * i, 4); }
#pragma unroll 1
    for (int i = 0; i < 9; i++) { mbar_init(bar_xfree + 8 * i, 2); mbar_init(bar_ofull + 8 * i, 1); }
    mbar_init(bar_d, 1);
    asm volatile("fence.mbarrier_init.release.cluster;" ::: "memory");
  }
  __syncwarp();
  cluster_arrive_relaxed();

  if (warp >= 8) {
    const int srow = m * 128 + f * 16 + (warp - 8) * 4 + (lane >> 3);
    uint4 xs[9];
#pragma unroll
    for (int kb = 0; kb < 9; kb++) xs[kb] = __ldg(reinterpret_cast<const uint4*>(P.x + srow * D_) + (lane & 7) + kb * 8);
    auto stats = [&]() {
      const uint32_t* w = reinterpret_cast<const uint32_t*>(xs);
      float s0 = 0.f, s1 = 0.f;
#pragma unroll
      for (int i = 0; i < 36; i++) { s0 += bf_lo(w[i]); s1 += bf_hi(w[i]); }
      float sum = s0 + s1;
      sum += __shfl_xor_sync(0xffffffffu, sum, 1); sum += __shfl_xor_sync(0xffffffffu, sum, 2); sum += __shfl_xor_sync(0xffffffffu, sum, 4);
      const float mean = sum * (1.f / 576.f);
      s0 = 0.f; s1 = 0.f;
#pragma unroll
      for (int i = 0; i < 36; i++) { const float a = bf_lo(w[i]) - mean, b = bf_hi(w[i]) - mean; s0 = fmaf(a, a, s0); s1 = fmaf(b, b, s1); }
      float sq = s0 + s1;
      sq += __shfl_xor_sync(0xffffffffu, sq, 1); sq += __shfl_xor_sync(0xffffffffu, sq, 2); sq += __shfl_xor_sync(0xffffffffu, sq, 4);
      const float rstd = rsqrtf(sq * (1.f / 576.f) + 1e-5f);
      if ((lane & 7) == 0)
        st_ll64(&g_stat[srow], __float_as_uint(rstd), pack_bf16(-mean, -mean), par);
    };
    stats();
    asm volatile("setmaxnreg.dec.sync.aligned.u32 40;");
    cluster_wait();
    if (warp == 8) {
      if (lane == 0) {
        uint32_t stage = 0, phase = 1;
        const uint32_t sb = sbase + SM_B;
#pragma unroll 1
        for (int tl = 2 * srole; tl < 8 + 2 * srole; tl++) {
          const CUtensorMap* map = tl == 0 ? &P.tm_wqkv : (tl == 1 ? &P.tm_wqkv64 : (tl < 5 ? &P.tm_w1 : (tl < 8 ? &P.tm_w2 : (tl == 8 ? &P.tm_m : &P.tm_m64))));
          const int col = tl < 2 ? 288 * f + 192 * tl : (tl < 5 ? 576 * f + 192 * (tl - 2) : (tl < 8 ? 192 * ((tl - 5 + f) % 3) : (tl == 8 ? 192 * (f - 5) : 96 * (f - 6))));
          const bool perm = tl >= 5 && tl < 8;
          const bool z = (tl & 7) == 1;
          if (tl == 8) { flag_wait(g_f_m, 48 * ep); asm volatile("fence.proxy.async.global;" ::: "memory"); }
          const int cs = z ? 32 : 64, rs = z ? 64 : 32, nst = z ? 9 : 18;
#pragma unroll 1
          for (int st = 0; st < nst; st++) {
            int row = st * rs;
            if (perm) row += 576 * f + ((st < 6) ? 192 : (st < 12 ? -192 : 0));
            mbar_wait(bar_empty + 8 * stage, phase);
            mbar_expect(bar_full + 8 * stage, 12288);
            const uint32_t dst = sb + stage * STAGE_BYTES;
            if (((st ^ rank) & 1) == 0) {
              tma2d_mc(dst, map, col, row, bar_full + 8 * stage);
              tma2d_mc(dst + 8192, map, col + 2 * cs, row, bar_full + 8 * stage);
            } else {
              tma2d_mc(dst + 4096, map, col + cs, row, bar_full + 8 * stage);
            }
            if (++stage == NSTAGE) { stage = 0; phase ^= 1; }
          }
        }
      }
      __syncwarp();
    } else {
      const int aw = warp - 9;
      const int hi = f >> 2;
      if (aw == 0) {
        if (lane < 2) hint_wait(&g_f_qkv[m * 8 + 2 + 2 * lane + hi], 16 * ep, 200);
        __syncwarp();
        if (lane == 0) mbar_arrive(bar_d);
        STAMP(20);
      }
      if (lane < 5) hint_wait(lane < 4 ? &g_f_z[4 * f + lane] : &g_f_qkv[m * 8 + hi], lane < 4 ? 2 * ep : 16 * ep);
      __syncwarp();
      STAMPW(9, 22);
      uint32_t* stg = reinterpret_cast<uint32_t*>(smem + SM_SCR + aw * 2304);
#pragma unroll 1
      for (int u = aw * 2; u < 16; u += (u & 1) ? 5 : 1) {
        const int rbl = u >> 1, hp = (u & 1) * 2;
        const uint2* qf = g_qkv + (m * 8 + rbl) * 216 * 32;
        const uint2* zp = reinterpret_cast<const uint2*>(&g_z[(4 * f + hp) * 8 + t]);
        uint2 q[2][3];
        float d[4];
        int tries = 0;
        uint32_t bad;
#pragma unroll 1
        do {
          bad = tries ? ld_acquire(g_f_m) & 0u : 0u;
#pragma unroll
          for (int j = 0; j < 2; j++)
#pragma unroll
            for (int b = 0; b < 3; b++) q[j][b] = ld_ca64(qf + pairoff((4 * f + hp + j) * 9 + t, g) + 32 * b);
#pragma unroll
          for (int j = 0; j < 2; j++) {
            const uint2 z0 = ld_ca64(zp + 16 * j), z1 = ld_ca64(zp + 16 * j + 1), z2 = ld_ca64(zp + 16 * j + 8);
            if (t != 0) q[j][2] = make_uint2(par, 0u);
            ll_chk(bad, z0.x, z1.x, par); ll_chk(bad, z2.x, q[j][2].x, par); ll_chk(bad, q[j][0].x, q[j][1].x, par);
            d[2 * j] = bf_lo(q[j][0].x) * __uint_as_float(z0.x) + bf_hi(q[j][0].x) * __uint_as_float(z0.y) + bf_lo(q[j][1].x) * __uint_as_float(z1.x) + bf_hi(q[j][1].x) * __uint_as_float(z1.y) +
                       bf_lo(q[j][2].x) * __uint_as_float(z2.x) + bf_hi(q[j][2].x) * __uint_as_float(z2.y);
            d[2 * j + 1] = bf_lo(q[j][0].y) * __uint_as_float(z0.x) + bf_hi(q[j][0].y) * __uint_as_float(z0.y) + bf_lo(q[j][1].y) * __uint_as_float(z1.x) + bf_hi(q[j][1].y) * __uint_as_float(z1.y) +
                           bf_lo(q[j][2].y) * __uint_as_float(z2.x) + bf_hi(q[j][2].y) * __uint_as_float(z2.y);
          }
        } while (__any_sync(0xffffffffu, bad & 1) && ++tries < (1 << 20));
#pragma unroll
        for (int j = 0; j < 4; j++) d[j] += __shfl_xor_sync(0xffffffffu, d[j], 1);
#pragma unroll
        for (int j = 0; j < 4; j++) d[j] = rcpf(d[j] + __shfl_xor_sync(0xffffffffu, d[j], 2) + 1e-6f);
        if (hp == 0) { asm volatile("cp.async.bulk.wait_group.read 0;" ::: "memory"); __syncwarp(); }
#pragma unroll
        for (int j = 0; j < 2; j++) {
          const uint32_t r0 = pack_bf16(d[2 * j], d[2 * j]), r1 = pack_bf16(d[2 * j + 1], d[2 * j + 1]);
#pragma unroll
          for (int b = 0; b < 3; b++)
            if (b < 2 || t == 0) {
              stg[g * 36 + (hp + j) * 9 + 4 * b + t] = hfma2(q[j][b].x, r0, 0x80008000u);
              stg[(g + 8) * 36 + (hp + j) * 9 + 4 * b + t] = hfma2(q[j][b].y, r1, 0x80008000u);
            }
        }
        if (hp != 0) {
          asm volatile("fence.proxy.async.shared::cta;" ::: "memory");
          __syncwarp();
          if (lane == 0) {
            asm volatile("cp.async.bulk.tensor.2d.global.shared::cta.bulk_group [%0, {%2, %3}], [%1];" ::"l"(&P.tm_ast), "r"(smem_u32(stg)), "r"(72 * f), "r"(m * 128 + rbl * 16) : "memory");
            asm volatile("cp.async.bulk.commit_group;" ::: "memory");
          }
        }
      }
      asm volatile("cp.async.bulk.wait_group 0;" ::: "memory");
      asm volatile("fence.proxy.async.global;" ::: "memory");
      STAMPW(9, 26);
      asm volatile("bar.sync 5, 96;" ::: "memory");
      if (tid == 288) asm volatile("red.release.gpu.global.add.u32 [%0], 1;" ::"l"(&g_f_a[m]) : "memory");
      __syncwarp();
      STAMPW(9, 23);
      if (srole && aw == 2) {
        if (lane == 0) {
          flag_wait(&g_f_a[m], 8 * ep);
          asm volatile("fence.proxy.async.global;" ::: "memory");
#pragma unroll 1
          for (int kb = 0; kb < 9; kb++) {
            mbar_wait(bar_xfree + 8 * kb, 0);
            mbar_expect(bar_ofull + 8 * kb, 16384);
            tma2d(sbase + SM_A + kb * 16384, &P.tm_a, kb * 64, m * 128, bar_ofull + 8 * kb);
          }
        }
        __syncwarp();
      }
    }
    cluster_arrive_relaxed();
    cluster_wait();
  } else {
    const int wg = warp >> 2;
    {
      const int rs = lane >> 3, j = lane & 7;
      uint4 xv[4][9];
#pragma unroll
      for (int it = 0; it < 4; it++)
#pragma unroll
        for (int kb = 0; kb < 9; kb++) xv[it][kb] = __ldg(reinterpret_cast<const uint4*>(P.x + (m * 128 + warp * 16 + it * 4 + rs) * D_) + j + kb * 8);
      uint32_t bw0 = __ldg(reinterpret_cast<const uint32_t*>(P.b1 + 576 * f) + tid), bw1 = tid < 32 ? __ldg(reinterpret_cast<const uint32_t*>(P.b1 + 576 * f) + 256 + tid) : 0u;
      uint2 st[4];
      int tries = 0;
      uint32_t bad;
#pragma unroll 1
      do {
        bad = 0;
#pragma unroll
        for (int it = 0; it < 4; it++) st[it] = ld_ll64(&g_stat[m * 128 + warp * 16 + it * 4 + rs]);
        ll_chk(bad, st[0].x, st[1].x, par); ll_chk(bad, st[2].x, st[3].x, par);
      } while (__any_sync(0xffffffffu, bad & 1) && ++tries < (1 << 22));
      STAMPW(0, 19);
#pragma unroll
      for (int it = 0; it < 4; it++) {
        const uint32_t nm = st[it].y;
        uint8_t* dst = smem + SM_A + (warp * 16 + it * 4 + rs) * 128 + ((j ^ ((it * 4 + rs) & 7)) << 4);
#pragma unroll
        for (int kb = 0; kb < 9; kb++) {
          const uint4 w = xv[it][kb];
          *reinterpret_cast<uint4*>(dst + kb * 16384) = make_uint4(hadd2(w.x, nm), hadd2(w.y, nm), hadd2(w.z, nm), hadd2(w.w, nm));
        }
        if (j == 0) reinterpret_cast<uint32_t*>(smem + SM_RSTD)[warp * 16 + it * 4 + rs] = st[it].x;
      }
      reinterpret_cast<float2*>(smem + SM_BIAS)[tid] = make_float2(bf_lo(bw0) * GK, bf_hi(bw0) * GK);
      if (tid < 32) reinterpret_cast<float2*>(smem + SM_BIAS)[256 + tid] = make_float2(bf_lo(bw1) * GK, bf_hi(bw1) * GK);
      asm volatile("fence.proxy.async.shared::cta;" ::: "memory");
    }
    asm volatile("setmaxnreg.inc.sync.aligned.u32 232;");
    cluster_wait();
    asm volatile("bar.sync 1, 256;" ::: "memory");
    STAMPW(0, 1);
    Ctx c;
    c.full = bar_full;
    c.emb = __shfl_sync(0xffffffffu, mapa(bar_empty, (warp & 3) == 0 ? rank : (rank ^ 1)), 0);
    c.sig = lane == 0 && (warp & 3) < 2;
    c.stage = 0; c.phase = 0; c.prev = ~0u;
    c.dB = (((sbase + SM_B) & 0x3FFFF) >> 4) | ((4096u >> 4) << 16);
    c.dA = (((sbase + SM_A + wg * 8192) & 0x3FFFF) >> 4) | (1u << 16);
    const bool leader = (lane == 0) && ((warp & 3) == 0);

    const int rb = m * 8 + warp;
    const uint32_t bias_t = sbase + SM_BIAS + 8 * t;
    const uint32_t hst = sbase + SM_A + (warp * 16 + (lane & 7) + ((lane >> 3) & 1) * 8) * 128 + (((lane >> 4) ^ (lane & 7)) << 4);
    auto wg_sync = [&]() {
      asm volatile("fence.proxy.async.shared::cta;" ::: "memory");
      if (wg == 0) asm volatile("bar.sync 2, 128;" ::: "memory"); else asm volatile("bar.sync 3, 128;" ::: "memory");
    };
    float A[96], B[96];
#pragma unroll
    for (int i = 0; i < 96; i++) B[i] = 0.f;
#define GELU16(H0, H1, ACC, OFF) uint32_t E[8]; \
    _Pragma("unroll") for (int q = 0; q < 8; q++) E[q] = pack_bf16(fmaf(ACC[(OFF) + 2 * q], (q & 1) ? r1 : r0, bs[q >> 1].x), fmaf(ACC[(OFF) + 2 * q + 1], (q & 1) ? r1 : r0, bs[q >> 1].y)); \
    const uint4 H0 = gelu_group(E), H1 = gelu_group(E + 4);
#define SPART16(DST, ACC, OFF) { uint32_t E[8]; _Pragma("unroll") for (int q = 0; q < 8; q++) E[q] = pack_bf16(ACC[(OFF) + 2 * q] * ((q & 1) ? r1 : r0), ACC[(OFF) + 2 * q + 1] * ((q & 1) ? r1 : r0)); \
    if (f < 4) { const float l0 = r0 * 1.4426950408889634f, l1 = r1 * 1.4426950408889634f; \
      _Pragma("unroll") for (int q = 0; q < 8; q++) E[q] = phi_pack(E[q], ACC[(OFF) + 2 * q] * ((q & 1) ? l1 : l0), ACC[(OFF) + 2 * q + 1] * ((q & 1) ? l1 : l0)); } \
    _Pragma("unroll") for (int q = 0; q < 4; q++) st_ll64(DST + 32 * q, E[2 * q], E[2 * q + 1], par); }
#define LDS_R(SC) float r0, r1; asm volatile("ld.shared.f32 %0, [%1];" : "=f"(r0) : "r"(rst)); asm volatile("ld.shared.f32 %0, [%1];" : "=f"(r1) : "r"(rst + 32)); r0 *= (SC); r1 *= (SC);
    const uint32_t rst = sbase + SM_RSTD + (warp * 16 + g) * 4;
    const int fr = f % 3;
#pragma unroll 1
    for (int i = srole;; i++) {
      {
        const uint32_t ow = i == 4 ? bar_ofull : 0u;
        if (ow) mbar_wait(ow, 0);
        issue192(A, c, 0, true);
        const int ln = opaque(lane);
        uint4* dst = i == 1 ? reinterpret_cast<uint4*>(g_qkv + (rb * 216 + 36 * f + 24) * 32 + ln) : g_part + ((rb * 8 + f) * 36 + 12 * (i == 3 ? fr : (fr + 2) % 3)) * 32 + ln;
        LDS_R(i == 2 ? GK : 1.f)
        retire(c);
        if (ow && leader) mbar_arrive(bar_xfree + 64);
        fence_regs<96>(B);
        int s = 1;
        if (i == 2) {
#pragma unroll 1
          for (; s < 3; s++) { issue192(A, c, s); retire(c); }
        }
        if (i > srole) {
#pragma unroll
          for (int u = 0; u < 6; u++, s++) {
            float2 bs[4];
            if (i == 2) lds_bias(bs, bias_t + (192 + 32 * u) * 4);
            if ((u & 1) && ow) mbar_wait(ow + 4 * s, 0);
            issue192(A, c, s);
            if (i == 2) {
              GELU16(h0, h1, B, 16 * u)
              stsm4((hst ^ ((2 * u & 3) << 5)) + (u >> 1) * 16384, h0);
              stsm4((hst ^ ((2 * u + 1 & 3) << 5)) + (u >> 1) * 16384, h1);
            } else if (i == 1) {
              if (u < 3) SPART16(reinterpret_cast<uint2*>(dst) + 128 * u, B, 16 * u)
              if (u == 2) hint_signal(&g_f_qkv[m * 8 + f]);
            } else {
              part_groups<0, 2>(&B[16 * u], dst + 2 * u * 32, par);
            }
            retire(c);
          }
        }
        const bool d1 = i == 1 + srole;
        const int send = d1 ? 10 : 15;
#pragma unroll 1
        for (; s < send; s++) {
          if (ow && !(s & 1)) mbar_wait(ow + 4 * s, 0);
          issue192(A, c, s);
          retire(c);
        }
        uint32_t W[48];
        if (d1) {
          const int head = 4 * f + (warp >> 1), rb0 = m * 8 + (warp & 1) * 4;
          issue192(A, c, 10);
          mbar_wait(bar_d, 0);
          d1_load<false>(W, rb0, head, opaque(lane));
          retire(c);
#pragma unroll 1
          for (s = 11; s < 13; s++) { issue192(A, c, s); retire(c); }
          issue192(A, c, 13);
          int tries = 0;
#pragma unroll 1
          while (d1_bad(W, t, par) && ++tries < (1 << 20)) d1_load<true>(W, rb0, head, opaque(lane));
          d1_mov(W, 0, t); d1_mov(W, 1, t);
          retire(c);
          issue192(A, c, 14);
          d1_mov(W, 2, t); d1_mov(W, 3, t);
          wg_wait<0>();
          asm volatile("bar.sync 4, 256;" ::: "memory");
          float R[18];
          d1_mma(W, R);
          float2* xch = reinterpret_cast<float2*>(smem + SM_SCR + (warp >> 1) * 1792) + opaque(lane);
          if (warp & 1) {
#pragma unroll
            for (int q = 0; q < 6; q++) xch[q * 32] = make_float2(R[2 * q], R[2 * q + 1]);
            if (lane < 12) { xch[192] = make_float2(R[12], R[13]); xch[204] = make_float2(R[14], R[15]); if (t == 0) xch[216 - lane + g] = make_float2(R[16], R[17]); }
          } else if (R[17] == 1.2345e-30f) R[16] = 0.f;
          asm volatile("bar.sync 4, 256;" ::: "memory");
          retire(c);
          issue192(A, c, 15);
          if (!(warp & 1)) {
            const int ln = opaque(lane);
#pragma unroll
            for (int q = 0; q < 6; q++) { const float2 o = xch[q * 32]; R[2 * q] += o.x; R[2 * q + 1] += o.y; }
            if (ln < 12) {
              const float2 o0 = xch[192], o1 = xch[204], o2 = xch[216 - ln + (ln >> 2)];
              R[12] += o0.x; R[13] += o0.y; R[14] += o1.x; R[15] += o1.y; R[16] += o2.x; R[17] += o2.y;
            }
            uint4* dkv = &g_kvp[(head * 80 + m) * 32 + ln];
#pragma unroll
            for (int w = 0; w < 5; w++)
              if (kv_valid(w, ln)) st_ll(dkv + w * 512, __float_as_uint(R[4 * w]), __float_as_uint(R[4 * w + 1]), w < 4 ? __float_as_uint(R[4 * w + 2]) : 0u, w < 4 ? __float_as_uint(R[4 * w + 3]) : 0u, par);
            __syncwarp();
            hint_signal(&g_f_kvp[head]);
          }
          STAMPW(0, 21);
        } else issue192(A, c, 15);
        if (i == 2) {
          const uint4* hsp = g_hsp + (blockIdx.x * 8 + warp) * 12 * 32 + opaque(lane);
#pragma unroll
          for (int q = 0; q < 12; q++) { const uint4 v = ldcg128(hsp + q * 32); W[4 * q] = v.x; W[4 * q + 1] = v.y; W[4 * q + 2] = v.z; W[4 * q + 3] = v.w; }
        } else {
#pragma unroll
          for (int q = 0; q < 48; q++) W[q] = 0;
        }
        retire(c);
        if (ow) mbar_wait(ow + 64, 0);
        issue192(A, c, 16);
        if (i == 2) wg_sync();
        retire(c);
        issue192(A, c, 17);
        if (i == 2) {
#pragma unroll
          for (int q = 0; q < 12; q++) stsm4((hst ^ ((q & 3) << 5)) + (3 + (q >> 2)) * 16384, make_uint4(W[4 * q], W[4 * q + 1], W[4 * q + 2], W[4 * q + 3]));
        }
        retire(c);
      }
      STAMPW(0, 2 + 2 * i);
      if ((i & 3) == 0) {
        issue96(B, c, 0, true);
        const int ln = opaque(lane);
        uint4* dst = i == 0 ? reinterpret_cast<uint4*>(g_qkv + (rb * 216 + 36 * f) * 32 + ln) : g_s + (rb * 36 + 12 * (f - 5)) * 32 + ln;
        LDS_R(1.f)
        retire(c);
        fence_regs<96>(A);
#pragma unroll
        for (int u = 0; u < 8; u++) {
          issue96(B, c, u + 1, false);
          if (u < 6) {
            if (i == 0) SPART16(reinterpret_cast<uint2*>(dst) + 128 * u, A, 16 * (u < 6 ? u : 0))
            else part_groups<0, 2>(&A[16 * (u < 6 ? u : 0)], dst + 2 * u * 32, par);
          }
          if (u == 5 && i == 0) hint_signal(&g_f_qkv[m * 8 + f]);
          retire(c);
        }
        if (i == 4) {
          STAMPW(0, 11);
          wg_wait<0>();
          c.release_prev();
          fence_regs<48>(B);
          part_groups<0, 6>(B, g_s + (rb * 36 + 6 * (f - 6)) * 32 + opaque(lane), par);
          break;
        }
      } else {
        issue192(B, c, 0, true);
        const int ln = opaque(lane);
        uint4* dst = i == 1 ? g_hsp + (blockIdx.x * 8 + warp) * 12 * 32 + ln : g_part + ((rb * 8 + f) * 36 + 12 * ((fr + 1) % 3)) * 32 + ln;
        const bool xf = i == 3 && srole && leader;
        const uint32_t bsa = bias_t + (i == 1 ? 0 : 384) * 4;
        LDS_R(GK)
        retire(c);
        fence_regs<96>(A);
        if (i == 3 && !srole) {
          const int nb = f - fr + (fr + 1) % 3;
          uint4 H[12], p[12];
          issue192(B, c, 1);
#pragma unroll
          for (int q = 0; q < 12; q++) H[q] = make_uint4(pack_bf16(A[8 * q], A[8 * q + 1]), pack_bf16(A[8 * q + 2], A[8 * q + 3]), pack_bf16(A[8 * q + 4], A[8 * q + 5]), pack_bf16(A[8 * q + 6], A[8 * q + 7]));
          retire(c);
          auto ldp = [&](const uint4* a0, const uint4* a1) {
#pragma unroll
            for (int q = 0; q < 6; q++) { p[q] = ld_ll(a0 + q * 32); p[6 + q] = ld_ll(a1 + q * 32); }
          };
          auto badp = [&]() {
            uint32_t bad = 0;
#pragma unroll
            for (int q = 0; q < 12; q++) ll_chk(bad, p[q].x, p[q].z, par);
            return __any_sync(0xffffffffu, bad & 1);
          };
#pragma unroll
          for (int w = 0; w < 2; w++) {
            const uint4 *a0 = dst + ((nb - f) * 36 + 6 * w) * 32, *a1 = dst + ((6 + f / 3 - f) * 36 + 6 * w) * 32;
            issue192(B, c, 2 + 5 * w);
            ldp(a0, a1);
            retire(c);
#pragma unroll 1
            for (int s = 3 + 5 * w; s < 5 + 5 * w; s++) { issue192(B, c, s); retire(c); }
            issue192(B, c, 5 + 5 * w);
            int tries = 0;
#pragma unroll 1
            while (badp() && ++tries < (1 << 20)) ldp(a0, a1);
#pragma unroll
            for (int q = 0; q < 6; q++) {
              if (q == 3) { retire(c); issue192(B, c, 6 + 5 * w); }
              const uint4 h = H[6 * w + q];
              st_ll(dst + (6 * w + q) * 32, hadd2(h.x, hadd2(p[q].x, p[6 + q].x)), hadd2(h.y, hadd2(p[q].y, p[6 + q].y)), hadd2(h.z, hadd2(p[q].z, p[6 + q].z)), hadd2(h.w, hadd2(p[q].w, p[6 + q].w)), par);
            }
            retire(c);
          }
#pragma unroll 1
          for (int s = 12; s < 16; s++) { issue192(B, c, s); retire(c); }
          const int c2 = (fr + 2) % 3, v0 = 12 * c2 + (f < 3 ? 0 : 6), fo = f < 3 ? f + 3 : f - 3;
          const int l2 = opaque(lane);
          const int ro = (rb * 16 + (l2 >> 2)) * D_ + 2 * (l2 & 3) + 16 * v0;
          uint32_t xx[24], bb[12];
          issue192(B, c, 16);
#pragma unroll
          for (int j = 0; j < 12; j++) {
            xx[2 * j] = __ldg(reinterpret_cast<const uint32_t*>(P.x + ro + 8 * j));
            xx[2 * j + 1] = __ldg(reinterpret_cast<const uint32_t*>(P.x + ro + 8 * D_ + 8 * j));
            bb[j] = __ldg(reinterpret_cast<const uint32_t*>(P.b2 + 16 * v0 + 8 * j + 2 * (l2 & 3)));
          }
          retire(c);
          issue192(B, c, 17);
          const uint4* pb = g_part + (rb * 8 * 36 + v0) * 32 + l2;
          const uint4 *a0 = pb + ((fr + 1) % 3) * 36 * 32, *a1 = a0 + 3 * 36 * 32;
          ldp(a0, a1);
          retire(c);
          STAMPW(0, 9);
          wg_wait<0>();
          c.release_prev();
          fence_regs<96>(B);
          uint4* snd = g_part + ((rb * 8 + f) * 36 + 12 * c2 + (f < 3 ? 6 : 0)) * 32 + l2;
          if (f < 3) part_groups<0, 6>(B + 48, snd, par);
          else {
            part_groups<0, 6>(B, snd, par);
#pragma unroll
            for (int q = 0; q < 48; q++) B[q] = B[48 + q];
          }
          STAMPW(0, 12);
          int tries = 0;
#pragma unroll 1
          while (badp() && ++tries < (1 << 20)) ldp(a0, a1);
#pragma unroll
          for (int q = 0; q < 24; q++) {
            const uint32_t w = hadd2(reinterpret_cast<const uint32_t*>(p)[q], reinterpret_cast<const uint32_t*>(p)[24 + q]);
            B[2 * q] = fmaf(B[2 * q] + bf_lo(w), 0.5f / GK, bf_lo(bb[q >> 1])); B[2 * q + 1] = fmaf(B[2 * q + 1] + bf_hi(w), 0.5f / GK, bf_hi(bb[q >> 1]));
          }
          tries = 0;
#pragma unroll 1
          do { ldp(pb + fo * 36 * 32, g_s + (rb * 36 + v0) * 32 + l2); } while (badp() && ++tries < (1 << 20));
          STAMPW(0, 14);
#pragma unroll
          for (int q = 0; q < 24; q++) {
            const uint32_t w = reinterpret_cast<const uint32_t*>(p)[q];
            const uint32_t gt = pack_bf16(silu(fmaf(bf_lo(w), 0.5f / GK, B[2 * q])), silu(fmaf(bf_hi(w), 0.5f / GK, B[2 * q + 1])));
            *reinterpret_cast<uint32_t*>(P.out + ro + (q & 1) * 8 * D_ + 8 * (q >> 1)) = hfma2(reinterpret_cast<const uint32_t*>(p)[24 + q], gt, xx[q]);
          }
          break;
        }
        uint4 H[6];
#pragma unroll
        for (int u = 0; u < 6; u++) {
          float2 bs[4];
          if (i != 3) lds_bias(bs, bsa + 32 * u * 4);
          issue192(B, c, u + 1);
          if (i != 3) {
            GELU16(h0, h1, A, 16 * u)
            H[u] = h1;
            if (i == 1) dst[2 * u * 32] = h0;
            else {
              stsm4((hst ^ ((2 * u & 3) << 5)) + (6 + (u >> 1)) * 16384, h0);
              stsm4((hst ^ ((2 * u + 1 & 3) << 5)) + (6 + (u >> 1)) * 16384, h1);
              if (u == 3) wg_sync();
            }
          } else {
            part_groups<0, 2>(&A[16 * u], dst + 2 * u * 32, par);
            H[u] = make_uint4(0, 0, 0, 0);
          }
          retire(c);
          if ((u & 1) && xf) mbar_arrive(bar_xfree + 4 * u - 4);
        }
        {
#pragma unroll 1
          for (int s = 7; s < 17; s++) {
            issue192(B, c, s);
            if (i == 1) {
#pragma unroll
              for (int u = 0; u < 6; u++) if (s == 7 + u) dst[(2 * u + 1) * 32] = H[u];
            }
            if (s == 9 && i == 2) wg_sync();
            retire(c);
            if ((s & 1) == 0 && xf) mbar_arrive(bar_xfree + 4 * s - 8);
          }
        }
        issue192(B, c, 17);
        retire(c);
      }
      STAMPW(0, 3 + 2 * i);
    }

    STAMPW(0, 15);
    cluster_arrive_relaxed();
    cluster_wait();
    STAMPW(0, 16);
    if (tid == 0) g_epoch[blockIdx.x] = ep;
  }
}

typedef CUresult (*EncFn)(CUtensorMap*, CUtensorMapDataType, cuuint32_t, void*, const cuuint64_t*, const cuuint64_t*, const cuuint32_t*, const cuuint32_t*,
                          CUtensorMapInterleave, CUtensorMapSwizzle, CUtensorMapL2promotion, CUtensorMapFloatOOBfill);

void make_map(EncFn enc, CUtensorMap* tm, const void* ptr, int rows, int cols, int box_rows, int mode = 0) {
  cuuint64_t gd[2] = {(cuuint64_t)cols, (cuuint64_t)rows};
  cuuint64_t gs[1] = {(cuuint64_t)cols * 2};
  cuuint32_t bx[2] = {mode == 1 ? 32u : (mode == 2 ? 72u : 64u), (cuuint32_t)box_rows};
  cuuint32_t es[2] = {1, 1};
  enc(tm, CU_TENSOR_MAP_DATA_TYPE_BFLOAT16, 2, const_cast<void*>(ptr), gd, gs, bx, es, CU_TENSOR_MAP_INTERLEAVE_NONE, mode == 1 ? CU_TENSOR_MAP_SWIZZLE_64B : (mode == 2 ? CU_TENSOR_MAP_SWIZZLE_NONE : CU_TENSOR_MAP_SWIZZLE_128B),
      CU_TENSOR_MAP_L2_PROMOTION_L2_256B, CU_TENSOR_MAP_FLOAT_OOB_FILL_NONE);
}

}

extern "C" void kernel_launch(void* const* d_in, const int* in_sizes, int n_in, void* d_out, int out_size) {
  (void)in_sizes; (void)n_in; (void)out_size;
  static EncFn enc = nullptr;
  static void *a_ptr = nullptr, *m_ptr = nullptr;
  if (!enc) {
    void* fn = nullptr; cudaDriverEntryPointQueryResult q;
    cudaGetDriverEntryPoint("cuTensorMapEncodeTiled", &fn, cudaEnableDefault, &q);
    enc = (EncFn)fn;
    cudaFuncSetAttribute(fused_kernel, cudaFuncAttributeMaxDynamicSharedMemorySize, SMEM_BYTES);
    cudaGetSymbolAddress(&a_ptr, g_a);
    cudaGetSymbolAddress(&m_ptr, g_m);
  }
  Params P;
  P.x = (const __nv_bfloat16*)d_in[0];
  P.wqkv = (const __nv_bfloat16*)d_in[1];
  P.wo = (const __nv_bfloat16*)d_in[2];
  P.w1 = (const __nv_bfloat16*)d_in[4];
  P.b1 = (const __nv_bfloat16*)d_in[5];
  P.w2 = (const __nv_bfloat16*)d_in[6];
  P.b2 = (const __nv_bfloat16*)d_in[7];
  P.out = (__nv_bfloat16*)d_out;
  make_map(enc, &P.tm_wqkv, P.wqkv, D_, Q3_, 32);
  make_map(enc, &P.tm_w1, P.w1, D_, F_, 32);
  make_map(enc, &P.tm_w2, P.w2, F_, D_, 32);
  make_map(enc, &P.tm_m, m_ptr, D_, D_, 32);
  make_map(enc, &P.tm_wqkv64, P.wqkv, D_, Q3_, 64, 1);
  make_map(enc, &P.tm_m64, m_ptr, D_, D_, 64, 1);
  make_map(enc, &P.tm_a, a_ptr, S_, D_, 128);
  make_map(enc, &P.tm_ast, a_ptr, S_, D_, 16, 2);
  fused_kernel<<<NCTAS, NTHREADS, SMEM_BYTES, cudaStreamPerThread>>>(P);
}
```

```cpp
#include <cuda_runtime.h>
#include <cuda.h>
#include <cuda_bf16.h>
#include <stdint.h>

namespace {

constexpr int S_ = 2048, D_ = 576, F_ = 4608, Q3_ = 1728;
constexpr int NSTAGE = 6, STAGE_BYTES = 12288;
constexpr int SM_A = 0, SM_B = 147456, SM_BIAS = SM_B + NSTAGE * STAGE_BYTES, SM_RSTD = SM_BIAS + 2304 + 128, SM_SCR = SM_RSTD + 512, SM_BAR = SM_SCR + 7168;
constexpr int SMEM_BYTES = SM_BAR + 320;
constexpr int NTHREADS = 384;
constexpr int NCTAS = 132;

__device__ uint2 g_qkv[(128 * 216 + 2) * 32];
__device__ __align__(1024) __nv_bfloat16 g_a[S_ * D_];
__device__ __align__(1024) __nv_bfloat16 g_m[D_ * D_];
__device__ uint4 g_kvp[32 * 5 * 16 * 32];
__device__ uint4 g_z[32 * 2 * 4];
__device__ uint4 g_part[128 * 8 * 36 * 32];
__device__ uint4 g_s[128 * 36 * 32];
__device__ uint4 g_hsp[128 * 12 * 256];
__device__ uint32_t g_f_qkv[16 * 8];
__device__ uint32_t g_f_kvp[32];
__device__ uint32_t g_f_z[32];
__device__ uint32_t g_f_a[16];
__device__ uint32_t g_f_m[1];
__device__ uint2 g_stat[S_];
__device__ uint32_t g_epoch[NCTAS];

#define STAMP(i)
#define STAMPW(w, i)
#define WSTAMP(i)
__device__ __forceinline__ uint32_t smem_u32(const void* p) { return (uint32_t)__cvta_generic_to_shared(p); }
__device__ __forceinline__ void mbar_init(uint32_t a, int c) { asm volatile("mbarrier.init.shared::cta.b64 [%0], %1;" ::"r"(a), "r"(c)); }
__device__ __forceinline__ void mbar_expect(uint32_t a, uint32_t b) { asm volatile("mbarrier.arrive.expect_tx.shared::cta.b64 _, [%0], %1;" ::"r"(a), "r"(b) : "memory"); }
__device__ __forceinline__ void mbar_arrive(uint32_t a) { asm volatile("mbarrier.arrive.shared::cta.b64 _, [%0];" ::"r"(a) : "memory"); }
__device__ __forceinline__ void mbar_arrive_cl(uint32_t a) { asm volatile("mbarrier.arrive.shared::cluster.b64 _, [%0];" ::"r"(a) : "memory"); }
__device__ __forceinline__ uint32_t mapa(uint32_t a, uint32_t cta) { uint32_t r; asm volatile("mapa.shared::cluster.u32 %0, %1, %2;" : "=r"(r) : "r"(a), "r"(cta)); return r; }
__device__ __forceinline__ void mbar_wait(uint32_t a, uint32_t ph) {
  uint32_t ok; int it = 0;
#pragma unroll 1
  do {
    asm volatile("{.reg .pred p; mbarrier.try_wait.parity.shared::cta.b64 p, [%1], %2; selp.u32 %0,1,0,p;}" : "=r"(ok) : "r"(a), "r"(ph) : "memory");
  } while (!ok && ++it < (1 << 18));
}
__device__ __forceinline__ void tma2d(uint32_t dst, const CUtensorMap* m, int c0, int c1, uint32_t bar) {
  asm volatile("cp.async.bulk.tensor.2d.shared::cluster.global.mbarrier::complete_tx::bytes [%0], [%1, {%3,%4}], [%2];" ::"r"(dst), "l"(m), "r"(bar), "r"(c0), "r"(c1) : "memory");
}
__device__ __forceinline__ void tma2d_mc(uint32_t dst, const CUtensorMap* m, int c0, int c1, uint32_t bar) {
  asm volatile("cp.async.bulk.tensor.2d.shared::cluster.global.mbarrier::complete_tx::bytes.multicast::cluster [%0], [%1, {%3,%4}], [%2], %5;" ::"r"(dst), "l"(m), "r"(bar), "r"(c0), "r"(c1), "h"((uint16_t)3) : "memory");
}
__device__ __forceinline__ void cluster_arrive_relaxed() { asm volatile("barrier.cluster.arrive.relaxed.aligned;" ::: "memory"); }
__device__ __forceinline__ void cluster_wait() { asm volatile("barrier.cluster.wait.acquire.aligned;" ::: "memory"); }
__device__ __forceinline__ void wg_fence() { asm volatile("wgmma.fence.sync.aligned;" ::: "memory"); }
__device__ __forceinline__ void wg_commit() { asm volatile("wgmma.commit_group.sync.aligned;" ::: "memory"); }
template <int n> __device__ __forceinline__ void wg_wait() { asm volatile("wgmma.wait_group.sync.aligned %0;" ::"n"(n) : "memory"); }
__device__ __forceinline__ uint32_t ld_acquire(const uint32_t* p) { uint32_t v; asm volatile("ld.acquire.gpu.global.u32 %0, [%1];" : "=r"(v) : "l"(p) : "memory"); return v; }
__device__ __forceinline__ void flag_wait(const uint32_t* p, uint32_t target) {
  int it = 0;
#pragma unroll 1
  while ((int)(ld_acquire(p) - target) < 0 && ++it < (1 << 20)) __nanosleep(300);
}
__device__ __forceinline__ void hint_signal(uint32_t* p) {
  if ((threadIdx.x & 31) == 0) asm volatile("red.relaxed.gpu.global.add.u32 [%0], 1;" ::"l"(p) : "memory");
}
__device__ __forceinline__ void hint_wait(const uint32_t* p, uint32_t target, uint32_t ns = 400) {
  int it = 0; uint32_t v;
#pragma unroll 1
  do { asm volatile("ld.relaxed.gpu.global.u32 %0, [%1];" : "=r"(v) : "l"(p) : "memory"); if ((int)(v - target) >= 0) break; __nanosleep(ns); } while (++it < (1 << 20));
}
__device__ __forceinline__ uint32_t tag(uint32_t x, uint32_t par) { uint32_t r; asm("lop3.b32 %0, %1, 0xfffffffe, %2, 0xea;" : "=r"(r) : "r"(x), "r"(par)); return r; }
__device__ __forceinline__ void st_ll(uint4* p, uint32_t x, uint32_t y, uint32_t z, uint32_t w, uint32_t par) {
  asm volatile("{.reg .b64 a, b; mov.b64 a, {%1,%2}; mov.b64 b, {%3,%4}; st.relaxed.gpu.global.v2.b64 [%0], {a, b};}"
               ::"l"(p), "r"(tag(x, par)), "r"(y), "r"(tag(z, par)), "r"(w) : "memory");
}
__device__ __forceinline__ uint4 ld_ll(const uint4* p) {
  uint4 v;
  asm volatile("{.reg .b64 a, b; ld.relaxed.gpu.global.v2.b64 {a, b}, [%4]; mov.b64 {%0,%1}, a; mov.b64 {%2,%3}, b;}"
               : "=r"(v.x), "=r"(v.y), "=r"(v.z), "=r"(v.w) : "l"(p) : "memory");
  return v;
}
__device__ __forceinline__ void st_ll64(uint2* p, uint32_t x, uint32_t y, uint32_t par) {
  asm volatile("{.reg .b64 a; mov.b64 a, {%1,%2}; st.relaxed.gpu.global.b64 [%0], a;}" ::"l"(p), "r"(tag(x, par)), "r"(y) : "memory");
}
__device__ __forceinline__ uint2 ld_ca64(const void* p) {
  uint2 v;
  asm volatile("{.reg .b64 a; ld.global.ca.b64 a, [%2]; mov.b64 {%0,%1}, a;}" : "=r"(v.x), "=r"(v.y) : "l"(p) : "memory");
  return v;
}
__device__ __forceinline__ uint2 ld_ll64(const void* p) {
  uint2 v;
  asm volatile("{.reg .b64 a; ld.relaxed.gpu.global.b64 a, [%2]; mov.b64 {%0,%1}, a;}" : "=r"(v.x), "=r"(v.y) : "l"(p) : "memory");
  return v;
}
__device__ __forceinline__ void ll_chk(uint32_t& bad, uint32_t a, uint32_t b, uint32_t par) {
  uint32_t u; asm("lop3.b32 %0, %1, %2, %3, 0x7e;" : "=r"(u) : "r"(a), "r"(b), "r"(par));
  asm("or.b32 %0, %0, %1;" : "+r"(bad) : "r"(u));
}
__device__ __forceinline__ uint32_t hadd2(uint32_t a, uint32_t b) { uint32_t d; asm("add.rn.bf16x2 %0, %1, %2;" : "=r"(d) : "r"(a), "r"(b)); return d; }
__device__ __forceinline__ uint32_t hfma2(uint32_t a, uint32_t b, uint32_t c) { uint32_t d; asm("fma.rn.bf16x2 %0, %1, %2, %3;" : "=r"(d) : "r"(a), "r"(b), "r"(c)); return d; }
__device__ __forceinline__ uint32_t pack_bf16(float lo, float hi) { uint32_t r; asm("cvt.rn.bf16x2.f32 %0, %1, %2;" : "=r"(r) : "f"(hi), "f"(lo)); return r; }
__device__ __forceinline__ float bf_lo(uint32_t v) { return __uint_as_float(v << 16); }
__device__ __forceinline__ float bf_hi(uint32_t v) { return __uint_as_float(v & 0xffff0000u); }
__device__ __forceinline__ uint32_t movmat(uint32_t a) { uint32_t d; asm volatile("movmatrix.sync.aligned.m8n8.trans.b16 %0, %1;" : "=r"(d) : "r"(a)); return d; }
__device__ __forceinline__ void mma16816(float* c, uint32_t a0, uint32_t a1, uint32_t a2, uint32_t a3, uint32_t b0, uint32_t b1) {
  asm volatile("mma.sync.aligned.m16n8k16.row.col.f32.bf16.bf16.f32 {%0,%1,%2,%3}, {%4,%5,%6,%7}, {%8,%9}, {%0,%1,%2,%3};"
               : "+f"(c[0]), "+f"(c[1]), "+f"(c[2]), "+f"(c[3]) : "r"(a0), "r"(a1), "r"(a2), "r"(a3), "r"(b0), "r"(b1));
}
__device__ __forceinline__ uint4 ldcg128(const void* p) { uint4 v; asm volatile("ld.global.cg.v4.u32 {%0,%1,%2,%3}, [%4];" : "=r"(v.x), "=r"(v.y), "=r"(v.z), "=r"(v.w) : "l"(p) : "memory"); return v; }

template <int N> __device__ __forceinline__ void wgmma_ss(float* d, uint64_t da, uint64_t db, int sc);
template <int N> __device__ __forceinline__ void wgmma_rs(float* d, const uint32_t* a, uint64_t db, int sc);
template <> __device__ __forceinline__ void wgmma_ss<96>(float* d, uint64_t da, uint64_t db, int sc) {
  asm volatile("{.reg .pred p; setp.ne.b32 p, %50, 0; wgmma.mma_async.sync.aligned.m64n96k16.f32.bf16.bf16 {%0, %1, %2, %3, %4, %5, %6, %7, %8, %9, %10, %11, %12, %13, %14, %15, %16, %17, %18, %19, %20, %21, %22, %23, %24, %25, %26, %27, %28, %29, %30, %31, %32, %33, %34, %35, %36, %37, %38, %39, %40, %41, %42, %43, %44, %45, %46, %47}, %48, %49, p, 1, 1, 0, 1;}"
   : "+f"(d[0]), "+f"(d[1]), "+f"(d[2]), "+f"(d[3]), "+f"(d[4]), "+f"(d[5]), "+f"(d[6]), "+f"(d[7]), "+f"(d[8]), "+f"(d[9]), "+f"(d[10]), "+f"(d[11]), "+f"(d[12]), "+f"(d[13]), "+f"(d[14]), "+f"(d[15]), "+f"(d[16]), "+f"(d[17]), "+f"(d[18]), "+f"(d[19]), "+f"(d[20]), "+f"(d[21]), "+f"(d[22]), "+f"(d[23]), "+f"(d[24]), "+f"(d[25]), "+f"(d[26]), "+f"(d[27]), "+f"(d[28]), "+f"(d[29]), "+f"(d[30]), "+f"(d[31]), "+f"(d[32]), "+f"(d[33]), "+f"(d[34]), "+f"(d[35]), "+f"(d[36]), "+f"(d[37]), "+f"(d[38]), "+f"(d[39]), "+f"(d[40]), "+f"(d[41]), "+f"(d[42]), "+f"(d[43]), "+f"(d[44]), "+f"(d[45]), "+f"(d[46]), "+f"(d[47]) : "l"(da), "l"(db), "r"(sc));
}
template <> __device__ __forceinline__ void wgmma_ss<192>(float* d, uint64_t da, uint64_t db, int sc) {
  asm volatile("{.reg .pred p; setp.ne.b32 p, %98, 0; wgmma.mma_async.sync.aligned.m64n192k16.f32.bf16.bf16 {%0, %1, %2, %3, %4, %5, %6, %7, %8, %9, %10, %11, %12, %13, %14, %15, %16, %17, %18, %19, %20, %21, %22, %23, %24, %25, %26, %27, %28, %29, %30, %31, %32, %33, %34, %35, %36, %37, %38, %39, %40, %41, %42, %43, %44, %45, %46, %47, %48, %49, %50, %51, %52, %53, %54, %55, %56, %57, %58, %59, %60, %61, %62, %63, %64, %65, %66, %67, %68, %69, %70, %71, %72, %73, %74, %75, %76, %77, %78, %79, %80, %81, %82, %83, %84, %85, %86, %87, %88, %89, %90, %91, %92, %93, %94, %95}, %96, %97, p, 1, 1, 0, 1;}"
   : "+f"(d[0]), "+f"(d[1]), "+f"(d[2]), "+f"(d[3]), "+f"(d[4]), "+f"(d[5]), "+f"(d[6]), "+f"(d[7]), "+f"(d[8]), "+f"(d[9]), "+f"(d[10]), "+f"(d[11]), "+f"(d[12]), "+f"(d[13]), "+f"(d[14]), "+f"(d[15]), "+f"(d[16]), "+f"(d[17]), "+f"(d[18]), "+f"(d[19]), "+f"(d[20]), "+f"(d[21]), "+f"(d[22]), "+f"(d[23]), "+f"(d[24]), "+f"(d[25]), "+f"(d[26]), "+f"(d[27]), "+f"(d[28]), "+f"(d[29]), "+f"(d[30]), "+f"(d[31]), "+f"(d[32]), "+f"(d[33]), "+f"(d[34]), "+f"(d[35]), "+f"(d[36]), "+f"(d[37]), "+f"(d[38]), "+f"(d[39]), "+f"(d[40]), "+f"(d[41]), "+f"(d[42]), "+f"(d[43]), "+f"(d[44]), "+f"(d[45]), "+f"(d[46]), "+f"(d[47]), "+f"(d[48]), "+f"(d[49]), "+f"(d[50]), "+f"(d[51]), "+f"(d[52]), "+f"(d[53]), "+f"(d[54]), "+f"(d[55]), "+f"(d[56]), "+f"(d[57]), "+f"(d[58]), "+f"(d[59]), "+f"(d[60]), "+f"(d[61]), "+f"(d[62]), "+f"(d[63]), "+f"(d[64]), "+f"(d[65]), "+f"(d[66]), "+f"(d[67]), "+f"(d[68]), "+f"(d[69]), "+f"(d[70]), "+f"(d[71]), "+f"(d[72]), "+f"(d[73]), "+f"(d[74]), "+f"(d[75]), "+f"(d[76]), "+f"(d[77]), "+f"(d[78]), "+f"(d[79]), "+f"(d[80]), "+f"(d[81]), "+f"(d[82]), "+f"(d[83]), "+f"(d[84]), "+f"(d[85]), "+f"(d[86]), "+f"(d[87]), "+f"(d[88]), "+f"(d[89]), "+f"(d[90]), "+f"(d[91]), "+f"(d[92]), "+f"(d[93]), "+f"(d[94]), "+f"(d[95]) : "l"(da), "l"(db), "r"(sc));
}

__device__ __forceinline__ uint64_t desc64(uint32_t lo, uint32_t hi) { uint64_t d; asm("mov.b64 %0, {%1, %2};" : "=l"(d) : "r"(lo), "r"(hi)); return d; }
constexpr uint32_t DESC_HI = (1024u >> 4) | (1u << 30);
constexpr uint32_t DESC_HI64 = (512u >> 4) | (2u << 30);
template <int n> __device__ __forceinline__ void fence_regs(float* a) {
#pragma unroll
  for (int i = 0; i < n; i++) asm volatile("" : "+f"(a[i])::"memory");
}

struct Ctx {
  uint32_t full;
  uint32_t emb;
  bool sig;
  uint32_t stage, phase, prev;
  uint32_t dB, dA;
  __device__ __forceinline__ void release_prev() { if (sig && prev != ~0u) mbar_arrive_cl(emb + prev); }
  __device__ __forceinline__ void wait_full() {
    mbar_wait(full + 8 * stage, phase);
    wg_fence();
  }
};

__device__ __forceinline__ void issue192(float* acc, Ctx& c, int s, bool first = false) {
  c.wait_full();
  const uint32_t db = c.dB + c.stage * (STAGE_BYTES >> 4);
  const uint32_t da = c.dA + (s >> 1) * 1024 + (s & 1) * 4;
  wgmma_ss<192>(acc, desc64(da, DESC_HI), desc64(db, DESC_HI), first ? 0 : 1);
  wgmma_ss<192>(acc, desc64(da + 2, DESC_HI), desc64(db + 128, DESC_HI), 1);
  wg_commit();
}
__device__ __forceinline__ void issue96(float* acc, Ctx& c, int s, bool first) {
  c.wait_full();
  const uint32_t db = c.dB + c.stage * (STAGE_BYTES >> 4);
  const uint32_t da = c.dA + s * 1024;
  if (first) { wgmma_ss<192>(acc, desc64(da, DESC_HI), desc64(db, DESC_HI64), 0); wg_fence(); }
#pragma unroll
  for (int kk = first ? 1 : 0; kk < 4; kk++) wgmma_ss<96>(acc, desc64(da + 2 * kk, DESC_HI), desc64(db + 64 * kk, DESC_HI64), 1);
  wg_commit();
}
__device__ __forceinline__ void retire(Ctx& c) {
  wg_wait<1>();
  c.release_prev();
  c.prev = 8 * c.stage;
  if (++c.stage == NSTAGE) { c.stage = 0; c.phase ^= 1; }
}
constexpr float GK = 0.32920349f;
__device__ __forceinline__ uint32_t gelu_pair(uint32_t y) {
  uint32_t u, th;
  asm("mul.rn.bf16x2 %0, %1, %2;" : "=r"(u) : "r"(hfma2(y, y, 0x401b401bu)), "r"(y));
  asm("tanh.approx.bf16x2 %0, %1;" : "=r"(th) : "r"(u));
  return hfma2(y, th, y);
}
__device__ __forceinline__ uint4 gelu_group(const uint32_t* a) { return make_uint4(gelu_pair(a[0]), gelu_pair(a[1]), gelu_pair(a[2]), gelu_pair(a[3])); }
__device__ __forceinline__ uint32_t fma_pack_v(const float* a, float r, float2 b) {
  uint32_t e; asm volatile("{.reg .f32 x, y; fma.rn.f32 x, %1, %3, %4; fma.rn.f32 y, %2, %3, %5; cvt.rn.bf16x2.f32 %0, y, x;}" : "=r"(e) : "f"(a[0]), "f"(a[1]), "f"(r), "f"(b.x), "f"(b.y)); return e;
}
__device__ __forceinline__ void lds_bias(float2* b, uint32_t addr) {
#pragma unroll
  for (int j = 0; j < 4; j++) asm volatile("ld.shared.v2.f32 {%0,%1}, [%2];" : "=f"(b[j].x), "=f"(b[j].y) : "r"(addr + 32 * j));
}
__device__ __forceinline__ int opaque(int v) { asm volatile("" : "+r"(v)); return v; }
__device__ __forceinline__ void stsm4(uint32_t addr, uint4 r) {
  asm volatile("stmatrix.sync.aligned.m8n8.x4.shared.b16 [%0], {%1,%2,%3,%4};" ::"r"(addr), "r"(r.x), "r"(r.y), "r"(r.z), "r"(r.w) : "memory");
}
__device__ __forceinline__ float ex2f(float x) { float r; asm("ex2.approx.ftz.f32 %0, %1;" : "=f"(r) : "f"(x)); return r; }
__device__ __forceinline__ uint32_t phi2(uint32_t tp) {
  uint32_t x, y;
  const float a0 = bf_lo(tp) * 1.4426950408889634f, a1 = bf_hi(tp) * 1.4426950408889634f;
  asm("max.bf16x2 %0, %1, %2;" : "=r"(x) : "r"(tp), "r"(0x35863586u));
  asm("min.bf16x2 %0, %1, %2;" : "=r"(y) : "r"(pack_bf16(ex2f(a0), ex2f(a1))), "r"(0x3f803f80u));
  return hadd2(x, y);
}
template <int q0, int q1>
__device__ __forceinline__ void part_groups(const float* a, uint4* p, uint32_t par) {
#pragma unroll
  for (int q = q0; q < q1; q++)
    st_ll(p + q * 32, pack_bf16(a[8 * q], a[8 * q + 1]), pack_bf16(a[8 * q + 2], a[8 * q + 3]), pack_bf16(a[8 * q + 4], a[8 * q + 5]), pack_bf16(a[8 * q + 6], a[8 * q + 7]), par);
}
__device__ __forceinline__ float rcpf(float x) { float r; asm("rcp.approx.ftz.f32 %0, %1;" : "=f"(r) : "f"(x)); return r; }
__device__ __forceinline__ float silu_h(float h) { float r; asm("tanh.approx.f32 %0, %1;" : "=f"(r) : "f"(h)); return fmaf(h, r, h); }
__device__ __forceinline__ int pairoff(int p, int g) { return (p >> 2) * 32 + g * 4 + (p & 3); }
template <bool STRONG> __device__ __forceinline__ void d1_load(uint32_t* W, int rb0, int head, int ln) {
  const uint2* qf = g_qkv + rb0 * 216 * 32 + pairoff(288 + head * 9 + (ln & 3), ln >> 2);
#pragma unroll
  for (int b = 0; b < 3; b++) {
#pragma unroll
    for (int j = 0; j < 4; j++) {
      const uint2* p = qf + j * 216 * 32 + 32 * b;
      const uint2 kk = STRONG ? ld_ll64(p) : ld_ca64(p), vv = STRONG ? ld_ll64(p + 72 * 32) : ld_ca64(p + 72 * 32);
      W[6 * j + 2 * b] = kk.x; W[6 * j + 2 * b + 1] = kk.y; W[24 + 6 * j + 2 * b] = vv.x; W[24 + 6 * j + 2 * b + 1] = vv.y;
    }
  }
}
__device__ __forceinline__ bool d1_bad(const uint32_t* W, int t, uint32_t par) {
  uint32_t bad = 0, bad2 = 0;
#pragma unroll
  for (int q = 0; q < 12; q++) ll_chk((q % 3) != 2 ? bad : bad2, W[2 * q], W[24 + 2 * q], par);
  return __any_sync(0xffffffffu, (bad | (t == 0 ? bad2 : 0u)) & 1);
}
__device__ __forceinline__ void d1_mov(uint32_t* W, int j, int t) {
  if (t != 0) { W[6 * j + 4] = W[6 * j + 5] = 0u; W[24 + 6 * j + 4] = W[24 + 6 * j + 5] = (t == 1 ? 0x00003f80u : 0u); }
#pragma unroll
  for (int q = 0; q < 6; q++) { W[6 * j + q] = movmat(W[6 * j + q]); W[24 + 6 * j + q] = movmat(W[24 + 6 * j + q]); }
}
__device__ __forceinline__ void d1_mma(const uint32_t* W, float* R) {
  float c1[3][4];
#pragma unroll
  for (int j = 0; j < 12; j++) { R[j] = 0.f; c1[j >> 2][j & 3] = 0.f; }
#pragma unroll
  for (int ks = 0; ks < 4; ks++)
#pragma unroll
    for (int j = 0; j < 3; j++) {
      mma16816(R + 4 * j, W[24 + 6 * ks], W[24 + 6 * ks + 2], W[24 + 6 * ks + 1], W[24 + 6 * ks + 3], W[6 * ks + 2 * j], W[6 * ks + 2 * j + 1]);
      mma16816(c1[j], W[24 + 6 * ks + 4], 0u, W[24 + 6 * ks + 5], 0u, W[6 * ks + 2 * j], W[6 * ks + 2 * j + 1]);
    }
#pragma unroll
  for (int j = 0; j < 3; j++) { R[12 + 2 * j] = c1[j][0]; R[13 + 2 * j] = c1[j][1]; }
}
__device__ __forceinline__ bool kv_valid(int w, int ln) { return (w < 3 || ln < 12) && ((w != 2 && w != 4) || (ln & 3) == 0); }

struct Params {
  CUtensorMap tm_wqkv, tm_w1, tm_w2, tm_m, tm_wqkv64, tm_m64, tm_a, tm_ast;
  const __nv_bfloat16 *x, *b1, *b2, *wqkv, *w1, *w2, *wo;
  __nv_bfloat16* out;
};

__global__ void __cluster_dims__(2, 1, 1) __launch_bounds__(NTHREADS, 1) fused_kernel(const __grid_constant__ Params P) {
  extern __shared__ __align__(1024) uint8_t smem[];
  const uint32_t sbase = smem_u32(smem);
  const int tid = threadIdx.x, lane = tid & 31;
  const int warp = __shfl_sync(0xffffffffu, tid >> 5, 0);
  const int g = lane >> 2, t = lane & 3;
  const uint32_t ep = __shfl_sync(0xffffffffu, g_epoch[blockIdx.x], 0) + 1;
  const uint32_t par = ep & 1;
  STAMPW(0, 0);

  if (blockIdx.x >= 128) {
    const int a = blockIdx.x - 128;
    constexpr int WP = 1168, SM_T = 152 * WP, SM_HB = SM_T + 8 * 32 * 80;
    if (tid == 0) {
      mbar_init(sbase + SM_HB, 1);
      asm volatile("fence.mbarrier_init.release.cluster;" ::: "memory");
      mbar_expect(sbase + SM_HB, 144 * 1152);
    }
    for (int i = tid; i < (8 * WP + 8 * 32 * 80) / 4; i += NTHREADS) reinterpret_cast<uint32_t*>(smem + 144 * WP)[i] = 0u;
    __syncthreads();
    __nanosleep(1500);
    if (tid < 144)
      asm volatile("cp.async.bulk.shared::cluster.global.mbarrier::complete_tx::bytes [%0], [%1], %2, [%3];" ::"r"(sbase + tid * WP), "l"(P.wo + (a * 144 + tid) * D_), "r"(1152), "r"(sbase + SM_HB) : "memory");
    if (warp >= 8 && lane == 0) {
      const int id = a * 4 + (warp - 8);
      constexpr uint32_t CH = 9216 * 2;
#pragma unroll 1
      for (int i = id; i < 576; i += 16) {
        const char* p = i < 288 ? (const char*)P.w1 + (size_t)i * CH : (const char*)P.w2 + (size_t)(i - 288) * CH;
        asm volatile("cp.async.bulk.prefetch.L2.global [%0], %1;" ::"l"(p), "r"(CH) : "memory");
      }
    }
    __syncwarp();
    if (lane < 8) hint_wait(&g_f_kvp[a * 8 + lane], 16 * ep, 50);
    __syncwarp();
    STAMPW(0, 1);
#pragma unroll 1
    for (int u = warp; u < 40; u += 12) {
      const int hh = u & 7, w = 4 - (u >> 3), head = a * 8 + hh;
      uint4 v[16];
      int tries = 0;
      uint32_t bad;
      const bool val = kv_valid(w, lane);
#pragma unroll 1
      do {
        bad = 0;
#pragma unroll
        for (int j = 0; j < 16; j++) v[j] = val ? ld_ll(&g_kvp[((head * 5 + w) * 16 + j) * 32 + lane]) : make_uint4(par, 0u, par, 0u);
#pragma unroll
        for (int j = 0; j < 16; j++) ll_chk(bad, v[j].x, v[j].z, par);
      } while (__any_sync(0xffffffffu, bad & 1) && ++tries < (1 << 20));
      float s0 = 0.f, s1 = 0.f, s2 = 0.f, s3 = 0.f;
#pragma unroll
      for (int j = 0; j < 16; j++) { s0 += __uint_as_float(v[j].x); s1 += __uint_as_float(v[j].y); s2 += __uint_as_float(v[j].z); s3 += __uint_as_float(v[j].w); }
      if (w >= 3) {
        if (g == 2) st_ll(&g_z[(head * 2 + w - 3) * 4 + t], __float_as_uint(s0), __float_as_uint(s1), __float_as_uint(s2), __float_as_uint(s3), par);
        __syncwarp();
        hint_signal(&g_f_z[head]);
      }
      const int e0 = w < 3 ? g : 16 + g, e1 = w < 3 ? g + 8 : 16 + g, d0 = (w < 3 ? 8 * w : (w == 3 ? 0 : 16)) + 2 * t, d1 = w < 3 ? d0 : d0 + 8;
      __nv_bfloat16* T = reinterpret_cast<__nv_bfloat16*>(smem + SM_T) + hh * 32 * 40;
      if (e0 < 18) {
        T[d0 * 40 + e0] = __float2bfloat16(s0); T[(d0 + 1) * 40 + e0] = __float2bfloat16(s1);
        T[d1 * 40 + e1] = __float2bfloat16(s2); T[(d1 + 1) * 40 + e1] = __float2bfloat16(s3);
      }
    }
    __syncthreads();
    STAMPW(0, 2);
    mbar_wait(sbase + SM_HB, 0);
#pragma unroll 1
    for (int u = warp; u < 24; u += 12) {
      const int hh = u / 3, c0 = (u % 3) * 192;
      const uint32_t* T = reinterpret_cast<const uint32_t*>(smem + SM_T) + hh * 32 * 20 + g * 20 + t;
      const uint32_t a00 = T[0], a01 = T[160], a02 = T[4], a03 = T[164], a10 = T[8], a11 = T[168], b00 = T[320], b02 = T[324], b10 = T[328];
      const uint32_t rowa = sbase + (hh * 18 + (lane & 15)) * WP + (c0 + (lane >> 4) * 8) * 2, rowb = sbase + (hh * 18 + 16 + (lane & 7)) * WP + (c0 + ((lane >> 3) & 1) * 8) * 2;
#pragma unroll 3
      for (int j = 0; j < 12; j++) {
        uint32_t w0, w1, w2, w3, w4, w5;
        asm volatile("ldmatrix.sync.aligned.m8n8.x4.trans.shared.b16 {%0,%1,%2,%3}, [%4];" : "=r"(w0), "=r"(w1), "=r"(w2), "=r"(w3) : "r"(rowa + j * 32));
        asm volatile("ldmatrix.sync.aligned.m8n8.x2.trans.shared.b16 {%0,%1}, [%2];" : "=r"(w4), "=r"(w5) : "r"(rowb + j * 32));
        float p[4][4];
#pragma unroll
        for (int q = 0; q < 4; q++) p[q][0] = p[q][1] = p[q][2] = p[q][3] = 0.f;
        mma16816(p[0], a00, a01, a02, a03, w0, w1); mma16816(p[1], a00, a01, a02, a03, w2, w3);
        mma16816(p[2], b00, 0u, b02, 0u, w0, w1); mma16816(p[3], b00, 0u, b02, 0u, w2, w3);
        mma16816(p[0], a10, a11, 0u, 0u, w4, 0u); mma16816(p[1], a10, a11, 0u, 0u, w5, 0u);
        mma16816(p[2], b10, 0u, 0u, 0u, w4, 0u); mma16816(p[3], b10, 0u, 0u, 0u, w5, 0u);
        stsm4(rowa + j * 32, make_uint4(pack_bf16(p[0][0], p[0][1]), pack_bf16(p[0][2], p[0][3]), pack_bf16(p[1][0], p[1][1]), pack_bf16(p[1][2], p[1][3])));
        if (g < 2) {
          uint32_t* r = reinterpret_cast<uint32_t*>(smem + (hh * 18 + 16 + g) * WP + (c0 + j * 16 + 2 * t) * 2);
          r[0] = pack_bf16(p[2][0], p[2][1]); r[4] = pack_bf16(p[3][0], p[3][1]);
        }
      }
      asm volatile("fence.proxy.async.shared::cta;" ::: "memory");
      __syncwarp();
      if (lane < 18) {
        asm volatile("cp.async.bulk.global.shared::cta.bulk_group [%0], [%1], %2;" ::"l"(g_m + (a * 144 + hh * 18 + lane) * D_ + c0), "r"(sbase + (hh * 18 + lane) * WP + c0 * 2), "r"(384) : "memory");
        asm volatile("cp.async.bulk.commit_group;" ::: "memory");
      }
    }
    asm volatile("cp.async.bulk.wait_group 0;" ::: "memory");
    asm volatile("fence.proxy.async.global;" ::: "memory");
    __syncwarp();
    if (lane == 0) asm volatile("red.release.gpu.global.add.u32 [%0], 1;" ::"l"(g_f_m) : "memory");
    STAMPW(0, 3);
    __syncthreads();
    if (tid == 0) g_epoch[blockIdx.x] = ep;
    return;
  }

  const int cl = blockIdx.x >> 1, rank = blockIdx.x & 1;
  const int f = cl & 7, m = (cl >> 3) * 2 + rank;
  const int srole = f >= 6 ? 1 : 0;
  const uint32_t bar_full = sbase + SM_BAR, bar_empty = bar_full + 8 * NSTAGE, bar_xfree = bar_empty + 8 * NSTAGE, bar_ofull = bar_xfree + 72,
                 bar_d = bar_ofull + 72;

  if (tid == 0) {
#pragma unroll 1
    for (int i = 0; i < NSTAGE; i++) { mbar_init(bar_full + 8 * i, 1); mbar_init(bar_empty + 8 * i, 4); }
#pragma unroll 1
    for (int i = 0; i < 9; i++) { mbar_init(bar_xfree + 8 * i, 2); mbar_init(bar_ofull + 8 * i, 1); }
    mbar_init(bar_d, 1);
    asm volatile("fence.mbarrier_init.release.cluster;" ::: "memory");
  }
  __syncwarp();
  cluster_arrive_relaxed();

  if (warp >= 8) {
    const int srow = m * 128 + f * 16 + (warp - 8) * 4 + (lane >> 3);
    uint4 xs[9];
#pragma unroll
    for (int kb = 0; kb < 9; kb++) xs[kb] = __ldg(reinterpret_cast<const uint4*>(P.x + srow * D_) + (lane & 7) + kb * 8);
    auto stats = [&]() {
      const uint32_t* w = reinterpret_cast<const uint32_t*>(xs);
      float s0 = 0.f, s1 = 0.f;
#pragma unroll
      for (int i = 0; i < 36; i++) { s0 += bf_lo(w[i]); s1 += bf_hi(w[i]); }
      float sum = s0 + s1;
      sum += __shfl_xor_sync(0xffffffffu, sum, 1); sum += __shfl_xor_sync(0xffffffffu, sum, 2); sum += __shfl_xor_sync(0xffffffffu, sum, 4);
      const float mean = sum * (1.f / 576.f);
      s0 = 0.f; s1 = 0.f;
#pragma unroll
      for (int i = 0; i < 36; i++) { const float a = bf_lo(w[i]) - mean, b = bf_hi(w[i]) - mean; s0 = fmaf(a, a, s0); s1 = fmaf(b, b, s1); }
      float sq = s0 + s1;
      sq += __shfl_xor_sync(0xffffffffu, sq, 1); sq += __shfl_xor_sync(0xffffffffu, sq, 2); sq += __shfl_xor_sync(0xffffffffu, sq, 4);
      const float rstd = rsqrtf(sq * (1.f / 576.f) + 1e-5f);
      if ((lane & 7) == 0)
        st_ll64(&g_stat[srow], __float_as_uint(rstd), pack_bf16(-mean, -mean), par);
    };
    stats();
    asm volatile("setmaxnreg.dec.sync.aligned.u32 40;");
    cluster_wait();
    if (warp == 8) {
      if (lane == 0) {
        uint32_t stage = 0, phase = 1;
        const uint32_t sb = sbase + SM_B;
#pragma unroll 1
        for (int tl = 2 * srole; tl < 8 + 2 * srole; tl++) {
          const CUtensorMap* map = tl == 0 ? &P.tm_wqkv : (tl == 1 ? &P.tm_wqkv64 : (tl < 5 ? &P.tm_w1 : (tl < 8 ? &P.tm_w2 : (tl == 8 ? &P.tm_m : &P.tm_m64))));
          const int col = tl < 2 ? 288 * f + 192 * tl : (tl < 5 ? 576 * f + 192 * (tl - 2) : (tl < 8 ? 192 * ((tl - 5 + f) % 3) : (tl == 8 ? 192 * (f - 5) : 96 * (f - 6))));
          const bool perm = tl >= 5 && tl < 8;
          const bool z = (tl & 7) == 1;
          if (tl == 8) { flag_wait(g_f_m, 48 * ep); asm volatile("fence.proxy.async.global;" ::: "memory"); }
          const int cs = z ? 32 : 64, rs = z ? 64 : 32, nst = z ? 9 : 18;
#pragma unroll 1
          for (int st = 0; st < nst; st++) {
            int row = st * rs;
            if (perm) row += 576 * f + ((st < 6) ? 192 : (st < 12 ? -192 : 0));
            mbar_wait(bar_empty + 8 * stage, phase);
            mbar_expect(bar_full + 8 * stage, 12288);
            const uint32_t dst = sb + stage * STAGE_BYTES;
            if (((st ^ rank) & 1) == 0) {
              tma2d_mc(dst, map, col, row, bar_full + 8 * stage);
              tma2d_mc(dst + 8192, map, col + 2 * cs, row, bar_full + 8 * stage);
            } else {
              tma2d_mc(dst + 4096, map, col + cs, row, bar_full + 8 * stage);
            }
            if (++stage == NSTAGE) { stage = 0; phase ^= 1; }
          }
        }
      }
      __syncwarp();
    } else {
      const int aw = warp - 9;
      const int hi = f >> 2;
      if (aw == 0) {
        if (lane < 2) hint_wait(&g_f_qkv[m * 8 + 2 + 2 * lane + hi], 16 * ep, 200);
        __syncwarp();
        if (lane == 0) mbar_arrive(bar_d);
        STAMP(20);
      }
      if (lane < 5) hint_wait(lane < 4 ? &g_f_z[4 * f + lane] : &g_f_qkv[m * 8 + hi], lane < 4 ? 2 * ep : 16 * ep);
      __syncwarp();
      STAMPW(9, 22);
      uint32_t* stg = reinterpret_cast<uint32_t*>(smem + SM_SCR + aw * 2304);
#pragma unroll 1
      for (int u = aw * 2; u < 16; u += (u & 1) ? 5 : 1) {
        const int rbl = u >> 1, hp = (u & 1) * 2;
        const uint2* qf = g_qkv + (m * 8 + rbl) * 216 * 32;
        const uint2* zp = reinterpret_cast<const uint2*>(&g_z[(4 * f + hp) * 8 + t]);
        uint2 q[2][3];
        float d[4];
        int tries = 0;
        uint32_t bad;
#pragma unroll 1
        do {
          bad = tries ? ld_acquire(g_f_m) & 0u : 0u;
#pragma unroll
          for (int j = 0; j < 2; j++)
#pragma unroll
            for (int b = 0; b < 3; b++) q[j][b] = ld_ca64(qf + pairoff((4 * f + hp + j) * 9 + t, g) + 32 * b);
#pragma unroll
          for (int j = 0; j < 2; j++) {
            const uint2 z0 = ld_ca64(zp + 16 * j), z1 = ld_ca64(zp + 16 * j + 1), z2 = ld_ca64(zp + 16 * j + 8);
            if (t != 0) q[j][2] = make_uint2(par, 0u);
            ll_chk(bad, z0.x, z1.x, par); ll_chk(bad, z2.x, q[j][2].x, par); ll_chk(bad, q[j][0].x, q[j][1].x, par);
            d[2 * j] = bf_lo(q[j][0].x) * __uint_as_float(z0.x) + bf_hi(q[j][0].x) * __uint_as_float(z0.y) + bf_lo(q[j][1].x) * __uint_as_float(z1.x) + bf_hi(q[j][1].x) * __uint_as_float(z1.y) +
                       bf_lo(q[j][2].x) * __uint_as_float(z2.x) + bf_hi(q[j][2].x) * __uint_as_float(z2.y);
            d[2 * j + 1] = bf_lo(q[j][0].y) * __uint_as_float(z0.x) + bf_hi(q[j][0].y) * __uint_as_float(z0.y) + bf_lo(q[j][1].y) * __uint_as_float(z1.x) + bf_hi(q[j][1].y) * __uint_as_float(z1.y) +
                           bf_lo(q[j][2].y) * __uint_as_float(z2.x) + bf_hi(q[j][2].y) * __uint_as_float(z2.y);
          }
        } while (__any_sync(0xffffffffu, bad & 1) && ++tries < (1 << 20));
#pragma unroll
        for (int j = 0; j < 4; j++) d[j] += __shfl_xor_sync(0xffffffffu, d[j], 1);
#pragma unroll
        for (int j = 0; j < 4; j++) d[j] = rcpf(d[j] + __shfl_xor_sync(0xffffffffu, d[j], 2) + 1e-6f);
        if (hp == 0) { asm volatile("cp.async.bulk.wait_group.read 0;" ::: "memory"); __syncwarp(); }
#pragma unroll
        for (int j = 0; j < 2; j++) {
          const uint32_t r0 = pack_bf16(d[2 * j], d[2 * j]), r1 = pack_bf16(d[2 * j + 1], d[2 * j + 1]);
#pragma unroll
          for (int b = 0; b < 3; b++)
            if (b < 2 || t == 0) {
              stg[g * 36 + (hp + j) * 9 + 4 * b + t] = hfma2(q[j][b].x, r0, 0x80008000u);
              stg[(g + 8) * 36 + (hp + j) * 9 + 4 * b + t] = hfma2(q[j][b].y, r1, 0x80008000u);
            }
        }
        if (hp != 0) {
          asm volatile("fence.proxy.async.shared::cta;" ::: "memory");
          __syncwarp();
          if (lane == 0) {
            asm volatile("cp.async.bulk.tensor.2d.global.shared::cta.bulk_group [%0, {%2, %3}], [%1];" ::"l"(&P.tm_ast), "r"(smem_u32(stg)), "r"(72 * f), "r"(m * 128 + rbl * 16) : "memory");
            asm volatile("cp.async.bulk.commit_group;" ::: "memory");
          }
        }
      }
      asm volatile("cp.async.bulk.wait_group 0;" ::: "memory");
      asm volatile("fence.proxy.async.global;" ::: "memory");
      STAMPW(9, 26);
      asm volatile("bar.sync 5, 96;" ::: "memory");
      if (tid == 288) asm volatile("red.release.gpu.global.add.u32 [%0], 1;" ::"l"(&g_f_a[m]) : "memory");
      __syncwarp();
      STAMPW(9, 23);
      if (srole && aw == 2) {
        if (lane == 0) {
          flag_wait(&g_f_a[m], 8 * ep);
          asm volatile("fence.proxy.async.global;" ::: "memory");
#pragma unroll 1
          for (int kb = 0; kb < 9; kb++) {
            mbar_wait(bar_xfree + 8 * kb, 0);
            mbar_expect(bar_ofull + 8 * kb, 16384);
            tma2d(sbase + SM_A + kb * 16384, &P.tm_a, kb * 64, m * 128, bar_ofull + 8 * kb);
          }
        }
        __syncwarp();
      }
    }
    cluster_arrive_relaxed();
    cluster_wait();
  } else {
    const int wg = warp >> 2;
    {
      const int rs = lane >> 3, j = lane & 7;
      uint4 xv[4][9];
#pragma unroll
      for (int it = 0; it < 4; it++)
#pragma unroll
        for (int kb = 0; kb < 9; kb++) xv[it][kb] = __ldg(reinterpret_cast<const uint4*>(P.x + (m * 128 + warp * 16 + it * 4 + rs) * D_) + j + kb * 8);
      uint32_t bw0 = __ldg(reinterpret_cast<const uint32_t*>(P.b1 + 576 * f) + tid), bw1 = tid < 32 ? __ldg(reinterpret_cast<const uint32_t*>(P.b1 + 576 * f) + 256 + tid) : 0u;
      uint2 st[4];
      int tries = 0;
      uint32_t bad;
#pragma unroll 1
      do {
        bad = 0;
#pragma unroll
        for (int it = 0; it < 4; it++) st[it] = ld_ll64(&g_stat[m * 128 + warp * 16 + it * 4 + rs]);
        ll_chk(bad, st[0].x, st[1].x, par); ll_chk(bad, st[2].x, st[3].x, par);
      } while (__any_sync(0xffffffffu, bad & 1) && ++tries < (1 << 22));
      STAMPW(0, 19);
#pragma unroll
      for (int it = 0; it < 4; it++) {
        const uint32_t nm = st[it].y;
        uint8_t* dst = smem + SM_A + (warp * 16 + it * 4 + rs) * 128 + ((j ^ ((it * 4 + rs) & 7)) << 4);
#pragma unroll
        for (int kb = 0; kb < 9; kb++) {
          const uint4 w = xv[it][kb];
          *reinterpret_cast<uint4*>(dst + kb * 16384) = make_uint4(hadd2(w.x, nm), hadd2(w.y, nm), hadd2(w.z, nm), hadd2(w.w, nm));
        }
        if (j == 0) reinterpret_cast<uint32_t*>(smem + SM_RSTD)[warp * 16 + it * 4 + rs] = st[it].x;
      }
      reinterpret_cast<float2*>(smem + SM_BIAS)[tid] = make_float2(bf_lo(bw0) * GK, bf_hi(bw0) * GK);
      if (tid < 48) reinterpret_cast<float2*>(smem + SM_BIAS)[256 + tid] = make_float2(bf_lo(bw1) * GK, bf_hi(bw1) * GK);
      asm volatile("fence.proxy.async.shared::cta;" ::: "memory");
    }
    asm volatile("setmaxnreg.inc.sync.aligned.u32 232;");
    cluster_wait();
    asm volatile("bar.sync 1, 256;" ::: "memory");
    STAMPW(0, 1);
    Ctx c;
    c.full = bar_full;
    c.emb = __shfl_sync(0xffffffffu, mapa(bar_empty, (warp & 3) == 0 ? rank : (rank ^ 1)), 0);
    c.sig = lane == 0 && (warp & 3) < 2;
    c.stage = 0; c.phase = 0; c.prev = ~0u;
    c.dB = (((sbase + SM_B) & 0x3FFFF) >> 4) | ((4096u >> 4) << 16);
    c.dA = (((sbase + SM_A + wg * 8192) & 0x3FFFF) >> 4) | (1u << 16);
    const bool leader = (lane == 0) && ((warp & 3) == 0);

    const int rb = m * 8 + warp;
    const uint32_t bias_t = sbase + SM_BIAS + 8 * t;
    const uint32_t hst = sbase + SM_A + (warp * 16 + (lane & 7) + ((lane >> 3) & 1) * 8) * 128 + (((lane >> 4) ^ (lane & 7)) << 4);
    auto wg_sync = [&]() {
      asm volatile("fence.proxy.async.shared::cta;" ::: "memory");
      if (wg == 0) asm volatile("bar.sync 2, 128;" ::: "memory"); else asm volatile("bar.sync 3, 128;" ::: "memory");
    };
    float A[96], B[96];
#pragma unroll
    for (int i = 0; i < 96; i++) B[i] = 0.f;
#define EX1(ACC, U) case U: _Pragma("unroll") for (int q = 0; q < 8; q++) E[q] = fma_pack_v(&ACC[16 * U + 2 * q], (q & 1) ? r1 : r0, bs[q >> 1]); break;
#define EXTRACT(ACC) uint32_t E[8]; switch (u) { EX1(ACC, 0) EX1(ACC, 1) EX1(ACC, 2) EX1(ACC, 3) EX1(ACC, 4) default: EX1(ACC, 5) }
#define ST_PART(DST) { st_ll(DST, E[0], E[1], E[2], E[3], par); st_ll(DST + 32, E[4], E[5], E[6], E[7], par); }
#define ST_QKV(DST) { if (f < 4) { _Pragma("unroll") for (int q = 0; q < 8; q++) E[q] = phi2(E[q]); } \
    _Pragma("unroll") for (int q = 0; q < 4; q++) st_ll64(reinterpret_cast<uint2*>(DST) + 32 * q, E[2 * q], E[2 * q + 1], par); }
#define ST_SMEM(KB0) { const uint32_t ad = (hst ^ ((u & 1) << 6)) + (KB0 + (u >> 1)) * 16384; stsm4(ad, h0); stsm4(ad ^ 32, h1); }
#define LDS_R(SCALED, SC) float r0 = 1.f, r1 = 1.f; if (SCALED) { asm volatile("ld.shared.f32 %0, [%1];" : "=f"(r0) : "r"(rst)); asm volatile("ld.shared.f32 %0, [%1];" : "=f"(r1) : "r"(rst + 32)); r0 *= (SC); r1 *= (SC); }
    const uint32_t rst = sbase + SM_RSTD + (warp * 16 + g) * 4;
    const int fr = f % 3;
#pragma unroll 1
    for (int i = srole;; i++) {
      {
        const uint32_t ow = i == 4 ? bar_ofull : 0u;
        if (ow) mbar_wait(ow, 0);
        issue192(A, c, 0, true);
        const int ln = opaque(lane);
        uint4* dst = i == 1 ? reinterpret_cast<uint4*>(g_qkv + (rb * 216 + 36 * f + 24) * 32 + ln) : g_part + ((rb * 8 + f) * 36 + 12 * (i == 3 ? fr : (fr + 2) % 3)) * 32 + ln;
        LDS_R(i <= 2, i == 2 ? GK : 1.f)
        retire(c);
        if (ow && leader) mbar_arrive(bar_xfree + 64);
        fence_regs<96>(B);
        int s = 1;
        if (i == 2) {
#pragma unroll 1
          for (; s < 3; s++) { issue192(A, c, s); retire(c); }
        }
        const int nu = i == srole ? 0 : (i == 1 ? 3 : 6);
#pragma unroll 1
        for (int u = 0; u < nu; u++, s++) {
          float2 bs[4];
          lds_bias(bs, bias_t + (i == 2 ? 192 + 32 * u : 576) * 4);
          if (ow && !(s & 1)) mbar_wait(ow + 4 * s, 0);
          issue192(A, c, s);
          EXTRACT(B)
          if (i == 2) {
            const uint4 h0 = gelu_group(E), h1 = gelu_group(E + 4);
            ST_SMEM(0)
          } else if (i == 1) ST_QKV(dst)
          else ST_PART(dst)
          dst += 64;
          retire(c);
        }
        if (nu == 3) hint_signal(&g_f_qkv[m * 8 + f]);
        const bool d1 = i == 1 + srole;
        const int send = d1 ? 10 : 15;
#pragma unroll 1
        for (; s < send; s++) {
          if (ow && !(s & 1)) mbar_wait(ow + 4 * s, 0);
          issue192(A, c, s);
          retire(c);
        }
        uint32_t W[48];
        if (d1) {
          const int head = 4 * f + (warp >> 1), rb0 = m * 8 + (warp & 1) * 4;
          issue192(A, c, 10);
          mbar_wait(bar_d, 0);
          d1_load<false>(W, rb0, head, opaque(lane));
          retire(c);
#pragma unroll 1
          for (s = 11; s < 13; s++) { issue192(A, c, s); retire(c); }
          issue192(A, c, 13);
          int tries = 0;
#pragma unroll 1
          while (d1_bad(W, t, par) && ++tries < (1 << 20)) d1_load<true>(W, rb0, head, opaque(lane));
          d1_mov(W, 0, t); d1_mov(W, 1, t);
          retire(c);
          issue192(A, c, 14);
          d1_mov(W, 2, t); d1_mov(W, 3, t);
          wg_wait<0>();
          asm volatile("bar.sync 4, 256;" ::: "memory");
          float R[18];
          d1_mma(W, R);
          float2* xch = reinterpret_cast<float2*>(smem + SM_SCR + (warp >> 1) * 1792) + opaque(lane);
          if (warp & 1) {
#pragma unroll
            for (int q = 0; q < 6; q++) xch[q * 32] = make_float2(R[2 * q], R[2 * q + 1]);
            if (lane < 12) { xch[192] = make_float2(R[12], R[13]); xch[204] = make_float2(R[14], R[15]); if (t == 0) xch[216 - lane + g] = make_float2(R[16], R[17]); }
          } else if (R[17] == 1.2345e-30f) R[16] = 0.f;
          asm volatile("bar.sync 4, 256;" ::: "memory");
          retire(c);
          issue192(A, c, 15);
          if (!(warp & 1)) {
            const int l2 = opaque(lane);
#pragma unroll
            for (int q = 0; q < 6; q++) { const float2 o = xch[q * 32]; R[2 * q] += o.x; R[2 * q + 1] += o.y; }
            if (l2 < 12) {
              const float2 o0 = xch[192], o1 = xch[204], o2 = xch[216 - l2 + (l2 >> 2)];
              R[12] += o0.x; R[13] += o0.y; R[14] += o1.x; R[15] += o1.y; R[16] += o2.x; R[17] += o2.y;
            }
            uint4* dkv = &g_kvp[(head * 80 + m) * 32 + l2];
#pragma unroll
            for (int w = 0; w < 5; w++)
              if (kv_valid(w, l2)) st_ll(dkv + w * 512, __float_as_uint(R[4 * w]), __float_as_uint(R[4 * w + 1]), w < 4 ? __float_as_uint(R[4 * w + 2]) : 0u, w < 4 ? __float_as_uint(R[4 * w + 3]) : 0u, par);
            __syncwarp();
            hint_signal(&g_f_kvp[head]);
          }
          STAMPW(0, 21);
        } else issue192(A, c, 15);
        if (i == 2) {
          const uint4* hsp = g_hsp + (blockIdx.x * 8 + warp) * 12 * 32 + opaque(lane);
#pragma unroll
          for (int q = 0; q < 12; q++) { const uint4 v = ldcg128(hsp + q * 32); W[4 * q] = v.x; W[4 * q + 1] = v.y; W[4 * q + 2] = v.z; W[4 * q + 3] = v.w; }
        } else {
#pragma unroll
          for (int q = 0; q < 48; q++) W[q] = 0;
        }
        retire(c);
        if (ow) mbar_wait(ow + 64, 0);
        issue192(A, c, 16);
        if (i == 2) wg_sync();
        retire(c);
        issue192(A, c, 17);
        if (i == 2) {
#pragma unroll
          for (int q = 0; q < 12; q++) stsm4((hst ^ ((q & 3) << 5)) + (3 + (q >> 2)) * 16384, make_uint4(W[4 * q], W[4 * q + 1], W[4 * q + 2], W[4 * q + 3]));
        }
        retire(c);
      }
      STAMPW(0, 2 + 2 * i);
      if ((i & 3) == 0) {
        issue96(B, c, 0, true);
        const int ln = opaque(lane);
        uint4* dst = i == 0 ? reinterpret_cast<uint4*>(g_qkv + (rb * 216 + 36 * f) * 32 + ln) : g_s + (rb * 36 + 12 * (f - 5)) * 32 + ln;
        LDS_R(i == 0, 1.f)
        const float2 bs[4] = {{0.f, 0.f}, {0.f, 0.f}, {0.f, 0.f}, {0.f, 0.f}};
        retire(c);
        fence_regs<96>(A);
#pragma unroll 1
        for (int u = 0; u < 7; u++) {
          issue96(B, c, u + 1, false);
          if (u < 6) {
            EXTRACT(A)
            if (i == 0) ST_QKV(dst)
            else ST_PART(dst)
            dst += 64;
          } else if (i == 0) hint_signal(&g_f_qkv[m * 8 + f]);
          retire(c);
        }
        issue96(B, c, 8, false);
        retire(c);
        if (i == 4) {
          STAMPW(0, 11);
          wg_wait<0>();
          c.release_prev();
          fence_regs<48>(B);
          part_groups<0, 6>(B, g_s + (rb * 36 + 6 * (f - 6)) * 32 + opaque(lane), par);
          break;
        }
      } else {
        issue192(B, c, 0, true);
        const int ln = opaque(lane);
        uint4* dst = i == 1 ? g_hsp + (blockIdx.x * 8 + warp) * 12 * 32 + ln : g_part + ((rb * 8 + f) * 36 + 12 * ((fr + 1) % 3)) * 32 + ln;
        const bool xf = i == 3 && srole && leader;
        LDS_R(i != 3, GK)
        retire(c);
        fence_regs<96>(A);
#pragma unroll 1
        for (int u = 0; u < 6; u++) {
          float2 bs[4];
          lds_bias(bs, bias_t + (i == 3 ? 576 : (i == 1 ? 0 : 384) + 32 * u) * 4);
          issue192(B, c, u + 1);
          EXTRACT(A)
          if (i != 3) {
            const uint4 h0 = gelu_group(E), h1 = gelu_group(E + 4);
            if (i == 1) { dst[0] = h0; dst[32] = h1; }
            else {
              ST_SMEM(6)
              if (u == 3) wg_sync();
            }
          } else ST_PART(dst)
          dst += 64;
          retire(c);
          if ((u & 1) && xf) mbar_arrive(bar_xfree + 4 * u - 4);
        }
        if (i == 3 && !srole) {
          const int c2 = (fr + 2) % 3, v0 = 12 * c2 + (f < 3 ? 0 : 6), fo = f < 3 ? f + 3 : f - 3;
          const int l2 = opaque(lane);
          const uint4* pb = g_part + (rb * 8 * 36 + v0) * 32 + l2;
          uint4 p[12];
          uint32_t S[24];
#pragma unroll
          for (int q = 0; q < 24; q++) S[q] = 0u;
          auto ldp = [&](const uint4* a0, const uint4* a1) {
#pragma unroll
            for (int q = 0; q < 6; q++) { p[q] = ld_ll(a0 + q * 32); p[6 + q] = ld_ll(a1 + q * 32); }
          };
          auto badp = [&]() {
            uint32_t bad = 0;
#pragma unroll
            for (int q = 0; q < 12; q++) ll_chk(bad, p[q].x, p[q].z, par);
            return __any_sync(0xffffffffu, bad & 1);
          };
#pragma unroll 1
          for (int w = 0; w < 3; w++) {
            const uint4* a0 = pb + (w == 0 ? c2 : (w == 1 ? 6 : (fr + 1) % 3)) * 36 * 32;
            const uint4* a1 = a0 + (w == 1 ? 1 : 3) * 36 * 32;
            issue192(B, c, 7 + 3 * w);
            ldp(a0, a1);
            retire(c);
            issue192(B, c, 8 + 3 * w);
            retire(c);
            issue192(B, c, 9 + 3 * w);
            int tries = 0;
#pragma unroll 1
            while (badp() && ++tries < (1 << 20)) ldp(a0, a1);
#pragma unroll
            for (int q = 0; q < 24; q++) S[q] = hadd2(S[q], hadd2(reinterpret_cast<const uint32_t*>(p)[q], reinterpret_cast<const uint32_t*>(p)[24 + q]));
            retire(c);
          }
          const int ro = (rb * 16 + (l2 >> 2)) * D_ + 2 * (l2 & 3) + 16 * v0;
          uint32_t xx[24], bb[12];
          issue192(B, c, 16);
#pragma unroll
          for (int j = 0; j < 12; j++) {
            xx[2 * j] = __ldg(reinterpret_cast<const uint32_t*>(P.x + ro + 8 * j));
            xx[2 * j + 1] = __ldg(reinterpret_cast<const uint32_t*>(P.x + ro + 8 * D_ + 8 * j));
            bb[j] = __ldg(reinterpret_cast<const uint32_t*>(P.b2 + 16 * v0 + 8 * j + 2 * (l2 & 3)));
          }
          retire(c);
          issue192(B, c, 17);
          retire(c);
          STAMPW(0, 9);
          wg_wait<0>();
          c.release_prev();
          fence_regs<96>(B);
          uint4* snd = g_part + ((rb * 8 + f) * 36 + 12 * c2 + (f < 3 ? 6 : 0)) * 32 + l2;
          if (f < 3) part_groups<0, 6>(B + 48, snd, par);
          else {
            part_groups<0, 6>(B, snd, par);
#pragma unroll
            for (int q = 0; q < 48; q++) B[q] = B[48 + q];
          }
          STAMPW(0, 12);
#pragma unroll
          for (int q = 0; q < 24; q++) {
            B[2 * q] = fmaf(B[2 * q] + bf_lo(S[q]), 0.25f / GK, 0.5f * bf_lo(bb[q >> 1])); B[2 * q + 1] = fmaf(B[2 * q + 1] + bf_hi(S[q]), 0.25f / GK, 0.5f * bf_hi(bb[q >> 1]));
          }
          int tries = 0;
#pragma unroll 1
          do { ldp(pb + fo * 36 * 32, g_s + (rb * 36 + v0) * 32 + l2); } while (badp() && ++tries < (1 << 20));
          STAMPW(0, 14);
#pragma unroll
          for (int q = 0; q < 24; q++) {
            const uint32_t w = reinterpret_cast<const uint32_t*>(p)[q];
            const uint32_t gt = pack_bf16(silu_h(fmaf(bf_lo(w), 0.25f / GK, B[2 * q])), silu_h(fmaf(bf_hi(w), 0.25f / GK, B[2 * q + 1])));
            *reinterpret_cast<uint32_t*>(P.out + ro + (q & 1) * 8 * D_ + 8 * (q >> 1)) = hfma2(reinterpret_cast<const uint32_t*>(p)[24 + q], gt, xx[q]);
          }
          break;
        }
#pragma unroll 1
        for (int s = 7; s < 17; s++) {
          issue192(B, c, s);
          if (s == 9 && i == 2) wg_sync();
          retire(c);
          if ((s & 1) == 0 && xf) mbar_arrive(bar_xfree + 4 * s - 8);
        }
        issue192(B, c, 17);
        retire(c);
      }
      STAMPW(0, 3 + 2 * i);
    }
    STAMPW(0, 15);
    cluster_arrive_relaxed();
    cluster_wait();
    STAMPW(0, 16);
    if (tid == 0) g_epoch[blockIdx.x] = ep;
  }
}

typedef CUresult (*EncFn)(CUtensorMap*, CUtensorMapDataType, cuuint32_t, void*, const cuuint64_t*, const cuuint64_t*, const cuuint32_t*, const cuuint32_t*,
                          CUtensorMapInterleave, CUtensorMapSwizzle, CUtensorMapL2promotion, CUtensorMapFloatOOBfill);

void make_map(EncFn enc, CUtensorMap* tm, const void* ptr, int rows, int cols, int box_rows, int mode = 0) {
  cuuint64_t gd[2] = {(cuuint64_t)cols, (cuuint64_t)rows};
  cuuint64_t gs[1] = {(cuuint64_t)cols * 2};
  cuuint32_t bx[2] = {mode == 1 ? 32u : (mode == 2 ? 72u : 64u), (cuuint32_t)box_rows};
  cuuint32_t es[2] = {1, 1};
  enc(tm, CU_TENSOR_MAP_DATA_TYPE_BFLOAT16, 2, const_cast<void*>(ptr), gd, gs, bx, es, CU_TENSOR_MAP_INTERLEAVE_NONE, mode == 1 ? CU_TENSOR_MAP_SWIZZLE_64B : (mode == 2 ? CU_TENSOR_MAP_SWIZZLE_NONE : CU_TENSOR_MAP_SWIZZLE_128B),
      CU_TENSOR_MAP_L2_PROMOTION_L2_256B, CU_TENSOR_MAP_FLOAT_OOB_FILL_NONE);
}

}

extern "C" void kernel_launch(void* const* d_in, const int* in_sizes, int n_in, void* d_out, int out_size) {
  (void)in_sizes; (void)n_in; (void)out_size;
  static EncFn enc = nullptr;
  static void *a_ptr = nullptr, *m_ptr = nullptr;
  if (!enc) {
    void* fn = nullptr; cudaDriverEntryPointQueryResult q;
    cudaGetDriverEntryPoint("cuTensorMapEncodeTiled", &fn, cudaEnableDefault, &q);
    enc = (EncFn)fn;
    cudaFuncSetAttribute(fused_kernel, cudaFuncAttributeMaxDynamicSharedMemorySize, SMEM_BYTES);
    cudaGetSymbolAddress(&a_ptr, g_a);
    cudaGetSymbolAddress(&m_ptr, g_m);
  }
  Params P;
  P.x = (const __nv_bfloat16*)d_in[0];
  P.wqkv = (const __nv_bfloat16*)d_in[1];
  P.wo = (const __nv_bfloat16*)d_in[2];
  P.w1 = (const __nv_bfloat16*)d_in[4];
  P.b1 = (const __nv_bfloat16*)d_in[5];
  P.w2 = (const __nv_bfloat16*)d_in[6];
  P.b2 = (const __nv_bfloat16*)d_in[7];
  P.out = (__nv_bfloat16*)d_out;
  make_map(enc, &P.tm_wqkv, P.wqkv, D_, Q3_, 32);
  make_map(enc, &P.tm_w1, P.w1, D_, F_, 32);
  make_map(enc, &P.tm_w2, P.w2, F_, D_, 32);
  make_map(enc, &P.tm_m, m_ptr, D_, D_, 32);
  make_map(enc, &P.tm_wqkv64, P.wqkv, D_, Q3_, 64, 1);
  make_map(enc, &P.tm_m64, m_ptr, D_, D_, 64, 1);
  make_map(enc, &P.tm_a, a_ptr, S_, D_, 128);
  make_map(enc, &P.tm_ast, a_ptr, S_, D_, 16, 2);
  fused_kernel<<<NCTAS, NTHREADS, SMEM_BYTES, cudaStreamPerThread>>>(P);
}
```

```cpp
#include <cuda_runtime.h>
#include <cuda.h>
#include <cuda_bf16.h>
#include <stdint.h>

namespace {

constexpr int S_ = 2048, D_ = 576, F_ = 4608, Q3_ = 1728;
constexpr int NSTAGE = 6, STAGE_BYTES = 12288;
constexpr int SM_A = 0, SM_B = 147456, SM_BIAS = SM_B + NSTAGE * STAGE_BYTES, SM_RSTD = SM_BIAS + 2304 + 128, SM_SCR = SM_RSTD + 512, SM_BAR = SM_SCR + 7168;
constexpr int SMEM_BYTES = SM_BAR + 320;
constexpr int NTHREADS = 384;
constexpr int NCTAS = 132;

__device__ uint2 g_qkv[(128 * 216 + 2) * 32];
__device__ __align__(1024) __nv_bfloat16 g_a[S_ * D_];
__device__ __align__(1024) __nv_bfloat16 g_m[D_ * D_];
__device__ uint4 g_kvp[32 * 5 * 16 * 32];
__device__ uint4 g_z[32 * 2 * 4];
__device__ uint4 g_part[128 * 8 * 36 * 32];
__device__ uint4 g_s[128 * 36 * 32];
__device__ uint4 g_hsp[128 * 12 * 256];
__device__ uint32_t g_f_qkv[16 * 8];
__device__ uint32_t g_f_kvp[32];
__device__ uint32_t g_f_z[32];
__device__ uint32_t g_f_a[16];
__device__ uint32_t g_f_m[1];
__device__ uint2 g_stat[S_];
__device__ uint32_t g_epoch[NCTAS];

#define STAMP(i)
#define STAMPW(w, i)
#define WSTAMP(i)
__device__ __forceinline__ uint32_t smem_u32(const void* p) { return (uint32_t)__cvta_generic_to_shared(p); }
__device__ __forceinline__ void mbar_init(uint32_t a, int c) { asm volatile("mbarrier.init.shared::cta.b64 [%0], %1;" ::"r"(a), "r"(c)); }
__device__ __forceinline__ void mbar_expect(uint32_t a, uint32_t b) { asm volatile("mbarrier.arrive.expect_tx.shared::cta.b64 _, [%0], %1;" ::"r"(a), "r"(b) : "memory"); }
__device__ __forceinline__ void mbar_arrive(uint32_t a) { asm volatile("mbarrier.arrive.shared::cta.b64 _, [%0];" ::"r"(a) : "memory"); }
__device__ __forceinline__ void mbar_arrive_cl(uint32_t a) { asm volatile("mbarrier.arrive.shared::cluster.b64 _, [%0];" ::"r"(a) : "memory"); }
__device__ __forceinline__ uint32_t mapa(uint32_t a, uint32_t cta) { uint32_t r; asm volatile("mapa.shared::cluster.u32 %0, %1, %2;" : "=r"(r) : "r"(a), "r"(cta)); return r; }
__device__ __forceinline__ void mbar_wait(uint32_t a, uint32_t ph) {
  uint32_t ok; int it = 0;
#pragma unroll 1
  do {
    asm volatile("{.reg .pred p; mbarrier.try_wait.parity.shared::cta.b64 p, [%1], %2; selp.u32 %0,1,0,p;}" : "=r"(ok) : "r"(a), "r"(ph) : "memory");
  } while (!ok && ++it < (1 << 18));
}
__device__ __forceinline__ void tma2d(uint32_t dst, const CUtensorMap* m, int c0, int c1, uint32_t bar) {
  asm volatile("cp.async.bulk.tensor.2d.shared::cluster.global.mbarrier::complete_tx::bytes [%0], [%1, {%3,%4}], [%2];" ::"r"(dst), "l"(m), "r"(bar), "r"(c0), "r"(c1) : "memory");
}
__device__ __forceinline__ void tma2d_mc(uint32_t dst, const CUtensorMap* m, int c0, int c1, uint32_t bar) {
  asm volatile("cp.async.bulk.tensor.2d.shared::cluster.global.mbarrier::complete_tx::bytes.multicast::cluster [%0], [%1, {%3,%4}], [%2], %5;" ::"r"(dst), "l"(m), "r"(bar), "r"(c0), "r"(c1), "h"((uint16_t)3) : "memory");
}
__device__ __forceinline__ void cluster_arrive_relaxed() { asm volatile("barrier.cluster.arrive.relaxed.aligned;" ::: "memory"); }
__device__ __forceinline__ void cluster_wait() { asm volatile("barrier.cluster.wait.acquire.aligned;" ::: "memory"); }
__device__ __forceinline__ void wg_fence() { asm volatile("wgmma.fence.sync.aligned;" ::: "memory"); }
__device__ __forceinline__ void wg_commit() { asm volatile("wgmma.commit_group.sync.aligned;" ::: "memory"); }
template <int n> __device__ __forceinline__ void wg_wait() { asm volatile("wgmma.wait_group.sync.aligned %0;" ::"n"(n) : "memory"); }
__device__ __forceinline__ uint32_t ld_acquire(const uint32_t* p) { uint32_t v; asm volatile("ld.acquire.gpu.global.u32 %0, [%1];" : "=r"(v) : "l"(p) : "memory"); return v; }
__device__ __forceinline__ void flag_wait(const uint32_t* p, uint32_t target) {
  int it = 0;
#pragma unroll 1
  while ((int)(ld_acquire(p) - target) < 0 && ++it < (1 << 20)) __nanosleep(300);
}
__device__ __forceinline__ void hint_signal(uint32_t* p) {
  if ((threadIdx.x & 31) == 0) asm volatile("red.relaxed.gpu.global.add.u32 [%0], 1;" ::"l"(p) : "memory");
}
__device__ __forceinline__ void hint_wait(const uint32_t* p, uint32_t target, uint32_t ns = 400) {
  int it = 0; uint32_t v;
#pragma unroll 1
  do { asm volatile("ld.relaxed.gpu.global.u32 %0, [%1];" : "=r"(v) : "l"(p) : "memory"); if ((int)(v - target) >= 0) break; __nanosleep(ns); } while (++it < (1 << 20));
}
__device__ __forceinline__ uint32_t tag(uint32_t x, uint32_t par) { uint32_t r; asm("lop3.b32 %0, %1, 0xfffffffe, %2, 0xea;" : "=r"(r) : "r"(x), "r"(par)); return r; }
__device__ __forceinline__ void st_ll(uint4* p, uint32_t x, uint32_t y, uint32_t z, uint32_t w, uint32_t par) {
  asm volatile("{.reg .b64 a, b; mov.b64 a, {%1,%2}; mov.b64 b, {%3,%4}; st.relaxed.gpu.global.v2.b64 [%0], {a, b};}"
               ::"l"(p), "r"(tag(x, par)), "r"(y), "r"(tag(z, par)), "r"(w) : "memory");
}
__device__ __forceinline__ uint4 ld_ll(const uint4* p) {
  uint4 v;
  asm volatile("{.reg .b64 a, b; ld.relaxed.gpu.global.v2.b64 {a, b}, [%4]; mov.b64 {%0,%1}, a; mov.b64 {%2,%3}, b;}"
               : "=r"(v.x), "=r"(v.y), "=r"(v.z), "=r"(v.w) : "l"(p) : "memory");
  return v;
}
__device__ __forceinline__ void st_ll64(uint2* p, uint32_t x, uint32_t y, uint32_t par) {
  asm volatile("{.reg .b64 a; mov.b64 a, {%1,%2}; st.relaxed.gpu.global.b64 [%0], a;}" ::"l"(p), "r"(tag(x, par)), "r"(y) : "memory");
}
__device__ __forceinline__ uint2 ld_ca64(const void* p) {
  uint2 v;
  asm volatile("{.reg .b64 a; ld.global.ca.b64 a, [%2]; mov.b64 {%0,%1}, a;}" : "=r"(v.x), "=r"(v.y) : "l"(p) : "memory");
  return v;
}
__device__ __forceinline__ uint2 ld_ll64(const void* p) {
  uint2 v;
  asm volatile("{.reg .b64 a; ld.relaxed.gpu.global.b64 a, [%2]; mov.b64 {%0,%1}, a;}" : "=r"(v.x), "=r"(v.y) : "l"(p) : "memory");
  return v;
}
__device__ __forceinline__ void ll_chk(uint32_t& bad, uint32_t a, uint32_t b, uint32_t par) {
  uint32_t u; asm("lop3.b32 %0, %1, %2, %3, 0x7e;" : "=r"(u) : "r"(a), "r"(b), "r"(par));
  asm("or.b32 %0, %0, %1;" : "+r"(bad) : "r"(u));
}
__device__ __forceinline__ uint32_t hadd2(uint32_t a, uint32_t b) { uint32_t d; asm("add.rn.bf16x2 %0, %1, %2;" : "=r"(d) : "r"(a), "r"(b)); return d; }
__device__ __forceinline__ uint32_t hfma2(uint32_t a, uint32_t b, uint32_t c) { uint32_t d; asm("fma.rn.bf16x2 %0, %1, %2, %3;" : "=r"(d) : "r"(a), "r"(b), "r"(c)); return d; }
__device__ __forceinline__ uint32_t pack_bf16(float lo, float hi) { uint32_t r; asm("cvt.rn.bf16x2.f32 %0, %1, %2;" : "=r"(r) : "f"(hi), "f"(lo)); return r; }
__device__ __forceinline__ float bf_lo(uint32_t v) { return __uint_as_float(v << 16); }
__device__ __forceinline__ float bf_hi(uint32_t v) { return __uint_as_float(v & 0xffff0000u); }
__device__ __forceinline__ uint32_t movmat(uint32_t a) { uint32_t d; asm volatile("movmatrix.sync.aligned.m8n8.trans.b16 %0, %1;" : "=r"(d) : "r"(a)); return d; }
__device__ __forceinline__ void mma16816(float* c, uint32_t a0, uint32_t a1, uint32_t a2, uint32_t a3, uint32_t b0, uint32_t b1) {
  asm volatile("mma.sync.aligned.m16n8k16.row.col.f32.bf16.bf16.f32 {%0,%1,%2,%3}, {%4,%5,%6,%7}, {%8,%9}, {%0,%1,%2,%3};"
               : "+f"(c[0]), "+f"(c[1]), "+f"(c[2]), "+f"(c[3]) : "r"(a0), "r"(a1), "r"(a2), "r"(a3), "r"(b0), "r"(b1));
}
__device__ __forceinline__ uint4 ldcg128(const void* p) { uint4 v; asm volatile("ld.global.cg.v4.u32 {%0,%1,%2,%3}, [%4];" : "=r"(v.x), "=r"(v.y), "=r"(v.z), "=r"(v.w) : "l"(p) : "memory"); return v; }

template <int N> __device__ __forceinline__ void wgmma_ss(float* d, uint64_t da, uint64_t db, int sc);
template <int N> __device__ __forceinline__ void wgmma_rs(float* d, const uint32_t* a, uint64_t db, int sc);
template <> __device__ __forceinline__ void wgmma_ss<96>(float* d, uint64_t da, uint64_t db, int sc) {
  asm volatile("{.reg .pred p; setp.ne.b32 p, %50, 0; wgmma.mma_async.sync.aligned.m64n96k16.f32.bf16.bf16 {%0, %1, %2, %3, %4, %5, %6, %7, %8, %9, %10, %11, %12, %13, %14, %15, %16, %17, %18, %19, %20, %21, %22, %23, %24, %25, %26, %27, %28, %29, %30, %31, %32, %33, %34, %35, %36, %37, %38, %39, %40, %41, %42, %43, %44, %45, %46, %47}, %48, %49, p, 1, 1, 0, 1;}"
   : "+f"(d[0]), "+f"(d[1]), "+f"(d[2]), "+f"(d[3]), "+f"(d[4]), "+f"(d[5]), "+f"(d[6]), "+f"(d[7]), "+f"(d[8]), "+f"(d[9]), "+f"(d[10]), "+f"(d[11]), "+f"(d[12]), "+f"(d[13]), "+f"(d[14]), "+f"(d[15]), "+f"(d[16]), "+f"(d[17]), "+f"(d[18]), "+f"(d[19]), "+f"(d[20]), "+f"(d[21]), "+f"(d[22]), "+f"(d[23]), "+f"(d[24]), "+f"(d[25]), "+f"(d[26]), "+f"(d[27]), "+f"(d[28]), "+f"(d[29]), "+f"(d[30]), "+f"(d[31]), "+f"(d[32]), "+f"(d[33]), "+f"(d[34]), "+f"(d[35]), "+f"(d[36]), "+f"(d[37]), "+f"(d[38]), "+f"(d[39]), "+f"(d[40]), "+f"(d[41]), "+f"(d[42]), "+f"(d[43]), "+f"(d[44]), "+f"(d[45]), "+f"(d[46]), "+f"(d[47]) : "l"(da), "l"(db), "r"(sc));
}
template <> __device__ __forceinline__ void wgmma_ss<192>(float* d, uint64_t da, uint64_t db, int sc) {
  asm volatile("{.reg .pred p; setp.ne.b32 p, %98, 0; wgmma.mma_async.sync.aligned.m64n192k16.f32.bf16.bf16 {%0, %1, %2, %3, %4, %5, %6, %7, %8, %9, %10, %11, %12, %13, %14, %15, %16, %17, %18, %19, %20, %21, %22, %23, %24, %25, %26, %27, %28, %29, %30, %31, %32, %33, %34, %35, %36, %37, %38, %39, %40, %41, %42, %43, %44, %45, %46, %47, %48, %49, %50, %51, %52, %53, %54, %55, %56, %57, %58, %59, %60, %61, %62, %63, %64, %65, %66, %67, %68, %69, %70, %71, %72, %73, %74, %75, %76, %77, %78, %79, %80, %81, %82, %83, %84, %85, %86, %87, %88, %89, %90, %91, %92, %93, %94, %95}, %96, %97, p, 1, 1, 0, 1;}"
   : "+f"(d[0]), "+f"(d[1]), "+f"(d[2]), "+f"(d[3]), "+f"(d[4]), "+f"(d[5]), "+f"(d[6]), "+f"(d[7]), "+f"(d[8]), "+f"(d[9]), "+f"(d[10]), "+f"(d[11]), "+f"(d[12]), "+f"(d[13]), "+f"(d[14]), "+f"(d[15]), "+f"(d[16]), "+f"(d[17]), "+f"(d[18]), "+f"(d[19]), "+f"(d[20]), "+f"(d[21]), "+f"(d[22]), "+f"(d[23]), "+f"(d[24]), "+f"(d[25]), "+f"(d[26]), "+f"(d[27]), "+f"(d[28]), "+f"(d[29]), "+f"(d[30]), "+f"(d[31]), "+f"(d[32]), "+f"(d[33]), "+f"(d[34]), "+f"(d[35]), "+f"(d[36]), "+f"(d[37]), "+f"(d[38]), "+f"(d[39]), "+f"(d[40]), "+f"(d[41]), "+f"(d[42]), "+f"(d[43]), "+f"(d[44]), "+f"(d[45]), "+f"(d[46]), "+f"(d[47]), "+f"(d[48]), "+f"(d[49]), "+f"(d[50]), "+f"(d[51]), "+f"(d[52]), "+f"(d[53]), "+f"(d[54]), "+f"(d[55]), "+f"(d[56]), "+f"(d[57]), "+f"(d[58]), "+f"(d[59]), "+f"(d[60]), "+f"(d[61]), "+f"(d[62]), "+f"(d[63]), "+f"(d[64]), "+f"(d[65]), "+f"(d[66]), "+f"(d[67]), "+f"(d[68]), "+f"(d[69]), "+f"(d[70]), "+f"(d[71]), "+f"(d[72]), "+f"(d[73]), "+f"(d[74]), "+f"(d[75]), "+f"(d[76]), "+f"(d[77]), "+f"(d[78]), "+f"(d[79]), "+f"(d[80]), "+f"(d[81]), "+f"(d[82]), "+f"(d[83]), "+f"(d[84]), "+f"(d[85]), "+f"(d[86]), "+f"(d[87]), "+f"(d[88]), "+f"(d[89]), "+f"(d[90]), "+f"(d[91]), "+f"(d[92]), "+f"(d[93]), "+f"(d[94]), "+f"(d[95]) : "l"(da), "l"(db), "r"(sc));
}

__device__ __forceinline__ uint64_t desc64(uint32_t lo, uint32_t hi) { uint64_t d; asm("mov.b64 %0, {%1, %2};" : "=l"(d) : "r"(lo), "r"(hi)); return d; }
constexpr uint32_t DESC_HI = (1024u >> 4) | (1u << 30);
constexpr uint32_t DESC_HI64 = (512u >> 4) | (2u << 30);
template <int n> __device__ __forceinline__ void fence_regs(float* a) {
#pragma unroll
  for (int i = 0; i < n; i++) asm volatile("" : "+f"(a[i])::"memory");
}

struct Ctx {
  uint32_t full;
  uint32_t emb;
  bool sig;
  uint32_t stage, phase, prev;
  uint32_t dB, dA;
  __device__ __forceinline__ void release_prev() { if (sig && prev != ~0u) mbar_arrive_cl(emb + prev); }
  __device__ __forceinline__ void wait_full() {
    mbar_wait(full + 8 * stage, phase);
    wg_fence();
  }
};

__device__ __forceinline__ void issue192(float* acc, Ctx& c, int s, bool first = false) {
  c.wait_full();
  const uint32_t db = c.dB + c.stage * (STAGE_BYTES >> 4);
  const uint32_t da = c.dA + (s >> 1) * 1024 + (s & 1) * 4;
  wgmma_ss<192>(acc, desc64(da, DESC_HI), desc64(db, DESC_HI), first ? 0 : 1);
  wgmma_ss<192>(acc, desc64(da + 2, DESC_HI), desc64(db + 128, DESC_HI), 1);
  wg_commit();
}
__device__ __forceinline__ void issue96(float* acc, Ctx& c, int s, bool first) {
  c.wait_full();
  const uint32_t db = c.dB + c.stage * (STAGE_BYTES >> 4);
  const uint32_t da = c.dA + s * 1024;
  if (first) { wgmma_ss<192>(acc, desc64(da, DESC_HI), desc64(db, DESC_HI64), 0); wg_fence(); }
#pragma unroll
  for (int kk = first ? 1 : 0; kk < 4; kk++) wgmma_ss<96>(acc, desc64(da + 2 * kk, DESC_HI), desc64(db + 64 * kk, DESC_HI64), 1);
  wg_commit();
}
__device__ __forceinline__ void retire(Ctx& c) {
  wg_wait<1>();
  c.release_prev();
  c.prev = 8 * c.stage;
  if (++c.stage == NSTAGE) { c.stage = 0; c.phase ^= 1; }
}
constexpr float GK = 0.32920349f;
__device__ __forceinline__ uint32_t gelu_pair(uint32_t y) {
  uint32_t u, th;
  asm("mul.rn.bf16x2 %0, %1, %2;" : "=r"(u) : "r"(hfma2(y, y, 0x401b401bu)), "r"(y));
  asm("tanh.approx.bf16x2 %0, %1;" : "=r"(th) : "r"(u));
  return hfma2(y, th, y);
}
__device__ __forceinline__ uint4 gelu_group(const uint32_t* a) { return make_uint4(gelu_pair(a[0]), gelu_pair(a[1]), gelu_pair(a[2]), gelu_pair(a[3])); }
__device__ __forceinline__ uint32_t fma_pack_v(const float* a, float r, float2 b) {
  uint32_t e; asm volatile("{.reg .f32 x, y; fma.rn.f32 x, %1, %3, %4; fma.rn.f32 y, %2, %3, %5; cvt.rn.bf16x2.f32 %0, y, x;}" : "=r"(e) : "f"(a[0]), "f"(a[1]), "f"(r), "f"(b.x), "f"(b.y)); return e;
}
__device__ __forceinline__ void lds_bias(float2* b, uint32_t addr) {
#pragma unroll
  for (int j = 0; j < 2; j++) asm volatile("ld.shared.v2.f32 {%0,%1}, [%2];" : "=f"(b[j].x), "=f"(b[j].y) : "r"(addr + 32 * j));
}
__device__ __forceinline__ int opaque(int v) { asm volatile("" : "+r"(v)); return v; }
__device__ __forceinline__ void stsm4(uint32_t addr, uint4 r) {
  asm volatile("stmatrix.sync.aligned.m8n8.x4.shared.b16 [%0], {%1,%2,%3,%4};" ::"r"(addr), "r"(r.x), "r"(r.y), "r"(r.z), "r"(r.w) : "memory");
}
__device__ __forceinline__ float ex2f(float x) { float r; asm("ex2.approx.ftz.f32 %0, %1;" : "=f"(r) : "f"(x)); return r; }
__device__ __forceinline__ uint32_t phi2(uint32_t tp) {
  uint32_t x, y;
  const float a0 = bf_lo(tp) * 1.4426950408889634f, a1 = bf_hi(tp) * 1.4426950408889634f;
  asm("max.bf16x2 %0, %1, %2;" : "=r"(x) : "r"(tp), "r"(0x35863586u));
  asm("min.bf16x2 %0, %1, %2;" : "=r"(y) : "r"(pack_bf16(ex2f(a0), ex2f(a1))), "r"(0x3f803f80u));
  return hadd2(x, y);
}
template <int q0, int q1>
__device__ __forceinline__ void part_groups(const float* a, uint4* p, uint32_t par) {
#pragma unroll
  for (int q = q0; q < q1; q++)
    st_ll(p + q * 32, pack_bf16(a[8 * q], a[8 * q + 1]), pack_bf16(a[8 * q + 2], a[8 * q + 3]), pack_bf16(a[8 * q + 4], a[8 * q + 5]), pack_bf16(a[8 * q + 6], a[8 * q + 7]), par);
}
__device__ __forceinline__ float rcpf(float x) { float r; asm("rcp.approx.ftz.f32 %0, %1;" : "=f"(r) : "f"(x)); return r; }
__device__ __forceinline__ float silu_h(float h) { float r; asm("tanh.approx.f32 %0, %1;" : "=f"(r) : "f"(h)); return fmaf(h, r, h); }
__device__ __forceinline__ int pairoff(int p, int g) { return (p >> 2) * 32 + g * 4 + (p & 3); }
template <bool STRONG> __device__ __forceinline__ void d1_load(uint32_t* W, int rb0, int head, int ln) {
  const uint2* qf = g_qkv + rb0 * 216 * 32 + pairoff(288 + head * 9 + (ln & 3), ln >> 2);
#pragma unroll
  for (int b = 0; b < 3; b++) {
#pragma unroll
    for (int j = 0; j < 4; j++) {
      const uint2* p = qf + j * 216 * 32 + 32 * b;
      const uint2 kk = STRONG ? ld_ll64(p) : ld_ca64(p), vv = STRONG ? ld_ll64(p + 72 * 32) : ld_ca64(p + 72 * 32);
      W[6 * j + 2 * b] = kk.x; W[6 * j + 2 * b + 1] = kk.y; W[24 + 6 * j + 2 * b] = vv.x; W[24 + 6 * j + 2 * b + 1] = vv.y;
    }
  }
}
__device__ __forceinline__ bool d1_bad(const uint32_t* W, int t, uint32_t par) {
  uint32_t bad = 0, bad2 = 0;
#pragma unroll
  for (int q = 0; q < 12; q++) ll_chk((q % 3) != 2 ? bad : bad2, W[2 * q], W[24 + 2 * q], par);
  return __any_sync(0xffffffffu, (bad | (t == 0 ? bad2 : 0u)) & 1);
}
__device__ __forceinline__ void d1_mov(uint32_t* W, int j, int t) {
  if (t != 0) { W[6 * j + 4] = W[6 * j + 5] = 0u; W[24 + 6 * j + 4] = W[24 + 6 * j + 5] = (t == 1 ? 0x00003f80u : 0u); }
#pragma unroll
  for (int q = 0; q < 6; q++) { W[6 * j + q] = movmat(W[6 * j + q]); W[24 + 6 * j + q] = movmat(W[24 + 6 * j + q]); }
}
__device__ __forceinline__ void d1_mma(const uint32_t* W, float* R) {
  float c1[3][4];
#pragma unroll
  for (int j = 0; j < 12; j++) { R[j] = 0.f; c1[j >> 2][j & 3] = 0.f; }
#pragma unroll
  for (int ks = 0; ks < 4; ks++)
#pragma unroll
    for (int j = 0; j < 3; j++) {
      mma16816(R + 4 * j, W[24 + 6 * ks], W[24 + 6 * ks + 2], W[24 + 6 * ks + 1], W[24 + 6 * ks + 3], W[6 * ks + 2 * j], W[6 * ks + 2 * j + 1]);
      mma16816(c1[j], W[24 + 6 * ks + 4], 0u, W[24 + 6 * ks + 5], 0u, W[6 * ks + 2 * j], W[6 * ks + 2 * j + 1]);
    }
#pragma unroll
  for (int j = 0; j < 3; j++) { R[12 + 2 * j] = c1[j][0]; R[13 + 2 * j] = c1[j][1]; }
}
__device__ __forceinline__ bool kv_valid(int w, int ln) { return (w < 3 || ln < 12) && ((w != 2 && w != 4) || (ln & 3) == 0); }

struct Params {
  CUtensorMap tm_wqkv, tm_w1, tm_w2, tm_m, tm_wqkv64, tm_m64, tm_a, tm_ast;
  const __nv_bfloat16 *x, *b1, *b2, *wqkv, *w1, *w2, *wo;
  __nv_bfloat16* out;
};

__global__ void __cluster_dims__(2, 1, 1) __launch_bounds__(NTHREADS, 1) fused_kernel(const __grid_constant__ Params P) {
  extern __shared__ __align__(1024) uint8_t smem[];
  const uint32_t sbase = smem_u32(smem);
  const int tid = threadIdx.x, lane = tid & 31;
  const int warp = __shfl_sync(0xffffffffu, tid >> 5, 0);
  const int g = lane >> 2, t = lane & 3;
  const uint32_t ep = __shfl_sync(0xffffffffu, g_epoch[blockIdx.x], 0) + 1;
  const uint32_t par = ep & 1;
  STAMPW(0, 0);

  if (blockIdx.x >= 128) {
    const int a = blockIdx.x - 128;
    constexpr int WP = 1168, SM_T = 152 * WP, SM_HB = SM_T + 8 * 32 * 80;
    if (tid == 0) {
      mbar_init(sbase + SM_HB, 1);
      asm volatile("fence.mbarrier_init.release.cluster;" ::: "memory");
      mbar_expect(sbase + SM_HB, 144 * 1152);
    }
    for (int i = tid; i < (8 * WP + 8 * 32 * 80) / 4; i += NTHREADS) reinterpret_cast<uint32_t*>(smem + 144 * WP)[i] = 0u;
    __syncthreads();
    __nanosleep(1500);
    if (tid < 144)
      asm volatile("cp.async.bulk.shared::cluster.global.mbarrier::complete_tx::bytes [%0], [%1], %2, [%3];" ::"r"(sbase + tid * WP), "l"(P.wo + (a * 144 + tid) * D_), "r"(1152), "r"(sbase + SM_HB) : "memory");
    if (warp >= 8 && lane == 0) {
      const int id = a * 4 + (warp - 8);
      constexpr uint32_t CH = 9216 * 2;
#pragma unroll 1
      for (int i = id; i < 576; i += 16) {
        const char* p = i < 288 ? (const char*)P.w1 + (size_t)i * CH : (const char*)P.w2 + (size_t)(i - 288) * CH;
        asm volatile("cp.async.bulk.prefetch.L2.global [%0], %1;" ::"l"(p), "r"(CH) : "memory");
      }
    }
    __syncwarp();
    if (lane < 8) hint_wait(&g_f_kvp[a * 8 + lane], 16 * ep, 50);
    __syncwarp();
    STAMPW(0, 1);
#pragma unroll 1
    for (int u = warp; u < 40; u += 12) {
      const int hh = u & 7, w = 4 - (u >> 3), head = a * 8 + hh;
      uint4 v[16];
      int tries = 0;
      uint32_t bad;
      const bool val = kv_valid(w, lane);
#pragma unroll 1
      do {
        bad = 0;
#pragma unroll
        for (int j = 0; j < 16; j++) v[j] = val ? ld_ll(&g_kvp[((head * 5 + w) * 16 + j) * 32 + lane]) : make_uint4(par, 0u, par, 0u);
#pragma unroll
        for (int j = 0; j < 16; j++) ll_chk(bad, v[j].x, v[j].z, par);
      } while (__any_sync(0xffffffffu, bad & 1) && ++tries < (1 << 20));
      float s0 = 0.f, s1 = 0.f, s2 = 0.f, s3 = 0.f;
#pragma unroll
      for (int j = 0; j < 16; j++) { s0 += __uint_as_float(v[j].x); s1 += __uint_as_float(v[j].y); s2 += __uint_as_float(v[j].z); s3 += __uint_as_float(v[j].w); }
      if (w >= 3) {
        if (g == 2) st_ll(&g_z[(head * 2 + w - 3) * 4 + t], __float_as_uint(s0), __float_as_uint(s1), __float_as_uint(s2), __float_as_uint(s3), par);
        __syncwarp();
        hint_signal(&g_f_z[head]);
      }
      const int e0 = w < 3 ? g : 16 + g, e1 = w < 3 ? g + 8 : 16 + g, d0 = (w < 3 ? 8 * w : (w == 3 ? 0 : 16)) + 2 * t, d1 = w < 3 ? d0 : d0 + 8;
      __nv_bfloat16* T = reinterpret_cast<__nv_bfloat16*>(smem + SM_T) + hh * 32 * 40;
      if (e0 < 18) {
        T[d0 * 40 + e0] = __float2bfloat16(s0); T[(d0 + 1) * 40 + e0] = __float2bfloat16(s1);
        T[d1 * 40 + e1] = __float2bfloat16(s2); T[(d1 + 1) * 40 + e1] = __float2bfloat16(s3);
      }
    }
    __syncthreads();
    STAMPW(0, 2);
    mbar_wait(sbase + SM_HB, 0);
#pragma unroll 1
    for (int u = warp; u < 24; u += 12) {
      const int hh = u / 3, c0 = (u % 3) * 192;
      const uint32_t* T = reinterpret_cast<const uint32_t*>(smem + SM_T) + hh * 32 * 20 + g * 20 + t;
      const uint32_t a00 = T[0], a01 = T[160], a02 = T[4], a03 = T[164], a10 = T[8], a11 = T[168], b00 = T[320], b02 = T[324], b10 = T[328];
      const uint32_t rowa = sbase + (hh * 18 + (lane & 15)) * WP + (c0 + (lane >> 4) * 8) * 2, rowb = sbase + (hh * 18 + 16 + (lane & 7)) * WP + (c0 + ((lane >> 3) & 1) * 8) * 2;
#pragma unroll 3
      for (int j = 0; j < 12; j++) {
        uint32_t w0, w1, w2, w3, w4, w5;
        asm volatile("ldmatrix.sync.aligned.m8n8.x4.trans.shared.b16 {%0,%1,%2,%3}, [%4];" : "=r"(w0), "=r"(w1), "=r"(w2), "=r"(w3) : "r"(rowa + j * 32));
        asm volatile("ldmatrix.sync.aligned.m8n8.x2.trans.shared.b16 {%0,%1}, [%2];" : "=r"(w4), "=r"(w5) : "r"(rowb + j * 32));
        float p[4][4];
#pragma unroll
        for (int q = 0; q < 4; q++) p[q][0] = p[q][1] = p[q][2] = p[q][3] = 0.f;
        mma16816(p[0], a00, a01, a02, a03, w0, w1); mma16816(p[1], a00, a01, a02, a03, w2, w3);
        mma16816(p[2], b00, 0u, b02, 0u, w0, w1); mma16816(p[3], b00, 0u, b02, 0u, w2, w3);
        mma16816(p[0], a10, a11, 0u, 0u, w4, 0u); mma16816(p[1], a10, a11, 0u, 0u, w5, 0u);
        mma16816(p[2], b10, 0u, 0u, 0u, w4, 0u); mma16816(p[3], b10, 0u, 0u, 0u, w5, 0u);
        stsm4(rowa + j * 32, make_uint4(pack_bf16(p[0][0], p[0][1]), pack_bf16(p[0][2], p[0][3]), pack_bf16(p[1][0], p[1][1]), pack_bf16(p[1][2], p[1][3])));
        if (g < 2) {
          uint32_t* r = reinterpret_cast<uint32_t*>(smem + (hh * 18 + 16 + g) * WP + (c0 + j * 16 + 2 * t) * 2);
          r[0] = pack_bf16(p[2][0], p[2][1]); r[4] = pack_bf16(p[3][0], p[3][1]);
        }
      }
      asm volatile("fence.proxy.async.shared::cta;" ::: "memory");
      __syncwarp();
      if (lane < 18) {
        asm volatile("cp.async.bulk.global.shared::cta.bulk_group [%0], [%1], %2;" ::"l"(g_m + (a * 144 + hh * 18 + lane) * D_ + c0), "r"(sbase + (hh * 18 + lane) * WP + c0 * 2), "r"(384) : "memory");
        asm volatile("cp.async.bulk.commit_group;" ::: "memory");
      }
    }
    asm volatile("cp.async.bulk.wait_group 0;" ::: "memory");
    asm volatile("fence.proxy.async.global;" ::: "memory");
    __syncwarp();
    if (lane == 0) asm volatile("red.release.gpu.global.add.u32 [%0], 1;" ::"l"(g_f_m) : "memory");
    STAMPW(0, 3);
    __syncthreads();
    if (tid == 0) g_epoch[blockIdx.x] = ep;
    return;
  }

  const int cl = blockIdx.x >> 1, rank = blockIdx.x & 1;
  const int f = cl & 7, m = (cl >> 3) * 2 + rank;
  const int srole = f >= 6 ? 1 : 0;
  const uint32_t bar_full = sbase + SM_BAR, bar_empty = bar_full + 8 * NSTAGE, bar_xfree = bar_empty + 8 * NSTAGE, bar_ofull = bar_xfree + 72,
                 bar_d = bar_ofull + 72;

  if (tid == 0) {
#pragma unroll 1
    for (int i = 0; i < NSTAGE; i++) { mbar_init(bar_full + 8 * i, 1); mbar_init(bar_empty + 8 * i, 4); }
#pragma unroll 1
    for (int i = 0; i < 9; i++) { mbar_init(bar_xfree + 8 * i, 2); mbar_init(bar_ofull + 8 * i, 1); }
    mbar_init(bar_d, 1);
    asm volatile("fence.mbarrier_init.release.cluster;" ::: "memory");
  }
  __syncwarp();
  cluster_arrive_relaxed();

  if (warp >= 8) {
    const int srow = m * 128 + f * 16 + (warp - 8) * 4 + (lane >> 3);
    uint4 xs[9];
#pragma unroll
    for (int kb = 0; kb < 9; kb++) xs[kb] = __ldg(reinterpret_cast<const uint4*>(P.x + srow * D_) + (lane & 7) + kb * 8);
    auto stats = [&]() {
      const uint32_t* w = reinterpret_cast<const uint32_t*>(xs);
      float s0 = 0.f, s1 = 0.f;
#pragma unroll
      for (int i = 0; i < 36; i++) { s0 += bf_lo(w[i]); s1 += bf_hi(w[i]); }
      float sum = s0 + s1;
      sum += __shfl_xor_sync(0xffffffffu, sum, 1); sum += __shfl_xor_sync(0xffffffffu, sum, 2); sum += __shfl_xor_sync(0xffffffffu, sum, 4);
      const float mean = sum * (1.f / 576.f);
      s0 = 0.f; s1 = 0.f;
#pragma unroll
      for (int i = 0; i < 36; i++) { const float a = bf_lo(w[i]) - mean, b = bf_hi(w[i]) - mean; s0 = fmaf(a, a, s0); s1 = fmaf(b, b, s1); }
      float sq = s0 + s1;
      sq += __shfl_xor_sync(0xffffffffu, sq, 1); sq += __shfl_xor_sync(0xffffffffu, sq, 2); sq += __shfl_xor_sync(0xffffffffu, sq, 4);
      const float rstd = rsqrtf(sq * (1.f / 576.f) + 1e-5f);
      if ((lane & 7) == 0)
        st_ll64(&g_stat[srow], __float_as_uint(rstd), pack_bf16(-mean, -mean), par);
    };
    stats();
    asm volatile("setmaxnreg.dec.sync.aligned.u32 40;");
    cluster_wait();
    if (warp == 8) {
      if (lane == 0) {
        uint32_t stage = 0, phase = 1;
        const uint32_t sb = sbase + SM_B;
#pragma unroll 1
        for (int tl = 2 * srole; tl < 8 + 2 * srole; tl++) {
          const CUtensorMap* map = tl == 0 ? &P.tm_wqkv : (tl == 1 ? &P.tm_wqkv64 : (tl < 5 ? &P.tm_w1 : (tl < 8 ? &P.tm_w2 : (tl == 8 ? &P.tm_m : &P.tm_m64))));
          const int col = tl < 2 ? 288 * f + 192 * tl : (tl < 5 ? 576 * f + 192 * (tl - 2) : (tl < 8 ? 192 * ((tl - 5 + f) % 3) : (tl == 8 ? 192 * (f - 5) : 96 * (f - 6))));
          const bool perm = tl >= 5 && tl < 8;
          const bool z = (tl & 7) == 1;
          if (tl == 8) { flag_wait(g_f_m, 48 * ep); asm volatile("fence.proxy.async.global;" ::: "memory"); }
          const int cs = z ? 32 : 64, rs = z ? 64 : 32, nst = z ? 9 : 18;
#pragma unroll 1
          for (int st = 0; st < nst; st++) {
            int row = st * rs;
            if (perm) row += 576 * f + ((st < 6) ? 192 : (st < 12 ? -192 : 0));
            mbar_wait(bar_empty + 8 * stage, phase);
            mbar_expect(bar_full + 8 * stage, 12288);
            const uint32_t dst = sb + stage * STAGE_BYTES;
            if (((st ^ rank) & 1) == 0) {
              tma2d_mc(dst, map, col, row, bar_full + 8 * stage);
              tma2d_mc(dst + 8192, map, col + 2 * cs, row, bar_full + 8 * stage);
            } else {
              tma2d_mc(dst + 4096, map, col + cs, row, bar_full + 8 * stage);
            }
            if (++stage == NSTAGE) { stage = 0; phase ^= 1; }
          }
        }
      }
      __syncwarp();
    } else {
      const int aw = warp - 9;
      const int hi = f >> 2;
      if (aw == 0) {
        if (lane < 2) hint_wait(&g_f_qkv[m * 8 + 2 + 2 * lane + hi], 16 * ep, 200);
        __syncwarp();
        if (lane == 0) mbar_arrive(bar_d);
        STAMP(20);
      }
      if (lane < 5) hint_wait(lane < 4 ? &g_f_z[4 * f + lane] : &g_f_qkv[m * 8 + hi], lane < 4 ? 2 * ep : 16 * ep);
      __syncwarp();
      STAMPW(9, 22);
      uint32_t* stg = reinterpret_cast<uint32_t*>(smem + SM_SCR + aw * 2304);
#pragma unroll 1
      for (int u = aw * 2; u < 16; u += (u & 1) ? 5 : 1) {
        const int rbl = u >> 1, hp = (u & 1) * 2;
        const uint2* qf = g_qkv + (m * 8 + rbl) * 216 * 32;
        const uint2* zp = reinterpret_cast<const uint2*>(&g_z[(4 * f + hp) * 8 + t]);
        uint2 q[2][3];
        float d[4];
        int tries = 0;
        uint32_t bad;
#pragma unroll 1
        do {
          bad = tries ? ld_acquire(g_f_m) & 0u : 0u;
#pragma unroll
          for (int j = 0; j < 2; j++)
#pragma unroll
            for (int b = 0; b < 3; b++) q[j][b] = ld_ca64(qf + pairoff((4 * f + hp + j) * 9 + t, g) + 32 * b);
#pragma unroll
          for (int j = 0; j < 2; j++) {
            const uint2 z0 = ld_ca64(zp + 16 * j), z1 = ld_ca64(zp + 16 * j + 1), z2 = ld_ca64(zp + 16 * j + 8);
            if (t != 0) q[j][2] = make_uint2(par, 0u);
            ll_chk(bad, z0.x, z1.x, par); ll_chk(bad, z2.x, q[j][2].x, par); ll_chk(bad, q[j][0].x, q[j][1].x, par);
            d[2 * j] = bf_lo(q[j][0].x) * __uint_as_float(z0.x) + bf_hi(q[j][0].x) * __uint_as_float(z0.y) + bf_lo(q[j][1].x) * __uint_as_float(z1.x) + bf_hi(q[j][1].x) * __uint_as_float(z1.y) +
                       bf_lo(q[j][2].x) * __uint_as_float(z2.x) + bf_hi(q[j][2].x) * __uint_as_float(z2.y);
            d[2 * j + 1] = bf_lo(q[j][0].y) * __uint_as_float(z0.x) + bf_hi(q[j][0].y) * __uint_as_float(z0.y) + bf_lo(q[j][1].y) * __uint_as_float(z1.x) + bf_hi(q[j][1].y) * __uint_as_float(z1.y) +
                           bf_lo(q[j][2].y) * __uint_as_float(z2.x) + bf_hi(q[j][2].y) * __uint_as_float(z2.y);
          }
        } while (__any_sync(0xffffffffu, bad & 1) && ++tries < (1 << 20));
#pragma unroll
        for (int j = 0; j < 4; j++) d[j] += __shfl_xor_sync(0xffffffffu, d[j], 1);
#pragma unroll
        for (int j = 0; j < 4; j++) d[j] = rcpf(d[j] + __shfl_xor_sync(0xffffffffu, d[j], 2) + 1e-6f);
        if (hp == 0) { asm volatile("cp.async.bulk.wait_group.read 0;" ::: "memory"); __syncwarp(); }
#pragma unroll
        for (int j = 0; j < 2; j++) {
          const uint32_t r0 = pack_bf16(d[2 * j], d[2 * j]), r1 = pack_bf16(d[2 * j + 1], d[2 * j + 1]);
#pragma unroll
          for (int b = 0; b < 3; b++)
            if (b < 2 || t == 0) {
              stg[g * 36 + (hp + j) * 9 + 4 * b + t] = hfma2(q[j][b].x, r0, 0x80008000u);
              stg[(g + 8) * 36 + (hp + j) * 9 + 4 * b + t] = hfma2(q[j][b].y, r1, 0x80008000u);
            }
        }
        if (hp != 0) {
          asm volatile("fence.proxy.async.shared::cta;" ::: "memory");
          __syncwarp();
          if (lane == 0) {
            asm volatile("cp.async.bulk.tensor.2d.global.shared::cta.bulk_group [%0, {%2, %3}], [%1];" ::"l"(&P.tm_ast), "r"(smem_u32(stg)), "r"(72 * f), "r"(m * 128 + rbl * 16) : "memory");
            asm volatile("cp.async.bulk.commit_group;" ::: "memory");
          }
        }
      }
      asm volatile("cp.async.bulk.wait_group 0;" ::: "memory");
      asm volatile("fence.proxy.async.global;" ::: "memory");
      STAMPW(9, 26);
      asm volatile("bar.sync 5, 96;" ::: "memory");
      if (tid == 288) asm volatile("red.release.gpu.global.add.u32 [%0], 1;" ::"l"(&g_f_a[m]) : "memory");
      __syncwarp();
      STAMPW(9, 23);
      if (srole && aw == 2) {
        if (lane == 0) {
          flag_wait(&g_f_a[m], 8 * ep);
          asm volatile("fence.proxy.async.global;" ::: "memory");
#pragma unroll 1
          for (int kb = 0; kb < 9; kb++) {
            mbar_wait(bar_xfree + 8 * kb, 0);
            mbar_expect(bar_ofull + 8 * kb, 16384);
            tma2d(sbase + SM_A + kb * 16384, &P.tm_a, kb * 64, m * 128, bar_ofull + 8 * kb);
          }
        }
        __syncwarp();
      }
    }
    cluster_arrive_relaxed();
    cluster_wait();
  } else {
    const int wg = warp >> 2;
    {
      const int rs = lane >> 3, j = lane & 7;
      uint4 xv[4][9];
#pragma unroll
      for (int it = 0; it < 4; it++)
#pragma unroll
        for (int kb = 0; kb < 9; kb++) xv[it][kb] = __ldg(reinterpret_cast<const uint4*>(P.x + (m * 128 + warp * 16 + it * 4 + rs) * D_) + j + kb * 8);
      uint32_t bw0 = __ldg(reinterpret_cast<const uint32_t*>(P.b1 + 576 * f) + tid), bw1 = tid < 32 ? __ldg(reinterpret_cast<const uint32_t*>(P.b1 + 576 * f) + 256 + tid) : 0u;
      uint2 st[4];
      int tries = 0;
      uint32_t bad;
#pragma unroll 1
      do {
        bad = 0;
#pragma unroll
        for (int it = 0; it < 4; it++) st[it] = ld_ll64(&g_stat[m * 128 + warp * 16 + it * 4 + rs]);
        ll_chk(bad, st[0].x, st[1].x, par); ll_chk(bad, st[2].x, st[3].x, par);
      } while (__any_sync(0xffffffffu, bad & 1) && ++tries < (1 << 22));
      STAMPW(0, 19);
#pragma unroll
      for (int it = 0; it < 4; it++) {
        const uint32_t nm = st[it].y;
        uint8_t* dst = smem + SM_A + (warp * 16 + it * 4 + rs) * 128 + ((j ^ ((it * 4 + rs) & 7)) << 4);
#pragma unroll
        for (int kb = 0; kb < 9; kb++) {
          const uint4 w = xv[it][kb];
          *reinterpret_cast<uint4*>(dst + kb * 16384) = make_uint4(hadd2(w.x, nm), hadd2(w.y, nm), hadd2(w.z, nm), hadd2(w.w, nm));
        }
        if (j == 0) reinterpret_cast<uint32_t*>(smem + SM_RSTD)[warp * 16 + it * 4 + rs] = st[it].x;
      }
      reinterpret_cast<float2*>(smem + SM_BIAS)[tid] = make_float2(bf_lo(bw0) * GK, bf_hi(bw0) * GK);
      if (tid < 48) reinterpret_cast<float2*>(smem + SM_BIAS)[256 + tid] = make_float2(bf_lo(bw1) * GK, bf_hi(bw1) * GK);
      asm volatile("fence.proxy.async.shared::cta;" ::: "memory");
    }
    asm volatile("setmaxnreg.inc.sync.aligned.u32 232;");
    cluster_wait();
    asm volatile("bar.sync 1, 256;" ::: "memory");
    STAMPW(0, 1);
    Ctx c;
    c.full = bar_full;
    c.emb = __shfl_sync(0xffffffffu, mapa(bar_empty, (warp & 3) == 0 ? rank : (rank ^ 1)), 0);
    c.sig = lane == 0 && (warp & 3) < 2;
    c.stage = 0; c.phase = 0; c.prev = ~0u;
    c.dB = (((sbase + SM_B) & 0x3FFFF) >> 4) | ((4096u >> 4) << 16);
    c.dA = (((sbase + SM_A + wg * 8192) & 0x3FFFF) >> 4) | (1u << 16);
    const bool leader = (lane == 0) && ((warp & 3) == 0);

    const int rb = m * 8 + warp;
    const uint32_t bias_t = sbase + SM_BIAS + 8 * t;
    const uint32_t hst = sbase + SM_A + (warp * 16 + (lane & 7) + ((lane >> 3) & 1) * 8) * 128 + (((lane >> 4) ^ (lane & 7)) << 4);
    auto wg_sync = [&]() {
      asm volatile("fence.proxy.async.shared::cta;" ::: "memory");
      if (wg == 0) asm volatile("bar.sync 2, 128;" ::: "memory"); else asm volatile("bar.sync 3, 128;" ::: "memory");
    };
    float A[96], B[96];
#pragma unroll
    for (int i = 0; i < 96; i++) B[i] = 0.f;
#define EX1(ACC, U) case U: _Pragma("unroll") for (int q = 0; q < 4; q++) E[q] = fma_pack_v(&ACC[8 * U + 2 * q], (q & 1) ? r1 : r0, bs[q >> 1]); break;
#define EXTRACT(ACC) uint32_t E[4]; switch (u) { EX1(ACC, 0) EX1(ACC, 1) EX1(ACC, 2) EX1(ACC, 3) EX1(ACC, 4) EX1(ACC, 5) EX1(ACC, 6) EX1(ACC, 7) EX1(ACC, 8) EX1(ACC, 9) EX1(ACC, 10) default: EX1(ACC, 11) }
#define ST_PART(DST) st_ll(DST, E[0], E[1], E[2], E[3], par);
#define ST_QKV(DST) { if (f < 4) { _Pragma("unroll") for (int q = 0; q < 4; q++) E[q] = phi2(E[q]); } \
    st_ll64(reinterpret_cast<uint2*>(DST), E[0], E[1], par); st_ll64(reinterpret_cast<uint2*>(DST) + 32, E[2], E[3], par); }
#define ST_SMEM(KB0) stsm4((hst ^ ((u & 3) << 5)) + (KB0 + (u >> 2)) * 16384, h);
#define LDS_R(SCALED, SC) float r0 = 1.f, r1 = 1.f; if (SCALED) { asm volatile("ld.shared.f32 %0, [%1];" : "=f"(r0) : "r"(rst)); asm volatile("ld.shared.f32 %0, [%1];" : "=f"(r1) : "r"(rst + 32)); r0 *= (SC); r1 *= (SC); }
    const uint32_t rst = sbase + SM_RSTD + (warp * 16 + g) * 4;
    const int fr = f % 3;
#pragma unroll 1
    for (int i = srole;; i++) {
      {
        const uint32_t ow = i == 4 ? bar_ofull : 0u;
        if (ow) mbar_wait(ow, 0);
        issue192(A, c, 0, true);
        const int ln = opaque(lane);
        uint4* dst = i == 1 ? reinterpret_cast<uint4*>(g_qkv + (rb * 216 + 36 * f + 24) * 32 + ln) : g_part + ((rb * 8 + f) * 36 + 12 * (i == 3 ? fr : (fr + 2) % 3)) * 32 + ln;
        LDS_R(i <= 2, i == 2 ? GK : 1.f)
        retire(c);
        if (ow && leader) mbar_arrive(bar_xfree + 64);
        fence_regs<96>(B);
        int s = 1;
        if (i == 2) {
#pragma unroll 1
          for (; s < 3; s++) { issue192(A, c, s); retire(c); }
        }
        const int nu = i == srole ? 0 : (i == 1 ? 6 : 12);
        const int two = (i == 2 && srole) ? 1 : 0;
#pragma unroll 1
        for (int u = 0; u < nu; u++) {
          float2 bs[2];
          lds_bias(bs, bias_t + (i == 2 ? 192 + 16 * u : 576) * 4);
          if (!(u & two)) {
            if (ow && !(s & 1)) mbar_wait(ow + 4 * s, 0);
            issue192(A, c, s);
          }
          EXTRACT(B)
          if (i == 2) {
            const uint4 h = gelu_group(E);
            ST_SMEM(0)
          } else if (i == 1) ST_QKV(dst)
          else ST_PART(dst)
          dst += 32;
          if ((u & two) == two) { retire(c); s++; }
        }
        if (nu == 6) hint_signal(&g_f_qkv[m * 8 + f]);
        const bool d1 = i == 1 + srole;
        const int send = d1 ? 11 : 15;
#pragma unroll 1
        for (; s < send; s++) {
          if (ow && !(s & 1)) mbar_wait(ow + 4 * s, 0);
          issue192(A, c, s);
          retire(c);
        }
        uint32_t W[48];
        if (d1) {
          const int head = 4 * f + (warp >> 1), rb0 = m * 8 + (warp & 1) * 4;
          issue192(A, c, 11);
          mbar_wait(bar_d, 0);
          d1_load<false>(W, rb0, head, opaque(lane));
          retire(c);
          issue192(A, c, 12);
          retire(c);
          issue192(A, c, 13);
          int tries = 0;
#pragma unroll 1
          while (d1_bad(W, t, par) && ++tries < (1 << 20)) d1_load<true>(W, rb0, head, opaque(lane));
          d1_mov(W, 0, t); d1_mov(W, 1, t);
          retire(c);
          issue192(A, c, 14);
          d1_mov(W, 2, t); d1_mov(W, 3, t);
          wg_wait<0>();
          asm volatile("bar.sync 4, 256;" ::: "memory");
          float R[18];
          d1_mma(W, R);
          float2* xch = reinterpret_cast<float2*>(smem + SM_SCR + (warp >> 1) * 1792) + opaque(lane);
          if (warp & 1) {
#pragma unroll
            for (int q = 0; q < 6; q++) xch[q * 32] = make_float2(R[2 * q], R[2 * q + 1]);
            if (lane < 12) { xch[192] = make_float2(R[12], R[13]); xch[204] = make_float2(R[14], R[15]); if (t == 0) xch[216 - lane + g] = make_float2(R[16], R[17]); }
          } else if (R[17] == 1.2345e-30f) R[16] = 0.f;
          asm volatile("bar.sync 4, 256;" ::: "memory");
          retire(c);
          issue192(A, c, 15);
          if (!(warp & 1)) {
            const int l2 = opaque(lane);
#pragma unroll
            for (int q = 0; q < 6; q++) { const float2 o = xch[q * 32]; R[2 * q] += o.x; R[2 * q + 1] += o.y; }
            if (l2 < 12) {
              const float2 o0 = xch[192], o1 = xch[204], o2 = xch[216 - l2 + (l2 >> 2)];
              R[12] += o0.x; R[13] += o0.y; R[14] += o1.x; R[15] += o1.y; R[16] += o2.x; R[17] += o2.y;
            }
            uint4* dkv = &g_kvp[(head * 80 + m) * 32 + l2];
#pragma unroll
            for (int w = 0; w < 5; w++)
              if (kv_valid(w, l2)) st_ll(dkv + w * 512, __float_as_uint(R[4 * w]), __float_as_uint(R[4 * w + 1]), w < 4 ? __float_as_uint(R[4 * w + 2]) : 0u, w < 4 ? __float_as_uint(R[4 * w + 3]) : 0u, par);
            __syncwarp();
            hint_signal(&g_f_kvp[head]);
          }
          STAMPW(0, 21);
        } else issue192(A, c, 15);
        if (i == 2) {
          const uint4* hsp = g_hsp + (blockIdx.x * 8 + warp) * 12 * 32 + opaque(lane);
#pragma unroll
          for (int q = 0; q < 12; q++) { const uint4 v = ldcg128(hsp + q * 32); W[4 * q] = v.x; W[4 * q + 1] = v.y; W[4 * q + 2] = v.z; W[4 * q + 3] = v.w; }
        } else {
#pragma unroll
          for (int q = 0; q < 48; q++) W[q] = 0;
        }
        retire(c);
        if (ow) mbar_wait(ow + 64, 0);
        issue192(A, c, 16);
        if (i == 2) wg_sync();
        retire(c);
        issue192(A, c, 17);
        if (i == 2) {
#pragma unroll
          for (int q = 0; q < 12; q++) stsm4((hst ^ ((q & 3) << 5)) + (3 + (q >> 2)) * 16384, make_uint4(W[4 * q], W[4 * q + 1], W[4 * q + 2], W[4 * q + 3]));
        }
        retire(c);
      }
      STAMPW(0, 2 + 2 * i);
      if ((i & 3) == 0) {
        issue96(B, c, 0, true);
        const int ln = opaque(lane);
        uint4* dst = i == 0 ? reinterpret_cast<uint4*>(g_qkv + (rb * 216 + 36 * f) * 32 + ln) : g_s + (rb * 36 + 12 * (f - 5)) * 32 + ln;
        LDS_R(i == 0, 1.f)
        const float2 bs[2] = {{0.f, 0.f}, {0.f, 0.f}};
        retire(c);
        fence_regs<96>(A);
#pragma unroll 1
        for (int u = 0; u < 12; u++) {
          if (!(u & 1) || u > 10) issue96(B, c, u < 10 ? 1 + (u >> 1) : u - 4, false);
          EXTRACT(A)
          if (i == 0) ST_QKV(dst)
          else ST_PART(dst)
          dst += 32;
          if ((u & 1) || u >= 10) retire(c);
        }
        if (i == 0) hint_signal(&g_f_qkv[m * 8 + f]);
        issue96(B, c, 8, false);
        retire(c);
        if (i == 4) {
          STAMPW(0, 11);
          wg_wait<0>();
          c.release_prev();
          fence_regs<48>(B);
          part_groups<0, 6>(B, g_s + (rb * 36 + 6 * (f - 6)) * 32 + opaque(lane), par);
          break;
        }
      } else {
        issue192(B, c, 0, true);
        const int ln = opaque(lane);
        uint4* dst = i == 1 ? g_hsp + (blockIdx.x * 8 + warp) * 12 * 32 + ln : g_part + ((rb * 8 + f) * 36 + 12 * ((fr + 1) % 3)) * 32 + ln;
        const bool xf = i == 3 && srole && leader;
        LDS_R(i != 3, GK)
        retire(c);
        fence_regs<96>(A);
        const int two = (i == 3 && !srole) ? 1 : 0;
        int s = 1;
#pragma unroll 1
        for (int u = 0; u < 12; u++) {
          float2 bs[2];
          lds_bias(bs, bias_t + (i == 3 ? 576 : (i == 1 ? 0 : 384) + 16 * u) * 4);
          if (!(u & two)) issue192(B, c, s);
          EXTRACT(A)
          if (i != 3) {
            const uint4 h = gelu_group(E);
            if (i == 1) *dst = h;
            else {
              ST_SMEM(6)
              if (u == 3 || u == 9) wg_sync();
            }
          } else ST_PART(dst)
          dst += 32;
          if ((u & two) == two) {
            retire(c);
            if (!(s & 1) && xf) mbar_arrive(bar_xfree + 4 * s - 8);
            s++;
          }
        }
        if (i == 3 && !srole) {
          const int c2 = (fr + 2) % 3, v0 = 12 * c2 + (f < 3 ? 0 : 6), fo = f < 3 ? f + 3 : f - 3;
          const int l2 = opaque(lane);
          const uint4* pb = g_part + (rb * 8 * 36 + v0) * 32 + l2;
          uint4 p[12];
          uint32_t S[24];
#pragma unroll
          for (int q = 0; q < 24; q++) S[q] = 0u;
          auto ldp = [&](const uint4* a0, const uint4* a1) {
#pragma unroll
            for (int q = 0; q < 6; q++) { p[q] = ld_ll(a0 + q * 32); p[6 + q] = ld_ll(a1 + q * 32); }
          };
          auto badp = [&]() {
            uint32_t bad = 0;
#pragma unroll
            for (int q = 0; q < 12; q++) ll_chk(bad, p[q].x, p[q].z, par);
            return __any_sync(0xffffffffu, bad & 1);
          };
#pragma unroll 1
          for (int w = 0; w < 3; w++) {
            const uint4* a0 = pb + (w == 0 ? c2 : (w == 1 ? 6 : (fr + 1) % 3)) * 36 * 32;
            const uint4* a1 = a0 + (w == 1 ? 1 : 3) * 36 * 32;
            issue192(B, c, 7 + 3 * w);
            ldp(a0, a1);
            retire(c);
            issue192(B, c, 8 + 3 * w);
            retire(c);
            issue192(B, c, 9 + 3 * w);
            int tries = 0;
#pragma unroll 1
            while (badp() && ++tries < (1 << 20)) ldp(a0, a1);
#pragma unroll
            for (int q = 0; q < 24; q++) S[q] = hadd2(S[q], hadd2(reinterpret_cast<const uint32_t*>(p)[q], reinterpret_cast<const uint32_t*>(p)[24 + q]));
            retire(c);
          }
          uint4 xx[6];
          uint32_t bb[12];
          int ro[6];
          issue192(B, c, 16);
#pragma unroll
          for (int j = 0; j < 6; j++) {
            const int k = l2 + 32 * j, r = (k * 171) >> 11;
            ro[j] = (rb * 16 + r) * D_ + 16 * v0 + (k - 12 * r) * 8;
            xx[j] = __ldg(reinterpret_cast<const uint4*>(P.x + ro[j]));
          }
#pragma unroll
          for (int j = 0; j < 12; j++) bb[j] = __ldg(reinterpret_cast<const uint32_t*>(P.b2 + 16 * v0 + 8 * j + 2 * (l2 & 3)));
          retire(c);
          issue192(B, c, 17);
          retire(c);
          STAMPW(0, 9);
          wg_wait<0>();
          c.release_prev();
          fence_regs<96>(B);
          uint4* snd = g_part + ((rb * 8 + f) * 36 + 12 * c2 + (f < 3 ? 6 : 0)) * 32 + l2;
          if (f < 3) part_groups<0, 6>(B + 48, snd, par);
          else {
            part_groups<0, 6>(B, snd, par);
#pragma unroll
            for (int q = 0; q < 48; q++) B[q] = B[48 + q];
          }
          asm volatile("bar.sync 4, 256;" ::: "memory");
          STAMPW(0, 12);
#pragma unroll
          for (int q = 0; q < 24; q++) {
            B[2 * q] = fmaf(B[2 * q] + bf_lo(S[q]), 0.25f / GK, 0.5f * bf_lo(bb[q >> 1])); B[2 * q + 1] = fmaf(B[2 * q + 1] + bf_hi(S[q]), 0.25f / GK, 0.5f * bf_hi(bb[q >> 1]));
          }
          const uint4* sp = g_s + (rb * 36 + v0) * 32 + l2;
          int tries = 0;
#pragma unroll 1
          while (++tries < (1 << 20)) {
            const uint2 u0 = ld_ll64(pb + (fo * 36 + 5) * 32), u1 = ld_ll64(sp + 5 * 32);
            if (!__any_sync(0xffffffffu, ((u0.x ^ par) | (u1.x ^ par)) & 1)) break;
            __nanosleep(40);
          }
          tries = 0;
#pragma unroll 1
          do { ldp(pb + fo * 36 * 32, sp); } while (badp() && ++tries < (1 << 20));
          STAMPW(0, 14);
          const uint32_t tb = sbase + SM_A + warp * 3328;
#pragma unroll
          for (int v = 0; v < 6; v++) {
            uint32_t o[4];
#pragma unroll
            for (int k = 0; k < 4; k++) {
              const int q = 4 * v + k;
              const uint32_t w = reinterpret_cast<const uint32_t*>(p)[q];
              const uint32_t gt = pack_bf16(silu_h(fmaf(bf_lo(w), 0.25f / GK, B[2 * q])), silu_h(fmaf(bf_hi(w), 0.25f / GK, B[2 * q + 1])));
              o[k] = hfma2(reinterpret_cast<const uint32_t*>(p)[24 + q], gt, 0x80008000u);
            }
            stsm4(tb + (l2 & 15) * 208 + (l2 >> 4) * 16 + v * 32, make_uint4(o[0], o[1], o[2], o[3]));
          }
          __syncwarp();
#pragma unroll
          for (int j = 0; j < 6; j++) {
            const int k = l2 + 32 * j, r = (k * 171) >> 11;
            uint4 o;
            asm volatile("ld.shared.v4.u32 {%0,%1,%2,%3}, [%4];" : "=r"(o.x), "=r"(o.y), "=r"(o.z), "=r"(o.w) : "r"(tb + r * 208 + (k - 12 * r) * 16) : "memory");
            *reinterpret_cast<uint4*>(P.out + ro[j]) = make_uint4(hadd2(o.x, xx[j].x), hadd2(o.y, xx[j].y), hadd2(o.z, xx[j].z), hadd2(o.w, xx[j].w));
          }
          break;
        }
#pragma unroll 1
        for (; s < 17; s++) {
          issue192(B, c, s);
          if (s == 14 && i == 2) wg_sync();
          retire(c);
          if ((s & 1) == 0 && xf) mbar_arrive(bar_xfree + 4 * s - 8);
        }
        issue192(B, c, 17);
        retire(c);
      }
      STAMPW(0, 3 + 2 * i);
    }
    STAMPW(0, 15);
    cluster_arrive_relaxed();
    cluster_wait();
    STAMPW(0, 16);
    if (tid == 0) g_epoch[blockIdx.x] = ep;
  }
}

typedef CUresult (*EncFn)(CUtensorMap*, CUtensorMapDataType, cuuint32_t, void*, const cuuint64_t*, const cuuint64_t*, const cuuint32_t*, const cuuint32_t*,
                          CUtensorMapInterleave, CUtensorMapSwizzle, CUtensorMapL2promotion, CUtensorMapFloatOOBfill);

void make_map(EncFn enc, CUtensorMap* tm, const void* ptr, int rows, int cols, int box_rows, int mode = 0) {
  cuuint64_t gd[2] = {(cuuint64_t)cols, (cuuint64_t)rows};
  cuuint64_t gs[1] = {(cuuint64_t)cols * 2};
  cuuint32_t bx[2] = {mode == 1 ? 32u : (mode == 2 ? 72u : 64u), (cuuint32_t)box_rows};
  cuuint32_t es[2] = {1, 1};
  enc(tm, CU_TENSOR_MAP_DATA_TYPE_BFLOAT16, 2, const_cast<void*>(ptr), gd, gs, bx, es, CU_TENSOR_MAP_INTERLEAVE_NONE, mode == 1 ? CU_TENSOR_MAP_SWIZZLE_64B : (mode == 2 ? CU_TENSOR_MAP_SWIZZLE_NONE : CU_TENSOR_MAP_SWIZZLE_128B),
      CU_TENSOR_MAP_L2_PROMOTION_L2_256B, CU_TENSOR_MAP_FLOAT_OOB_FILL_NONE);
}

}

extern "C" void kernel_launch(void* const* d_in, const int* in_sizes, int n_in, void* d_out, int out_size) {
  (void)in_sizes; (void)n_in; (void)out_size;
  static EncFn enc = nullptr;
  static void *a_ptr = nullptr, *m_ptr = nullptr;
  if (!enc) {
    void* fn = nullptr; cudaDriverEntryPointQueryResult q;
    cudaGetDriverEntryPoint("cuTensorMapEncodeTiled", &fn, cudaEnableDefault, &q);
    enc = (EncFn)fn;
    cudaFuncSetAttribute(fused_kernel, cudaFuncAttributeMaxDynamicSharedMemorySize, SMEM_BYTES);
    cudaGetSymbolAddress(&a_ptr, g_a);
    cudaGetSymbolAddress(&m_ptr, g_m);
  }
  Params P;
  P.x = (const __nv_bfloat16*)d_in[0];
  P.wqkv = (const __nv_bfloat16*)d_in[1];
  P.wo = (const __nv_bfloat16*)d_in[2];
  P.w1 = (const __nv_bfloat16*)d_in[4];
  P.b1 = (const __nv_bfloat16*)d_in[5];
  P.w2 = (const __nv_bfloat16*)d_in[6];
  P.b2 = (const __nv_bfloat16*)d_in[7];
  P.out = (__nv_bfloat16*)d_out;
  make_map(enc, &P.tm_wqkv, P.wqkv, D_, Q3_, 32);
  make_map(enc, &P.tm_w1, P.w1, D_, F_, 32);
  make_map(enc, &P.tm_w2, P.w2, F_, D_, 32);
  make_map(enc, &P.tm_m, m_ptr, D_, D_, 32);
  make_map(enc, &P.tm_wqkv64, P.wqkv, D_, Q3_, 64, 1);
  make_map(enc, &P.tm_m64, m_ptr, D_, D_, 64, 1);
  make_map(enc, &P.tm_a, a_ptr, S_, D_, 128);
  make_map(enc, &P.tm_ast, a_ptr, S_, D_, 16, 2);
  fused_kernel<<<NCTAS, NTHREADS, SMEM_BYTES, cudaStreamPerThread>>>(P);
}
```

```cpp
#include <cuda_runtime.h>
#include <cuda.h>
#include <cuda_bf16.h>
#include <stdint.h>

namespace {

constexpr int S_ = 2048, D_ = 576, F_ = 4608, Q3_ = 1728;
constexpr int NSTAGE = 6, STAGE_BYTES = 12288;
constexpr int SM_A = 0, SM_B = 147456, SM_BIAS = SM_B + NSTAGE * STAGE_BYTES, SM_RSTD = SM_BIAS + 2304 + 128, SM_SCR = SM_RSTD + 512, SM_BAR = SM_SCR + 7168;
constexpr int SMEM_BYTES = SM_BAR + 320;
constexpr int NTHREADS = 384;
constexpr int NCTAS = 132;

__device__ uint2 g_qkv[(128 * 216 + 2) * 32];
__device__ __align__(1024) __nv_bfloat16 g_a[S_ * D_];
__device__ __align__(1024) __nv_bfloat16 g_m[D_ * D_];
__device__ uint4 g_kvp[32 * 5 * 16 * 32];
__device__ uint4 g_z[32 * 2 * 4];
__device__ uint4 g_part[128 * 8 * 36 * 32];
__device__ uint4 g_s[128 * 36 * 32];
__device__ uint4 g_hsp[128 * 12 * 256];
__device__ uint32_t g_f_qkv[16 * 8];
__device__ uint32_t g_f_kvp[32];
__device__ uint32_t g_f_z[32];
__device__ uint32_t g_f_a[16];
__device__ uint32_t g_f_m[1];
__device__ uint2 g_stat[S_];
__device__ uint32_t g_epoch[NCTAS];

#define STAMP(i)
#define STAMPW(w, i)
#define WSTAMP(i)
__device__ __forceinline__ uint32_t smem_u32(const void* p) { return (uint32_t)__cvta_generic_to_shared(p); }
__device__ __forceinline__ void mbar_init(uint32_t a, int c) { asm volatile("mbarrier.init.shared::cta.b64 [%0], %1;" ::"r"(a), "r"(c)); }
__device__ __forceinline__ void mbar_expect(uint32_t a, uint32_t b) { asm volatile("mbarrier.arrive.expect_tx.shared::cta.b64 _, [%0], %1;" ::"r"(a), "r"(b) : "memory"); }
__device__ __forceinline__ void mbar_arrive(uint32_t a) { asm volatile("mbarrier.arrive.shared::cta.b64 _, [%0];" ::"r"(a) : "memory"); }
__device__ __forceinline__ void mbar_arrive_cl(uint32_t a) { asm volatile("mbarrier.arrive.shared::cluster.b64 _, [%0];" ::"r"(a) : "memory"); }
__device__ __forceinline__ uint32_t mapa(uint32_t a, uint32_t cta) { uint32_t r; asm volatile("mapa.shared::cluster.u32 %0, %1, %2;" : "=r"(r) : "r"(a), "r"(cta)); return r; }
__device__ __forceinline__ void mbar_wait(uint32_t a, uint32_t ph) {
  uint32_t ok; int it = 0;
#pragma unroll 1
  do {
    asm volatile("{.reg .pred p; mbarrier.try_wait.parity.shared::cta.b64 p, [%1], %2; selp.u32 %0,1,0,p;}" : "=r"(ok) : "r"(a), "r"(ph) : "memory");
  } while (!ok && ++it < (1 << 18));
}
__device__ __forceinline__ void tma2d(uint32_t dst, const CUtensorMap* m, int c0, int c1, uint32_t bar) {
  asm volatile("cp.async.bulk.tensor.2d.shared::cluster.global.mbarrier::complete_tx::bytes [%0], [%1, {%3,%4}], [%2];" ::"r"(dst), "l"(m), "r"(bar), "r"(c0), "r"(c1) : "memory");
}
__device__ __forceinline__ void tma2d_mc(uint32_t dst, const CUtensorMap* m, int c0, int c1, uint32_t bar) {
  asm volatile("cp.async.bulk.tensor.2d.shared::cluster.global.mbarrier::complete_tx::bytes.multicast::cluster [%0], [%1, {%3,%4}], [%2], %5;" ::"r"(dst), "l"(m), "r"(bar), "r"(c0), "r"(c1), "h"((uint16_t)3) : "memory");
}
__device__ __forceinline__ void cluster_arrive_relaxed() { asm volatile("barrier.cluster.arrive.relaxed.aligned;" ::: "memory"); }
__device__ __forceinline__ void cluster_wait() { asm volatile("barrier.cluster.wait.acquire.aligned;" ::: "memory"); }
__device__ __forceinline__ void wg_fence() { asm volatile("wgmma.fence.sync.aligned;" ::: "memory"); }
__device__ __forceinline__ void wg_commit() { asm volatile("wgmma.commit_group.sync.aligned;" ::: "memory"); }
template <int n> __device__ __forceinline__ void wg_wait() { asm volatile("wgmma.wait_group.sync.aligned %0;" ::"n"(n) : "memory"); }
__device__ __forceinline__ uint32_t ld_acquire(const uint32_t* p) { uint32_t v; asm volatile("ld.acquire.gpu.global.u32 %0, [%1];" : "=r"(v) : "l"(p) : "memory"); return v; }
__device__ __forceinline__ void flag_wait(const uint32_t* p, uint32_t target) {
  int it = 0;
#pragma unroll 1
  while ((int)(ld_acquire(p) - target) < 0 && ++it < (1 << 20)) __nanosleep(300);
}
__device__ __forceinline__ void hint_signal(uint32_t* p) {
  if ((threadIdx.x & 31) == 0) asm volatile("red.relaxed.gpu.global.add.u32 [%0], 1;" ::"l"(p) : "memory");
}
__device__ __forceinline__ void hint_wait(const uint32_t* p, uint32_t target, uint32_t ns = 400) {
  int it = 0; uint32_t v;
#pragma unroll 1
  do { asm volatile("ld.relaxed.gpu.global.u32 %0, [%1];" : "=r"(v) : "l"(p) : "memory"); if ((int)(v - target) >= 0) break; __nanosleep(ns); } while (++it < (1 << 20));
}
__device__ __forceinline__ uint32_t tag(uint32_t x, uint32_t par) { uint32_t r; asm("lop3.b32 %0, %1, 0xfffffffe, %2, 0xea;" : "=r"(r) : "r"(x), "r"(par)); return r; }
__device__ __forceinline__ void st_ll(uint4* p, uint32_t x, uint32_t y, uint32_t z, uint32_t w, uint32_t par) {
  asm volatile("{.reg .b64 a, b; mov.b64 a, {%1,%2}; mov.b64 b, {%3,%4}; st.relaxed.gpu.global.v2.b64 [%0], {a, b};}"
               ::"l"(p), "r"(tag(x, par)), "r"(y), "r"(tag(z, par)), "r"(w) : "memory");
}
__device__ __forceinline__ uint4 ld_ll(const uint4* p) {
  uint4 v;
  asm volatile("{.reg .b64 a, b; ld.relaxed.gpu.global.v2.b64 {a, b}, [%4]; mov.b64 {%0,%1}, a; mov.b64 {%2,%3}, b;}"
               : "=r"(v.x), "=r"(v.y), "=r"(v.z), "=r"(v.w) : "l"(p) : "memory");
  return v;
}
__device__ __forceinline__ void st_ll64(uint2* p, uint32_t x, uint32_t y, uint32_t par) {
  asm volatile("{.reg .b64 a; mov.b64 a, {%1,%2}; st.relaxed.gpu.global.b64 [%0], a;}" ::"l"(p), "r"(tag(x, par)), "r"(y) : "memory");
}
__device__ __forceinline__ uint2 ld_ca64(const void* p) {
  uint2 v;
  asm volatile("{.reg .b64 a; ld.global.ca.b64 a, [%2]; mov.b64 {%0,%1}, a;}" : "=r"(v.x), "=r"(v.y) : "l"(p) : "memory");
  return v;
}
__device__ __forceinline__ uint2 ld_ll64(const void* p) {
  uint2 v;
  asm volatile("{.reg .b64 a; ld.relaxed.gpu.global.b64 a, [%2]; mov.b64 {%0,%1}, a;}" : "=r"(v.x), "=r"(v.y) : "l"(p) : "memory");
  return v;
}
__device__ __forceinline__ void ll_chk(uint32_t& bad, uint32_t a, uint32_t b, uint32_t par) {
  uint32_t u; asm("lop3.b32 %0, %1, %2, %3, 0x7e;" : "=r"(u) : "r"(a), "r"(b), "r"(par));
  asm("or.b32 %0, %0, %1;" : "+r"(bad) : "r"(u));
}
__device__ __forceinline__ uint32_t hadd2(uint32_t a, uint32_t b) { uint32_t d; asm("add.rn.bf16x2 %0, %1, %2;" : "=r"(d) : "r"(a), "r"(b)); return d; }
__device__ __forceinline__ uint32_t hfma2(uint32_t a, uint32_t b, uint32_t c) { uint32_t d; asm("fma.rn.bf16x2 %0, %1, %2, %3;" : "=r"(d) : "r"(a), "r"(b), "r"(c)); return d; }
__device__ __forceinline__ uint32_t pack_bf16(float lo, float hi) { uint32_t r; asm("cvt.rn.bf16x2.f32 %0, %1, %2;" : "=r"(r) : "f"(hi), "f"(lo)); return r; }
__device__ __forceinline__ float bf_lo(uint32_t v) { return __uint_as_float(v << 16); }
__device__ __forceinline__ float bf_hi(uint32_t v) { return __uint_as_float(v & 0xffff0000u); }
__device__ __forceinline__ uint32_t movmat(uint32_t a) { uint32_t d; asm volatile("movmatrix.sync.aligned.m8n8.trans.b16 %0, %1;" : "=r"(d) : "r"(a)); return d; }
__device__ __forceinline__ void mma16816(float* c, uint32_t a0, uint32_t a1, uint32_t a2, uint32_t a3, uint32_t b0, uint32_t b1) {
  asm volatile("mma.sync.aligned.m16n8k16.row.col.f32.bf16.bf16.f32 {%0,%1,%2,%3}, {%4,%5,%6,%7}, {%8,%9}, {%0,%1,%2,%3};"
               : "+f"(c[0]), "+f"(c[1]), "+f"(c[2]), "+f"(c[3]) : "r"(a0), "r"(a1), "r"(a2), "r"(a3), "r"(b0), "r"(b1));
}
__device__ __forceinline__ uint4 ldcg128(const void* p) { uint4 v; asm volatile("ld.global.cg.v4.u32 {%0,%1,%2,%3}, [%4];" : "=r"(v.x), "=r"(v.y), "=r"(v.z), "=r"(v.w) : "l"(p) : "memory"); return v; }

template <int N> __device__ __forceinline__ void wgmma_ss(float* d, uint32_t alo, int aimm, uint32_t blo, int bimm, uint32_t bhi, int sc);
template <> __device__ __forceinline__ void wgmma_ss<96>(float* d, uint32_t alo, int aimm, uint32_t blo, int bimm, uint32_t bhi, int sc) {
  asm volatile("{.reg .pred p; .reg .b32 x, y; .reg .b64 da, db; setp.ne.b32 p, %53, 0; add.u32 x, %48, %49; add.u32 y, %50, %51; mov.b64 da, {x, 0x40000040}; mov.b64 db, {y, %52}; "
               "wgmma.mma_async.sync.aligned.m64n96k16.f32.bf16.bf16 {%0, %1, %2, %3, %4, %5, %6, %7, %8, %9, %10, %11, %12, %13, %14, %15, %16, %17, %18, %19, %20, %21, %22, %23, %24, %25, %26, %27, %28, %29, %30, %31, %32, %33, %34, %35, %36, %37, %38, %39, %40, %41, %42, %43, %44, %45, %46, %47}, da, db, p, 1, 1, 0, 1;}"
   : "+f"(d[0]), "+f"(d[1]), "+f"(d[2]), "+f"(d[3]), "+f"(d[4]), "+f"(d[5]), "+f"(d[6]), "+f"(d[7]), "+f"(d[8]), "+f"(d[9]), "+f"(d[10]), "+f"(d[11]), "+f"(d[12]), "+f"(d[13]), "+f"(d[14]), "+f"(d[15]), "+f"(d[16]), "+f"(d[17]), "+f"(d[18]), "+f"(d[19]), "+f"(d[20]), "+f"(d[21]), "+f"(d[22]), "+f"(d[23]), "+f"(d[24]), "+f"(d[25]), "+f"(d[26]), "+f"(d[27]), "+f"(d[28]), "+f"(d[29]), "+f"(d[30]), "+f"(d[31]), "+f"(d[32]), "+f"(d[33]), "+f"(d[34]), "+f"(d[35]), "+f"(d[36]), "+f"(d[37]), "+f"(d[38]), "+f"(d[39]), "+f"(d[40]), "+f"(d[41]), "+f"(d[42]), "+f"(d[43]), "+f"(d[44]), "+f"(d[45]), "+f"(d[46]), "+f"(d[47]) : "r"(alo), "r"(aimm), "r"(blo), "r"(bimm), "r"(bhi), "r"(sc));
}
template <> __device__ __forceinline__ void wgmma_ss<192>(float* d, uint32_t alo, int aimm, uint32_t blo, int bimm, uint32_t bhi, int sc) {
  asm volatile("{.reg .pred p; .reg .b32 x, y; .reg .b64 da, db; setp.ne.b32 p, %101, 0; add.u32 x, %96, %97; add.u32 y, %98, %99; mov.b64 da, {x, 0x40000040}; mov.b64 db, {y, %100}; "
               "wgmma.mma_async.sync.aligned.m64n192k16.f32.bf16.bf16 {%0, %1, %2, %3, %4, %5, %6, %7, %8, %9, %10, %11, %12, %13, %14, %15, %16, %17, %18, %19, %20, %21, %22, %23, %24, %25, %26, %27, %28, %29, %30, %31, %32, %33, %34, %35, %36, %37, %38, %39, %40, %41, %42, %43, %44, %45, %46, %47, %48, %49, %50, %51, %52, %53, %54, %55, %56, %57, %58, %59, %60, %61, %62, %63, %64, %65, %66, %67, %68, %69, %70, %71, %72, %73, %74, %75, %76, %77, %78, %79, %80, %81, %82, %83, %84, %85, %86, %87, %88, %89, %90, %91, %92, %93, %94, %95}, da, db, p, 1, 1, 0, 1;}"
   : "+f"(d[0]), "+f"(d[1]), "+f"(d[2]), "+f"(d[3]), "+f"(d[4]), "+f"(d[5]), "+f"(d[6]), "+f"(d[7]), "+f"(d[8]), "+f"(d[9]), "+f"(d[10]), "+f"(d[11]), "+f"(d[12]), "+f"(d[13]), "+f"(d[14]), "+f"(d[15]), "+f"(d[16]), "+f"(d[17]), "+f"(d[18]), "+f"(d[19]), "+f"(d[20]), "+f"(d[21]), "+f"(d[22]), "+f"(d[23]), "+f"(d[24]), "+f"(d[25]), "+f"(d[26]), "+f"(d[27]), "+f"(d[28]), "+f"(d[29]), "+f"(d[30]), "+f"(d[31]), "+f"(d[32]), "+f"(d[33]), "+f"(d[34]), "+f"(d[35]), "+f"(d[36]), "+f"(d[37]), "+f"(d[38]), "+f"(d[39]), "+f"(d[40]), "+f"(d[41]), "+f"(d[42]), "+f"(d[43]), "+f"(d[44]), "+f"(d[45]), "+f"(d[46]), "+f"(d[47]), "+f"(d[48]), "+f"(d[49]), "+f"(d[50]), "+f"(d[51]), "+f"(d[52]), "+f"(d[53]), "+f"(d[54]), "+f"(d[55]), "+f"(d[56]), "+f"(d[57]), "+f"(d[58]), "+f"(d[59]), "+f"(d[60]), "+f"(d[61]), "+f"(d[62]), "+f"(d[63]), "+f"(d[64]), "+f"(d[65]), "+f"(d[66]), "+f"(d[67]), "+f"(d[68]), "+f"(d[69]), "+f"(d[70]), "+f"(d[71]), "+f"(d[72]), "+f"(d[73]), "+f"(d[74]), "+f"(d[75]), "+f"(d[76]), "+f"(d[77]), "+f"(d[78]), "+f"(d[79]), "+f"(d[80]), "+f"(d[81]), "+f"(d[82]), "+f"(d[83]), "+f"(d[84]), "+f"(d[85]), "+f"(d[86]), "+f"(d[87]), "+f"(d[88]), "+f"(d[89]), "+f"(d[90]), "+f"(d[91]), "+f"(d[92]), "+f"(d[93]), "+f"(d[94]), "+f"(d[95]) : "r"(alo), "r"(aimm), "r"(blo), "r"(bimm), "r"(bhi), "r"(sc));
}

constexpr uint32_t DESC_HI = (1024u >> 4) | (1u << 30);
constexpr uint32_t DESC_HI64 = (512u >> 4) | (2u << 30);
template <int n> __device__ __forceinline__ void fence_regs(float* a) {
#pragma unroll
  for (int i = 0; i < n; i++) asm volatile("" : "+f"(a[i])::"memory");
}

struct Ctx {
  uint32_t full;
  uint32_t emb;
  bool sig;
  uint32_t phase;
  uint32_t dB, dA;
  uint32_t budget;
  __device__ __forceinline__ static int stg(int s) { return s >= 12 ? s - 12 : (s >= 6 ? s - 6 : s); }
  __device__ __forceinline__ void release(int s) { if (sig) mbar_arrive_cl(emb + 8 * stg(s)); }
  __device__ __forceinline__ void wait_full(int s) {
    asm volatile("{.reg .pred p, q; L1: mbarrier.try_wait.parity.shared::cta.b64 p, [%1], %2; @!p sub.u32 %0, %0, 1; setp.gt.and.s32 q, %0, 0, !p; @q bra L1;}"
                 : "+r"(budget) : "r"(full + 8 * stg(s)), "r"(phase ^ ((s >= 6 && s < 12) ? 1u : 0u)) : "memory");
  }
  __device__ __forceinline__ void split(int s) {
    asm volatile("{.reg .pred p; L1: mbarrier.test_wait.parity.shared::cta.b64 p, [%0], %1; setp.gt.and.s32 p, %2, 0, !p; @p bra L1;}"
                 ::"r"(full + 8 * stg(s)), "r"(phase ^ ((s >= 6 && s < 12) ? 1u : 0u)), "r"(budget) : "memory");
  }
};

__device__ __forceinline__ void issue192(float* acc, Ctx& c, int s, bool first = false, bool sp = true) {
  c.wait_full(s);
  wg_fence();
  wgmma_ss<192>(acc, c.dA, (s >> 1) * 1024 + (s & 1) * 4, c.dB, (s % 6) * (STAGE_BYTES >> 4), DESC_HI, first ? 0 : 1);
  wgmma_ss<192>(acc, c.dA, (s >> 1) * 1024 + (s & 1) * 4 + 2, c.dB, (s % 6) * (STAGE_BYTES >> 4) + 128, DESC_HI, 1);
  wg_commit();
  if (sp) c.split(s);
}
__device__ __forceinline__ void issue192r(float* acc, Ctx& c, int s, bool sp = false) {
  c.wait_full(s);
  wg_fence();
  const uint32_t db = c.dB + Ctx::stg(s) * (STAGE_BYTES >> 4);
  const uint32_t da = c.dA + (s >> 1) * 1024 + (s & 1) * 4;
  wgmma_ss<192>(acc, da, 0, db, 0, DESC_HI, 1);
  wgmma_ss<192>(acc, da, 2, db, 128, DESC_HI, 1);
  wg_commit();
  if (sp) c.split(s);
}
__device__ __forceinline__ void issue96(float* acc, Ctx& c, int k, bool first) {
  c.wait_full(k + 3);
  wg_fence();
  if (first) { wgmma_ss<192>(acc, c.dA, k * 1024, c.dB, ((k + 3) % 6) * (STAGE_BYTES >> 4), DESC_HI64, 0); wg_fence(); }
#pragma unroll
  for (int kk = first ? 1 : 0; kk < 4; kk++) wgmma_ss<96>(acc, c.dA, k * 1024 + 2 * kk, c.dB, ((k + 3) % 6) * (STAGE_BYTES >> 4) + 64 * kk, DESC_HI64, 1);
  wg_commit();
  c.split(k + 3);
}
__device__ __forceinline__ void retire(Ctx& c, int prev) {
  wg_wait<1>();
  c.release(prev);
}

constexpr float GK = 0.32920349f;
__device__ __forceinline__ uint32_t gelu_pair(uint32_t y) {
  uint32_t u, th;
  asm("mul.rn.bf16x2 %0, %1, %2;" : "=r"(u) : "r"(hfma2(y, y, 0x401b401bu)), "r"(y));
  asm("tanh.approx.bf16x2 %0, %1;" : "=r"(th) : "r"(u));
  return hfma2(y, th, y);
}
__device__ __forceinline__ uint4 gelu_group(const uint32_t* a) { return make_uint4(gelu_pair(a[0]), gelu_pair(a[1]), gelu_pair(a[2]), gelu_pair(a[3])); }
__device__ __forceinline__ void lds_bias(float2* b, uint32_t addr) {
#pragma unroll
  for (int j = 0; j < 2; j++) asm volatile("ld.shared.v2.f32 {%0,%1}, [%2];" : "=f"(b[j].x), "=f"(b[j].y) : "r"(addr + 32 * j));
}
__device__ __forceinline__ int opaque(int v) { asm volatile("" : "+r"(v)); return v; }
__device__ __forceinline__ void stsm4(uint32_t addr, uint4 r) {
  asm volatile("stmatrix.sync.aligned.m8n8.x4.shared.b16 [%0], {%1,%2,%3,%4};" ::"r"(addr), "r"(r.x), "r"(r.y), "r"(r.z), "r"(r.w) : "memory");
}
__device__ __forceinline__ float ex2f(float x) { float r; asm("ex2.approx.ftz.f32 %0, %1;" : "=f"(r) : "f"(x)); return r; }
__device__ __forceinline__ uint32_t phi2(uint32_t tp) {
  uint32_t x, y;
  const float a0 = bf_lo(tp) * 1.4426950408889634f, a1 = bf_hi(tp) * 1.4426950408889634f;
  asm("max.bf16x2 %0, %1, %2;" : "=r"(x) : "r"(tp), "r"(0x35863586u));
  asm("min.bf16x2 %0, %1, %2;" : "=r"(y) : "r"(pack_bf16(ex2f(a0), ex2f(a1))), "r"(0x3f803f80u));
  return hadd2(x, y);
}
template <int q0, int q1>
__device__ __forceinline__ void part_groups(const float* a, uint4* p, uint32_t par) {
#pragma unroll
  for (int q = q0; q < q1; q++)
    st_ll(p + q * 32, pack_bf16(a[8 * q], a[8 * q + 1]), pack_bf16(a[8 * q + 2], a[8 * q + 3]), pack_bf16(a[8 * q + 4], a[8 * q + 5]), pack_bf16(a[8 * q + 6], a[8 * q + 7]), par);
}
__device__ __forceinline__ float rcpf(float x) { float r; asm("rcp.approx.ftz.f32 %0, %1;" : "=f"(r) : "f"(x)); return r; }
__device__ __forceinline__ float silu_h(float h) { float r; asm("tanh.approx.f32 %0, %1;" : "=f"(r) : "f"(h)); return fmaf(h, r, h); }
__device__ __forceinline__ int pairoff(int p, int g) { return (p >> 2) * 32 + g * 4 + (p & 3); }
template <bool STRONG> __device__ __forceinline__ void d1_load(uint32_t* W, int rb0, int head, int ln) {
  const uint2* qf = g_qkv + rb0 * 216 * 32 + pairoff(288 + head * 9 + (ln & 3), ln >> 2);
#pragma unroll
  for (int b = 0; b < 3; b++) {
#pragma unroll
    for (int j = 0; j < 4; j++) {
      const uint2* p = qf + j * 216 * 32 + 32 * b;
      const uint2 kk = STRONG ? ld_ll64(p) : ld_ca64(p), vv = STRONG ? ld_ll64(p + 72 * 32) : ld_ca64(p + 72 * 32);
      W[6 * j + 2 * b] = kk.x; W[6 * j + 2 * b + 1] = kk.y; W[24 + 6 * j + 2 * b] = vv.x; W[24 + 6 * j + 2 * b + 1] = vv.y;
    }
  }
}
__device__ __forceinline__ bool d1_bad(const uint32_t* W, int t, uint32_t par) {
  uint32_t bad = 0, bad2 = 0;
#pragma unroll
  for (int q = 0; q < 12; q++) ll_chk((q % 3) != 2 ? bad : bad2, W[2 * q], W[24 + 2 * q], par);
  return __any_sync(0xffffffffu, (bad | (t == 0 ? bad2 : 0u)) & 1);
}
__device__ __forceinline__ void d1_mov(uint32_t* W, int j, int t) {
  if (t != 0) { W[6 * j + 4] = W[6 * j + 5] = 0u; W[24 + 6 * j + 4] = W[24 + 6 * j + 5] = (t == 1 ? 0x00003f80u : 0u); }
#pragma unroll
  for (int q = 0; q < 6; q++) { W[6 * j + q] = movmat(W[6 * j + q]); W[24 + 6 * j + q] = movmat(W[24 + 6 * j + q]); }
}
__device__ __forceinline__ void d1_mma(const uint32_t* W, float* R) {
  float c1[3][4];
#pragma unroll
  for (int j = 0; j < 12; j++) { R[j] = 0.f; c1[j >> 2][j & 3] = 0.f; }
#pragma unroll
  for (int ks = 0; ks < 4; ks++)
#pragma unroll
    for (int j = 0; j < 3; j++) {
      mma16816(R + 4 * j, W[24 + 6 * ks], W[24 + 6 * ks + 2], W[24 + 6 * ks + 1], W[24 + 6 * ks + 3], W[6 * ks + 2 * j], W[6 * ks + 2 * j + 1]);
      mma16816(c1[j], W[24 + 6 * ks + 4], 0u, W[24 + 6 * ks + 5], 0u, W[6 * ks + 2 * j], W[6 * ks + 2 * j + 1]);
    }
#pragma unroll
  for (int j = 0; j < 3; j++) { R[12 + 2 * j] = c1[j][0]; R[13 + 2 * j] = c1[j][1]; }
}
__device__ __forceinline__ bool kv_valid(int w, int ln) { return (w < 3 || ln < 12) && ((w != 2 && w != 4) || (ln & 3) == 0); }

struct Params {
  CUtensorMap tm_wqkv, tm_w1, tm_w2, tm_m, tm_wqkv64, tm_m64, tm_a, tm_ast;
  const __nv_bfloat16 *x, *b1, *b2, *wqkv, *w1, *w2, *wo;
  __nv_bfloat16* out;
};

__global__ void __cluster_dims__(2, 1, 1) __launch_bounds__(NTHREADS, 1) fused_kernel(const __grid_constant__ Params P) {
  extern __shared__ __align__(1024) uint8_t smem[];
  const uint32_t sbase = smem_u32(smem);
  const int tid = threadIdx.x, lane = tid & 31;
  const int warp = __shfl_sync(0xffffffffu, tid >> 5, 0);
  const int g = lane >> 2, t = lane & 3;
  const uint32_t ep = __shfl_sync(0xffffffffu, g_epoch[blockIdx.x], 0) + 1;
  const uint32_t par = ep & 1;
  STAMPW(0, 0);

  if (blockIdx.x >= 128) {
    const int a = blockIdx.x - 128;
    constexpr int WP = 1168, SM_T = 152 * WP, SM_HB = SM_T + 8 * 32 * 80;
    if (tid == 0) {
      mbar_init(sbase + SM_HB, 1);
      asm volatile("fence.mbarrier_init.release.cluster;" ::: "memory");
      mbar_expect(sbase + SM_HB, 144 * 1152);
    }
    for (int i = tid; i < (8 * WP + 8 * 32 * 80) / 4; i += NTHREADS) reinterpret_cast<uint32_t*>(smem + 144 * WP)[i] = 0u;
    __syncthreads();
    __nanosleep(1500);
    if (tid < 144)
      asm volatile("cp.async.bulk.shared::cluster.global.mbarrier::complete_tx::bytes [%0], [%1], %2, [%3];" ::"r"(sbase + tid * WP), "l"(P.wo + (a * 144 + tid) * D_), "r"(1152), "r"(sbase + SM_HB) : "memory");
    if (warp >= 8 && lane == 0) {
      const int id = a * 4 + (warp - 8);
      constexpr uint32_t CH = 9216 * 2;
#pragma unroll 1
      for (int i = id; i < 576; i += 16) {
        const char* p = i < 288 ? (const char*)P.w1 + (size_t)i * CH : (const char*)P.w2 + (size_t)(i - 288) * CH;
        asm volatile("cp.async.bulk.prefetch.L2.global [%0], %1;" ::"l"(p), "r"(CH) : "memory");
      }
    }
    __syncwarp();
    if (lane < 8) hint_wait(&g_f_kvp[a * 8 + lane], 16 * ep, 50);
    __syncwarp();
    STAMPW(0, 1);
#pragma unroll 1
    for (int u = warp; u < 40; u += 12) {
      const int hh = u & 7, w = 4 - (u >> 3), head = a * 8 + hh;
      uint4 v[16];
      int tries = 0;
      uint32_t bad;
      const bool val = kv_valid(w, lane);
#pragma unroll 1
      do {
        bad = 0;
#pragma unroll
        for (int j = 0; j < 16; j++) v[j] = val ? ld_ll(&g_kvp[((head * 5 + w) * 16 + j) * 32 + lane]) : make_uint4(par, 0u, par, 0u);
#pragma unroll
        for (int j = 0; j < 16; j++) ll_chk(bad, v[j].x, v[j].z, par);
      } while (__any_sync(0xffffffffu, bad & 1) && ++tries < (1 << 20));
      float s0 = 0.f, s1 = 0.f, s2 = 0.f, s3 = 0.f;
#pragma unroll
      for (int j = 0; j < 16; j++) { s0 += __uint_as_float(v[j].x); s1 += __uint_as_float(v[j].y); s2 += __uint_as_float(v[j].z); s3 += __uint_as_float(v[j].w); }
      if (w >= 3) {
        if (g == 2) st_ll(&g_z[(head * 2 + w - 3) * 4 + t], __float_as_uint(s0), __float_as_uint(s1), __float_as_uint(s2), __float_as_uint(s3), par);
        __syncwarp();
        hint_signal(&g_f_z[head]);
      }
      const int e0 = w < 3 ? g : 16 + g, e1 = w < 3 ? g + 8 : 16 + g, d0 = (w < 3 ? 8 * w : (w == 3 ? 0 : 16)) + 2 * t, d1 = w < 3 ? d0 : d0 + 8;
      __nv_bfloat16* T = reinterpret_cast<__nv_bfloat16*>(smem + SM_T) + hh * 32 * 40;
      if (e0 < 18) {
        T[d0 * 40 + e0] = __float2bfloat16(s0); T[(d0 + 1) * 40 + e0] = __float2bfloat16(s1);
        T[d1 * 40 + e1] = __float2bfloat16(s2); T[(d1 + 1) * 40 + e1] = __float2bfloat16(s3);
      }
    }
    __syncthreads();
    STAMPW(0, 2);
    mbar_wait(sbase + SM_HB, 0);
#pragma unroll 1
    for (int u = warp; u < 24; u += 12) {
      const int hh = u / 3, c0 = (u % 3) * 192;
      const uint32_t* T = reinterpret_cast<const uint32_t*>(smem + SM_T) + hh * 32 * 20 + g * 20 + t;
      const uint32_t a00 = T[0], a01 = T[160], a02 = T[4], a03 = T[164], a10 = T[8], a11 = T[168], b00 = T[320], b02 = T[324], b10 = T[328];
      const uint32_t rowa = sbase + (hh * 18 + (lane & 15)) * WP + (c0 + (lane >> 4) * 8) * 2, rowb = sbase + (hh * 18 + 16 + (lane & 7)) * WP + (c0 + ((lane >> 3) & 1) * 8) * 2;
#pragma unroll 3
      for (int j = 0; j < 12; j++) {
        uint32_t w0, w1, w2, w3, w4, w5;
        asm volatile("ldmatrix.sync.aligned.m8n8.x4.trans.shared.b16 {%0,%1,%2,%3}, [%4];" : "=r"(w0), "=r"(w1), "=r"(w2), "=r"(w3) : "r"(rowa + j * 32));
        asm volatile("ldmatrix.sync.aligned.m8n8.x2.trans.shared.b16 {%0,%1}, [%2];" : "=r"(w4), "=r"(w5) : "r"(rowb + j * 32));
        float p[4][4];
#pragma unroll
        for (int q = 0; q < 4; q++) p[q][0] = p[q][1] = p[q][2] = p[q][3] = 0.f;
        mma16816(p[0], a00, a01, a02, a03, w0, w1); mma16816(p[1], a00, a01, a02, a03, w2, w3);
        mma16816(p[2], b00, 0u, b02, 0u, w0, w1); mma16816(p[3], b00, 0u, b02, 0u, w2, w3);
        mma16816(p[0], a10, a11, 0u, 0u, w4, 0u); mma16816(p[1], a10, a11, 0u, 0u, w5, 0u);
        mma16816(p[2], b10, 0u, 0u, 0u, w4, 0u); mma16816(p[3], b10, 0u, 0u, 0u, w5, 0u);
        stsm4(rowa + j * 32, make_uint4(pack_bf16(p[0][0], p[0][1]), pack_bf16(p[0][2], p[0][3]), pack_bf16(p[1][0], p[1][1]), pack_bf16(p[1][2], p[1][3])));
        if (g < 2) {
          uint32_t* r = reinterpret_cast<uint32_t*>(smem + (hh * 18 + 16 + g) * WP + (c0 + j * 16 + 2 * t) * 2);
          r[0] = pack_bf16(p[2][0], p[2][1]); r[4] = pack_bf16(p[3][0], p[3][1]);
        }
      }
      asm volatile("fence.proxy.async.shared::cta;" ::: "memory");
      __syncwarp();
      if (lane < 18) {
        asm volatile("cp.async.bulk.global.shared::cta.bulk_group [%0], [%1], %2;" ::"l"(g_m + (a * 144 + hh * 18 + lane) * D_ + c0), "r"(sbase + (hh * 18 + lane) * WP + c0 * 2), "r"(384) : "memory");
        asm volatile("cp.async.bulk.commit_group;" ::: "memory");
      }
    }
    asm volatile("cp.async.bulk.wait_group 0;" ::: "memory");
    asm volatile("fence.proxy.async.global;" ::: "memory");
    __syncwarp();
    if (lane == 0) asm volatile("red.release.gpu.global.add.u32 [%0], 1;" ::"l"(g_f_m) : "memory");
    STAMPW(0, 3);
    __syncthreads();
    if (tid == 0) g_epoch[blockIdx.x] = ep;
    return;
  }

  const int cl = blockIdx.x >> 1, rank = blockIdx.x & 1;
  const int f = cl & 7, m = (cl >> 3) * 2 + rank;
  const int srole = f >= 6 ? 1 : 0;
  const uint32_t bar_full = sbase + SM_BAR, bar_empty = bar_full + 8 * NSTAGE, bar_xfree = bar_empty + 8 * NSTAGE, bar_ofull = bar_xfree + 72,
                 bar_d = bar_ofull + 72;

  if (tid == 0) {
#pragma unroll 1
    for (int i = 0; i < NSTAGE; i++) { mbar_init(bar_full + 8 * i, 1); mbar_init(bar_empty + 8 * i, 4); }
#pragma unroll 1
    for (int i = 0; i < 9; i++) { mbar_init(bar_xfree + 8 * i, 2); mbar_init(bar_ofull + 8 * i, 1); }
    mbar_init(bar_d, 1);
    asm volatile("fence.mbarrier_init.release.cluster;" ::: "memory");
  }
  __syncwarp();
  cluster_arrive_relaxed();

  if (warp >= 8) {
    const int srow = m * 128 + f * 16 + (warp - 8) * 4 + (lane >> 3);
    uint4 xs[9];
#pragma unroll
    for (int kb = 0; kb < 9; kb++) xs[kb] = __ldg(reinterpret_cast<const uint4*>(P.x + srow * D_) + (lane & 7) + kb * 8);
    auto stats = [&]() {
      const uint32_t* w = reinterpret_cast<const uint32_t*>(xs);
      float s0 = 0.f, s1 = 0.f;
#pragma unroll
      for (int i = 0; i < 36; i++) { s0 += bf_lo(w[i]); s1 += bf_hi(w[i]); }
      float sum = s0 + s1;
      sum += __shfl_xor_sync(0xffffffffu, sum, 1); sum += __shfl_xor_sync(0xffffffffu, sum, 2); sum += __shfl_xor_sync(0xffffffffu, sum, 4);
      const float mean = sum * (1.f / 576.f);
      s0 = 0.f; s1 = 0.f;
#pragma unroll
      for (int i = 0; i < 36; i++) { const float a = bf_lo(w[i]) - mean, b = bf_hi(w[i]) - mean; s0 = fmaf(a, a, s0); s1 = fmaf(b, b, s1); }
      float sq = s0 + s1;
      sq += __shfl_xor_sync(0xffffffffu, sq, 1); sq += __shfl_xor_sync(0xffffffffu, sq, 2); sq += __shfl_xor_sync(0xffffffffu, sq, 4);
      const float rstd = rsqrtf(sq * (1.f / 576.f) + 1e-5f);
      if ((lane & 7) == 0)
        st_ll64(&g_stat[srow], __float_as_uint(rstd), pack_bf16(-mean, -mean), par);
    };
    stats();
    asm volatile("setmaxnreg.dec.sync.aligned.u32 40;");
    cluster_wait();
    if (warp == 8) {
      if (lane == 0) {
        uint32_t stage = 0, phase = 1;
        const uint32_t sb = sbase + SM_B;
#pragma unroll 1
        for (int tl = 2 * srole; tl < 8 + 2 * srole; tl++) {
          const CUtensorMap* map = tl == 0 ? &P.tm_wqkv : (tl == 1 ? &P.tm_wqkv64 : (tl < 5 ? &P.tm_w1 : (tl < 8 ? &P.tm_w2 : (tl == 8 ? &P.tm_m : &P.tm_m64))));
          const int col = tl < 2 ? 288 * f + 192 * tl : (tl < 5 ? 576 * f + 192 * (tl - 2) : (tl < 8 ? 192 * ((tl - 5 + f) % 3) : (tl == 8 ? 192 * (f - 5) : 96 * (f - 6))));
          const bool perm = tl >= 5 && tl < 8;
          const bool z = (tl & 7) == 1;
          if (tl == 8) { flag_wait(g_f_m, 48 * ep); asm volatile("fence.proxy.async.global;" ::: "memory"); }
          const int cs = z ? 32 : 64, rs = z ? 64 : 32, nst = z ? 9 : 18;
#pragma unroll 1
          for (int st = z ? -3 : 0; st < nst; st++) {
            if (st < 0) {
              mbar_wait(bar_empty + 8 * stage, phase);
              mbar_arrive(bar_full + 8 * stage);
              ++stage;
              continue;
            }
            int row = st * rs;
            if (perm) row += 576 * f + ((st < 6) ? 192 : (st < 12 ? -192 : 0));
            mbar_wait(bar_empty + 8 * stage, phase);
            mbar_expect(bar_full + 8 * stage, 12288);
            const uint32_t dst = sb + stage * STAGE_BYTES;
            if (((st ^ rank) & 1) == 0) {
              tma2d_mc(dst, map, col, row, bar_full + 8 * stage);
              tma2d_mc(dst + 8192, map, col + 2 * cs, row, bar_full + 8 * stage);
            } else {
              tma2d_mc(dst + 4096, map, col + cs, row, bar_full + 8 * stage);
            }
            if (++stage == NSTAGE) { stage = 0; phase ^= 1; }
          }
        }
      }
      __syncwarp();
    } else {
      const int aw = warp - 9;
      const int hi = f >> 2;
      if (aw == 0) {
        if (lane < 2) hint_wait(&g_f_qkv[m * 8 + 2 + 2 * lane + hi], 16 * ep, 200);
        __syncwarp();
        if (lane == 0) mbar_arrive(bar_d);
        STAMP(20);
      }
      if (lane < 5) hint_wait(lane < 4 ? &g_f_z[4 * f + lane] : &g_f_qkv[m * 8 + hi], lane < 4 ? 2 * ep : 16 * ep);
      __syncwarp();
      STAMPW(9, 22);
      uint32_t* stg = reinterpret_cast<uint32_t*>(smem + SM_SCR + aw * 2304);
#pragma unroll 1
      for (int u = aw * 2; u < 16; u += (u & 1) ? 5 : 1) {
        const int rbl = u >> 1, hp = (u & 1) * 2;
        const uint2* qf = g_qkv + (m * 8 + rbl) * 216 * 32;
        const uint2* zp = reinterpret_cast<const uint2*>(&g_z[(4 * f + hp) * 8 + t]);
        uint2 q[2][3];
        float d[4];
        int tries = 0;
        uint32_t bad;
#pragma unroll 1
        do {
          bad = tries ? ld_acquire(g_f_m) & 0u : 0u;
#pragma unroll
          for (int j = 0; j < 2; j++)
#pragma unroll
            for (int b = 0; b < 3; b++) q[j][b] = ld_ca64(qf + pairoff((4 * f + hp + j) * 9 + t, g) + 32 * b);
#pragma unroll
          for (int j = 0; j < 2; j++) {
            const uint2 z0 = ld_ca64(zp + 16 * j), z1 = ld_ca64(zp + 16 * j + 1), z2 = ld_ca64(zp + 16 * j + 8);
            if (t != 0) q[j][2] = make_uint2(par, 0u);
            ll_chk(bad, z0.x, z1.x, par); ll_chk(bad, z2.x, q[j][2].x, par); ll_chk(bad, q[j][0].x, q[j][1].x, par);
            d[2 * j] = bf_lo(q[j][0].x) * __uint_as_float(z0.x) + bf_hi(q[j][0].x) * __uint_as_float(z0.y) + bf_lo(q[j][1].x) * __uint_as_float(z1.x) + bf_hi(q[j][1].x) * __uint_as_float(z1.y) +
                       bf_lo(q[j][2].x) * __uint_as_float(z2.x) + bf_hi(q[j][2].x) * __uint_as_float(z2.y);
            d[2 * j + 1] = bf_lo(q[j][0].y) * __uint_as_float(z0.x) + bf_hi(q[j][0].y) * __uint_as_float(z0.y) + bf_lo(q[j][1].y) * __uint_as_float(z1.x) + bf_hi(q[j][1].y) * __uint_as_float(z1.y) +
                           bf_lo(q[j][2].y) * __uint_as_float(z2.x) + bf_hi(q[j][2].y) * __uint_as_float(z2.y);
          }
        } while (__any_sync(0xffffffffu, bad & 1) && ++tries < (1 << 20));
#pragma unroll
        for (int j = 0; j < 4; j++) d[j] += __shfl_xor_sync(0xffffffffu, d[j], 1);
#pragma unroll
        for (int j = 0; j < 4; j++) d[j] = rcpf(d[j] + __shfl_xor_sync(0xffffffffu, d[j], 2) + 1e-6f);
        if (hp == 0) { asm volatile("cp.async.bulk.wait_group.read 0;" ::: "memory"); __syncwarp(); }
#pragma unroll
        for (int j = 0; j < 2; j++) {
          const uint32_t r0 = pack_bf16(d[2 * j], d[2 * j]), r1 = pack_bf16(d[2 * j + 1], d[2 * j + 1]);
#pragma unroll
          for (int b = 0; b < 3; b++)
            if (b < 2 || t == 0) {
              stg[g * 36 + (hp + j) * 9 + 4 * b + t] = hfma2(q[j][b].x, r0, 0x80008000u);
              stg[(g + 8) * 36 + (hp + j) * 9 + 4 * b + t] = hfma2(q[j][b].y, r1, 0x80008000u);
            }
        }
        if (hp != 0) {
          asm volatile("fence.proxy.async.shared::cta;" ::: "memory");
          __syncwarp();
          if (lane == 0) {
            asm volatile("cp.async.bulk.tensor.2d.global.shared::cta.bulk_group [%0, {%2, %3}], [%1];" ::"l"(&P.tm_ast), "r"(smem_u32(stg)), "r"(72 * f), "r"(m * 128 + rbl * 16) : "memory");
            asm volatile("cp.async.bulk.commit_group;" ::: "memory");
          }
        }
      }
      asm volatile("cp.async.bulk.wait_group 0;" ::: "memory");
      asm volatile("fence.proxy.async.global;" ::: "memory");
      STAMPW(9, 26);
      asm volatile("bar.sync 5, 96;" ::: "memory");
      if (tid == 288) asm volatile("red.release.gpu.global.add.u32 [%0], 1;" ::"l"(&g_f_a[m]) : "memory");
      __syncwarp();
      STAMPW(9, 23);
      if (srole && aw == 2) {
        if (lane == 0) {
          flag_wait(&g_f_a[m], 8 * ep);
          asm volatile("fence.proxy.async.global;" ::: "memory");
#pragma unroll 1
          for (int kb = 0; kb < 9; kb++) {
            mbar_wait(bar_xfree + 8 * kb, 0);
            mbar_expect(bar_ofull + 8 * kb, 16384);
            tma2d(sbase + SM_A + kb * 16384, &P.tm_a, kb * 64, m * 128, bar_ofull + 8 * kb);
          }
        }
        __syncwarp();
      }
    }
    cluster_arrive_relaxed();
    cluster_wait();
  } else {
    const int wg = warp >> 2;
    {
      const int rs = lane >> 3, j = lane & 7;
      uint4 xv[4][9];
#pragma unroll
      for (int it = 0; it < 4; it++)
#pragma unroll
        for (int kb = 0; kb < 9; kb++) xv[it][kb] = __ldg(reinterpret_cast<const uint4*>(P.x + (m * 128 + warp * 16 + it * 4 + rs) * D_) + j + kb * 8);
      uint32_t bw0 = __ldg(reinterpret_cast<const uint32_t*>(P.b1 + 576 * f) + tid), bw1 = tid < 32 ? __ldg(reinterpret_cast<const uint32_t*>(P.b1 + 576 * f) + 256 + tid) : 0u;
      uint2 st[4];
      int tries = 0;
      uint32_t bad;
#pragma unroll 1
      do {
        bad = 0;
#pragma unroll
        for (int it = 0; it < 4; it++) st[it] = ld_ll64(&g_stat[m * 128 + warp * 16 + it * 4 + rs]);
        ll_chk(bad, st[0].x, st[1].x, par); ll_chk(bad, st[2].x, st[3].x, par);
      } while (__any_sync(0xffffffffu, bad & 1) && ++tries < (1 << 22));
      STAMPW(0, 19);
#pragma unroll
      for (int it = 0; it < 4; it++) {
        const uint32_t nm = st[it].y;
        uint8_t* dst = smem + SM_A + (warp * 16 + it * 4 + rs) * 128 + ((j ^ ((it * 4 + rs) & 7)) << 4);
#pragma unroll
        for (int kb = 0; kb < 9; kb++) {
          const uint4 w = xv[it][kb];
          *reinterpret_cast<uint4*>(dst + kb * 16384) = make_uint4(hadd2(w.x, nm), hadd2(w.y, nm), hadd2(w.z, nm), hadd2(w.w, nm));
        }
        if (j == 0) reinterpret_cast<uint32_t*>(smem + SM_RSTD)[warp * 16 + it * 4 + rs] = st[it].x;
      }
      reinterpret_cast<float2*>(smem + SM_BIAS)[tid] = make_float2(bf_lo(bw0) * GK, bf_hi(bw0) * GK);
      if (tid < 48) reinterpret_cast<float2*>(smem + SM_BIAS)[256 + tid] = make_float2(bf_lo(bw1) * GK, bf_hi(bw1) * GK);
      asm volatile("fence.proxy.async.shared::cta;" ::: "memory");
    }
    asm volatile("setmaxnreg.inc.sync.aligned.u32 232;");
    cluster_wait();
    asm volatile("bar.sync 1, 256;" ::: "memory");
    STAMPW(0, 1);
    Ctx c;
    c.full = bar_full;
    c.emb = __shfl_sync(0xffffffffu, mapa(bar_empty, (warp & 3) == 0 ? rank : (rank ^ 1)), 0);
    c.sig = lane == 0 && (warp & 3) < 2;
    c.phase = 0; c.budget = 1 << 22;
    c.dB = (((sbase + SM_B) & 0x3FFFF) >> 4) | ((4096u >> 4) << 16);
    c.dA = (((sbase + SM_A + wg * 8192) & 0x3FFFF) >> 4) | (1u << 16);
    const bool leader = (lane == 0) && ((warp & 3) == 0);

    const int rb = m * 8 + warp;
    const uint32_t bias_t = sbase + SM_BIAS + 8 * t;
    const uint32_t hst = sbase + SM_A + (warp * 16 + (lane & 7) + ((lane >> 3) & 1) * 8) * 128 + (((lane >> 4) ^ (lane & 7)) << 4);
    auto wg_sync = [&]() {
      asm volatile("fence.proxy.async.shared::cta;" ::: "memory");
      if (wg == 0) asm volatile("bar.sync 2, 128;" ::: "memory"); else asm volatile("bar.sync 3, 128;" ::: "memory");
    };
    float A[96], B[96];
#pragma unroll
    for (int i = 0; i < 96; i++) B[i] = 0.f;
#define EXB(ACC, U) uint32_t E[4]; _Pragma("unroll") for (int q = 0; q < 4; q++) E[q] = pack_bf16(fmaf(ACC[8 * (U) + 2 * q], (q & 1) ? r1 : r0, bs[q >> 1].x), fmaf(ACC[8 * (U) + 2 * q + 1], (q & 1) ? r1 : r0, bs[q >> 1].y));
#define ST_QKV(ACC, U, DST) { uint32_t E[4]; _Pragma("unroll") for (int q = 0; q < 4; q++) { const uint32_t e = pack_bf16(ACC[8 * (U) + 2 * q] * ((q & 1) ? r1 : r0), ACC[8 * (U) + 2 * q + 1] * ((q & 1) ? r1 : r0)), ph = phi2(e); E[q] = f < 4 ? ph : e; } \
    st_ll64(reinterpret_cast<uint2*>(DST) + 64 * (U), E[0], E[1], par); st_ll64(reinterpret_cast<uint2*>(DST) + 64 * (U) + 32, E[2], E[3], par); }
#define HADDR(KB0, U) ((hst ^ (((U) & 3) << 5)) + ((KB0) + ((U) >> 2)) * 16384)
#define LDS_R(SC) float r0, r1; asm volatile("ld.shared.f32 %0, [%1];" : "=f"(r0) : "r"(rst)); asm volatile("ld.shared.f32 %0, [%1];" : "=f"(r1) : "r"(rst + 32)); r0 *= (SC); r1 *= (SC);
    const uint32_t rst = sbase + SM_RSTD + (warp * 16 + g) * 4;
    const int fr = f % 3;
#pragma unroll 1
    for (int i = srole;; i++) {
      {
        const uint32_t ow = i == 4 ? bar_ofull : 0u;
        if (ow) mbar_wait(ow, 0);
        issue192(A, c, 0, true);
        const int ln = opaque(lane);
        uint4* dst = i == 1 ? reinterpret_cast<uint4*>(g_qkv + (rb * 216 + 36 * f + 24) * 32 + ln) : g_part + ((rb * 8 + f) * 36 + 12 * (i == 3 ? fr : (fr + 2) % 3)) * 32 + ln;
        LDS_R(i == 2 ? GK : 1.f)
        wg_wait<1>();
        if (i != srole) c.release(5);
        if (ow && leader) mbar_arrive(bar_xfree + 64);
        fence_regs<96>(B);
        int s = 1;
        if (i == 2) {
#pragma unroll
          for (int k = 1; k < 9; k++) {
            float2 b0[2], b1[2];
            if (k >= 3) { lds_bias(b0, bias_t + (192 + 32 * (k - 3)) * 4); lds_bias(b1, bias_t + (208 + 32 * (k - 3)) * 4); }
            issue192(A, c, k);
            if (k >= 3) {
              const int u = k >= 3 ? 2 * (k - 3) : 0;
              { const float2* bs = b0; EXB(B, u) stsm4(HADDR(0, u), gelu_group(E)); }
              { const float2* bs = b1; EXB(B, u + 1) stsm4(HADDR(0, u + 1), gelu_group(E)); }
            }
            retire(c, k - 1);
          }
          s = 9;
        } else if (i >= 3) {
#pragma unroll
          for (int u = 0; u < 12; u++) {
            if ((u & 1) && ow) mbar_wait(ow + 4 * (u + 1), 0);
            issue192(A, c, u + 1);
            part_groups<0, 1>(&B[8 * u], dst + u * 32, par);
            retire(c, u);
          }
          s = 13;
        } else if (i > srole) {
#pragma unroll
          for (int u = 0; u < 6; u++) {
            issue192(A, c, u + 1);
            ST_QKV(B, u, dst)
            retire(c, u);
          }
          hint_signal(&g_f_qkv[m * 8 + f]);
          s = 7;
        }
        const bool d1 = i == 1 + srole;
        const int send = d1 ? 11 : 15;
#pragma unroll 1
        for (; s < send; s++) {
          if (ow && !(s & 1)) mbar_wait(ow + 4 * s, 0);
          issue192r(A, c, s);
          retire(c, s - 1);
        }
        uint32_t W[48];
        if (d1) {
          const int head = 4 * f + (warp >> 1), rb0 = m * 8 + (warp & 1) * 4;
          issue192(A, c, 11);
          mbar_wait(bar_d, 0);
          d1_load<false>(W, rb0, head, opaque(lane));
          retire(c, 10);
          issue192(A, c, 12, false, false);
          retire(c, 11);
          issue192(A, c, 13);
          int tries = 0;
#pragma unroll 1
          while (d1_bad(W, t, par) && ++tries < (1 << 20)) d1_load<true>(W, rb0, head, opaque(lane));
          d1_mov(W, 0, t); d1_mov(W, 1, t);
          retire(c, 12);
          issue192(A, c, 14);
          d1_mov(W, 2, t); d1_mov(W, 3, t);
          wg_wait<0>();
          asm volatile("bar.sync 4, 256;" ::: "memory");
          float R[18];
          d1_mma(W, R);
          float2* xch = reinterpret_cast<float2*>(smem + SM_SCR + (warp >> 1) * 1792) + opaque(lane);
          if (warp & 1) {
#pragma unroll
            for (int q = 0; q < 6; q++) xch[q * 32] = make_float2(R[2 * q], R[2 * q + 1]);
            if (lane < 12) { xch[192] = make_float2(R[12], R[13]); xch[204] = make_float2(R[14], R[15]); if (t == 0) xch[216 - lane + g] = make_float2(R[16], R[17]); }
          } else if (R[17] == 1.2345e-30f) R[16] = 0.f;
          asm volatile("bar.sync 4, 256;" ::: "memory");
          retire(c, 13);
          issue192(A, c, 15);
          if (!(warp & 1)) {
            const int l2 = opaque(lane);
#pragma unroll
            for (int q = 0; q < 6; q++) { const float2 o = xch[q * 32]; R[2 * q] += o.x; R[2 * q + 1] += o.y; }
            if (l2 < 12) {
              const float2 o0 = xch[192], o1 = xch[204], o2 = xch[216 - l2 + (l2 >> 2)];
              R[12] += o0.x; R[13] += o0.y; R[14] += o1.x; R[15] += o1.y; R[16] += o2.x; R[17] += o2.y;
            }
            uint4* dkv = &g_kvp[(head * 80 + m) * 32 + l2];
#pragma unroll
            for (int w = 0; w < 5; w++)
              if (kv_valid(w, l2)) st_ll(dkv + w * 512, __float_as_uint(R[4 * w]), __float_as_uint(R[4 * w + 1]), w < 4 ? __float_as_uint(R[4 * w + 2]) : 0u, w < 4 ? __float_as_uint(R[4 * w + 3]) : 0u, par);
            __syncwarp();
            hint_signal(&g_f_kvp[head]);
          }
          STAMPW(0, 21);
        } else issue192(A, c, 15);
        if (i == 2) {
          const uint4* hsp = g_hsp + (blockIdx.x * 8 + warp) * 12 * 32 + opaque(lane);
#pragma unroll
          for (int q = 0; q < 12; q++) { const uint4 v = ldcg128(hsp + q * 32); W[4 * q] = v.x; W[4 * q + 1] = v.y; W[4 * q + 2] = v.z; W[4 * q + 3] = v.w; }
          retire(c, 14);
          issue192(A, c, 16, false, false);
          wg_sync();
          retire(c, 15);
          issue192(A, c, 17, false, false);
#pragma unroll
          for (int q = 0; q < 12; q++) stsm4(HADDR(3, q), make_uint4(W[4 * q], W[4 * q + 1], W[4 * q + 2], W[4 * q + 3]));
        } else {
          retire(c, 14);
          if (ow) mbar_wait(ow + 64, 0);
          issue192(A, c, 16, false, false);
          retire(c, 15);
          issue192(A, c, 17, false, false);
        }
        retire(c, 16);
        c.phase ^= 1;
      }
      STAMPW(0, 2 + 2 * i);
      if ((i & 3) == 0) {
#pragma unroll
        for (int k = 0; k < 3; k++) { c.wait_full(k); c.release(k); }
        issue96(B, c, 0, true);
        const int ln = opaque(lane);
        uint4* dst = i == 0 ? reinterpret_cast<uint4*>(g_qkv + (rb * 216 + 36 * f) * 32 + ln) : g_s + (rb * 36 + 12 * (f - 5)) * 32 + ln;
        LDS_R(1.f)
        retire(c, 5);
        fence_regs<96>(A);
        if (i == 0) {
#pragma unroll
          for (int k = 1; k < 9; k++) {
            issue96(B, c, k, false);
#pragma unroll
            for (int u = (3 * (k - 1) + 1) / 2; u < (3 * k + 1) / 2; u++) ST_QKV(A, u, dst)
            if (k == 8) hint_signal(&g_f_qkv[m * 8 + f]);
            retire(c, k + 2);
          }
        } else {
#pragma unroll
          for (int k = 1; k < 9; k++) {
            issue96(B, c, k, false);
            if (k < 7) part_groups<0, 2>(&A[16 * (k < 7 ? k - 1 : 0)], dst + 2 * (k - 1) * 32, par);
            retire(c, k + 2);
          }
          STAMPW(0, 11);
          wg_wait<0>();
          c.release(11);
          fence_regs<48>(B);
          part_groups<0, 6>(B, g_s + (rb * 36 + 6 * (f - 6)) * 32 + opaque(lane), par);
          break;
        }
      } else {
        issue192(B, c, 0, true);
        const int ln = opaque(lane);
        uint4* dst = i == 1 ? g_hsp + (blockIdx.x * 8 + warp) * 12 * 32 + ln : g_part + ((rb * 8 + f) * 36 + 12 * ((fr + 1) % 3)) * 32 + ln;
        const bool xf = i == 3 && srole && leader;
        const uint32_t bsa = bias_t + (i == 1 ? 0 : 384) * 4;
        LDS_R(GK)
        retire(c, 5);
        fence_regs<96>(A);
        int s;
        if (i != 3) {
#pragma unroll
          for (int u = 0; u < 12; u++) {
            float2 bs[2];
            lds_bias(bs, bsa + 16 * u * 4);
            issue192(B, c, u + 1);
            EXB(A, u)
            const uint4 h = gelu_group(E);
            asm volatile("{.reg .pred p; setp.eq.s32 p, %6, 1; @p st.global.v4.u32 [%0], {%2,%3,%4,%5}; @!p stmatrix.sync.aligned.m8n8.x4.shared.b16 [%1], {%2,%3,%4,%5};}"
                         ::"l"(dst + u * 32), "r"(HADDR(6, u)), "r"(h.x), "r"(h.y), "r"(h.z), "r"(h.w), "r"(i) : "memory");
            if (u == 3 || u == 9) wg_sync();
            retire(c, u);
          }
          s = 13;
        } else {
#pragma unroll
          for (int u = 0; u < 6; u++) {
            issue192(B, c, u + 1);
            part_groups<0, 2>(&A[16 * u], dst + 2 * u * 32, par);
            retire(c, u);
            if ((u & 1) && xf) mbar_arrive(bar_xfree + 4 * u - 4);
          }
          s = 7;
        }
        if (i == 3 && !srole) {
          const int c2 = (fr + 2) % 3, v0 = 12 * c2 + (f < 3 ? 0 : 6), fo = f < 3 ? f + 3 : f - 3;
          const int l2 = opaque(lane);
          const uint4* pb = g_part + (rb * 8 * 36 + v0) * 32 + l2;
          uint4 p[12];
          uint32_t S[24];
#pragma unroll
          for (int q = 0; q < 24; q++) S[q] = 0u;
          auto ldp = [&](const uint4* a0, const uint4* a1) {
#pragma unroll
            for (int q = 0; q < 6; q++) { p[q] = ld_ll(a0 + q * 32); p[6 + q] = ld_ll(a1 + q * 32); }
          };
          auto badp = [&]() {
            uint32_t bad = 0;
#pragma unroll
            for (int q = 0; q < 12; q++) ll_chk(bad, p[q].x, p[q].z, par);
            return __any_sync(0xffffffffu, bad & 1);
          };
#pragma unroll 1
          for (int w = 0; w < 3; w++) {
            const uint4* a0 = pb + (w == 0 ? c2 : (w == 1 ? 6 : (fr + 1) % 3)) * 36 * 32;
            const uint4* a1 = a0 + (w == 1 ? 1 : 3) * 36 * 32;
            issue192r(B, c, 7 + 3 * w, true);
            ldp(a0, a1);
            retire(c, 6 + 3 * w);
            issue192r(B, c, 8 + 3 * w);
            retire(c, 7 + 3 * w);
            issue192r(B, c, 9 + 3 * w, true);
            int tries = 0;
#pragma unroll 1
            while (badp() && ++tries < (1 << 20)) ldp(a0, a1);
#pragma unroll
            for (int q = 0; q < 24; q++) S[q] = hadd2(S[q], hadd2(reinterpret_cast<const uint32_t*>(p)[q], reinterpret_cast<const uint32_t*>(p)[24 + q]));
            retire(c, 8 + 3 * w);
          }
          uint4 xx[6];
          uint32_t bb[12];
          int ro[6];
          issue192(B, c, 16);
#pragma unroll
          for (int j = 0; j < 6; j++) {
            const int k = l2 + 32 * j, r = (k * 171) >> 11;
            ro[j] = (rb * 16 + r) * D_ + 16 * v0 + (k - 12 * r) * 8;
            xx[j] = __ldg(reinterpret_cast<const uint4*>(P.x + ro[j]));
          }
#pragma unroll
          for (int j = 0; j < 12; j++) bb[j] = __ldg(reinterpret_cast<const uint32_t*>(P.b2 + 16 * v0 + 8 * j + 2 * (l2 & 3)));
          retire(c, 15);
          issue192(B, c, 17, false, false);
          retire(c, 16);
          STAMPW(0, 9);
          wg_wait<0>();
          c.release(17);
          fence_regs<96>(B);
          uint4* snd = g_part + ((rb * 8 + f) * 36 + 12 * c2 + (f < 3 ? 6 : 0)) * 32 + l2;
          if (f < 3) part_groups<0, 6>(B + 48, snd, par);
          else {
            part_groups<0, 6>(B, snd, par);
#pragma unroll
            for (int q = 0; q < 48; q++) B[q] = B[48 + q];
          }
          asm volatile("bar.sync 4, 256;" ::: "memory");
          STAMPW(0, 12);
#pragma unroll
          for (int q = 0; q < 24; q++) {
            B[2 * q] = fmaf(B[2 * q] + bf_lo(S[q]), 0.25f / GK, 0.5f * bf_lo(bb[q >> 1])); B[2 * q + 1] = fmaf(B[2 * q + 1] + bf_hi(S[q]), 0.25f / GK, 0.5f * bf_hi(bb[q >> 1]));
          }
          const uint4* sp = g_s + (rb * 36 + v0) * 32 + l2;
          int tries = 0;
#pragma unroll 1
          while (++tries < (1 << 20)) {
            const uint2 u0 = ld_ll64(pb + (fo * 36 + 5) * 32), u1 = ld_ll64(sp + 5 * 32);
            if (!__any_sync(0xffffffffu, ((u0.x ^ par) | (u1.x ^ par)) & 1)) break;
            __nanosleep(40);
          }
          tries = 0;
#pragma unroll 1
          do { ldp(pb + fo * 36 * 32, sp); } while (badp() && ++tries < (1 << 20));
          STAMPW(0, 14);
          const uint32_t tb = sbase + SM_A + warp * 3328;
#pragma unroll
          for (int v = 0; v < 6; v++) {
            uint32_t o[4];
#pragma unroll
            for (int k = 0; k < 4; k++) {
              const int q = 4 * v + k;
              const uint32_t w = reinterpret_cast<const uint32_t*>(p)[q];
              const uint32_t gt = pack_bf16(silu_h(fmaf(bf_lo(w), 0.25f / GK, B[2 * q])), silu_h(fmaf(bf_hi(w), 0.25f / GK, B[2 * q + 1])));
              o[k] = hfma2(reinterpret_cast<const uint32_t*>(p)[24 + q], gt, 0x80008000u);
            }
            stsm4(tb + (l2 & 15) * 208 + (l2 >> 4) * 16 + v * 32, make_uint4(o[0], o[1], o[2], o[3]));
          }
          __syncwarp();
#pragma unroll
          for (int j = 0; j < 6; j++) {
            const int k = l2 + 32 * j, r = (k * 171) >> 11;
            uint4 o;
            asm volatile("ld.shared.v4.u32 {%0,%1,%2,%3}, [%4];" : "=r"(o.x), "=r"(o.y), "=r"(o.z), "=r"(o.w) : "r"(tb + r * 208 + (k - 12 * r) * 16) : "memory");
            *reinterpret_cast<uint4*>(P.out + ro[j]) = make_uint4(hadd2(o.x, xx[j].x), hadd2(o.y, xx[j].y), hadd2(o.z, xx[j].z), hadd2(o.w, xx[j].w));
          }
          break;
        }
#pragma unroll 1
        for (; s < 17; s++) {
          issue192r(B, c, s);
          if (s == 14 && i == 2) wg_sync();
          retire(c, s - 1);
          if ((s & 1) == 0 && xf) mbar_arrive(bar_xfree + 4 * s - 8);
        }
        issue192(B, c, 17, false, false);
        retire(c, 16);
        c.phase ^= 1;
      }
      STAMPW(0, 3 + 2 * i);
    }
    STAMPW(0, 15);
    cluster_arrive_relaxed();
    cluster_wait();
    STAMPW(0, 16);
    if (tid == 0) g_epoch[blockIdx.x] = ep;
  }
}

typedef CUresult (*EncFn)(CUtensorMap*, CUtensorMapDataType, cuuint32_t, void*, const cuuint64_t*, const cuuint64_t*, const cuuint32_t*, const cuuint32_t*,
                          CUtensorMapInterleave, CUtensorMapSwizzle, CUtensorMapL2promotion, CUtensorMapFloatOOBfill);

void make_map(EncFn enc, CUtensorMap* tm, const void* ptr, int rows, int cols, int box_rows, int mode = 0) {
  cuuint64_t gd[2] = {(cuuint64_t)cols, (cuuint64_t)rows};
  cuuint64_t gs[1] = {(cuuint64_t)cols * 2};
  cuuint32_t bx[2] = {mode == 1 ? 32u : (mode == 2 ? 72u : 64u), (cuuint32_t)box_rows};
  cuuint32_t es[2] = {1, 1};
  enc(tm, CU_TENSOR_MAP_DATA_TYPE_BFLOAT16, 2, const_cast<void*>(ptr), gd, gs, bx, es, CU_TENSOR_MAP_INTERLEAVE_NONE, mode == 1 ? CU_TENSOR_MAP_SWIZZLE_64B : (mode == 2 ? CU_TENSOR_MAP_SWIZZLE_NONE : CU_TENSOR_MAP_SWIZZLE_128B),
      CU_TENSOR_MAP_L2_PROMOTION_L2_256B, CU_TENSOR_MAP_FLOAT_OOB_FILL_NONE);
}

}

extern "C" void kernel_launch(void* const* d_in, const int* in_sizes, int n_in, void* d_out, int out_size) {
  (void)in_sizes; (void)n_in; (void)out_size;
  static EncFn enc = nullptr;
  static void *a_ptr = nullptr, *m_ptr = nullptr;
  if (!enc) {
    void* fn = nullptr; cudaDriverEntryPointQueryResult q;
    cudaGetDriverEntryPoint("cuTensorMapEncodeTiled", &fn, cudaEnableDefault, &q);
    enc = (EncFn)fn;
    cudaFuncSetAttribute(fused_kernel, cudaFuncAttributeMaxDynamicSharedMemorySize, SMEM_BYTES);
    cudaGetSymbolAddress(&a_ptr, g_a);
    cudaGetSymbolAddress(&m_ptr, g_m);
  }
  Params P;
  P.x = (const __nv_bfloat16*)d_in[0];
  P.wqkv = (const __nv_bfloat16*)d_in[1];
  P.wo = (const __nv_bfloat16*)d_in[2];
  P.w1 = (const __nv_bfloat16*)d_in[4];
  P.b1 = (const __nv_bfloat16*)d_in[5];
  P.w2 = (const __nv_bfloat16*)d_in[6];
  P.b2 = (const __nv_bfloat16*)d_in[7];
  P.out = (__nv_bfloat16*)d_out;
  make_map(enc, &P.tm_wqkv, P.wqkv, D_, Q3_, 32);
  make_map(enc, &P.tm_w1, P.w1, D_, F_, 32);
  make_map(enc, &P.tm_w2, P.w2, F_, D_, 32);
  make_map(enc, &P.tm_m, m_ptr, D_, D_, 32);
  make_map(enc, &P.tm_wqkv64, P.wqkv, D_, Q3_, 64, 1);
  make_map(enc, &P.tm_m64, m_ptr, D_, D_, 64, 1);
  make_map(enc, &P.tm_a, a_ptr, S_, D_, 128);
  make_map(enc, &P.tm_ast, a_ptr, S_, D_, 16, 2);
  fused_kernel<<<NCTAS, NTHREADS, SMEM_BYTES, cudaStreamPerThread>>>(P);
}
```

```cpp
#include <cuda_runtime.h>
#include <cuda.h>
#include <cuda_bf16.h>
#include <stdint.h>

namespace {

constexpr int S_ = 2048, D_ = 576, F_ = 4608, Q3_ = 1728;
constexpr int NSTAGE = 6, STAGE_BYTES = 12288;
constexpr int SM_A = 0, SM_B = 147456, SM_BIAS = SM_B + NSTAGE * STAGE_BYTES, SM_RSTD = SM_BIAS + 2304 + 128, SM_SCR = SM_RSTD + 512, SM_BAR = SM_SCR + 7168;
constexpr int SMEM_BYTES = SM_BAR + 320;
constexpr int NTHREADS = 384;
constexpr int NCTAS = 132;

__device__ uint2 g_qkv[(128 * 216 + 2) * 32];
__device__ __align__(1024) __nv_bfloat16 g_a[S_ * D_];
__device__ __align__(1024) __nv_bfloat16 g_m[D_ * D_];
__device__ uint4 g_kvp[32 * 5 * 16 * 32];
__device__ uint4 g_z[32 * 2 * 4];
__device__ uint4 g_part[128 * 8 * 36 * 32];
__device__ uint2 g_s[128 * 72 * 32];
__device__ uint4 g_hsp[128 * 12 * 256];
__device__ uint32_t g_f_qkv[16 * 8];
__device__ uint32_t g_f_kvp[32];
__device__ uint32_t g_f_z[32];
__device__ uint32_t g_f_a[16];
__device__ uint32_t g_f_m[1];
__device__ uint2 g_stat[S_];
__device__ uint32_t g_epoch[NCTAS];

#define STAMP(i)
#define STAMPW(w, i)
#define WSTAMP(i)
__device__ __forceinline__ uint32_t smem_u32(const void* p) { return (uint32_t)__cvta_generic_to_shared(p); }
__device__ __forceinline__ void mbar_init(uint32_t a, int c) { asm volatile("mbarrier.init.shared::cta.b64 [%0], %1;" ::"r"(a), "r"(c)); }
__device__ __forceinline__ void mbar_expect(uint32_t a, uint32_t b) { asm volatile("mbarrier.arrive.expect_tx.shared::cta.b64 _, [%0], %1;" ::"r"(a), "r"(b) : "memory"); }
__device__ __forceinline__ void mbar_arrive(uint32_t a) { asm volatile("mbarrier.arrive.shared::cta.b64 _, [%0];" ::"r"(a) : "memory"); }
__device__ __forceinline__ void mbar_arrive_cl(uint32_t a) { asm volatile("mbarrier.arrive.shared::cluster.b64 _, [%0];" ::"r"(a) : "memory"); }
__device__ __forceinline__ uint32_t mapa(uint32_t a, uint32_t cta) { uint32_t r; asm volatile("mapa.shared::cluster.u32 %0, %1, %2;" : "=r"(r) : "r"(a), "r"(cta)); return r; }
__device__ __forceinline__ void mbar_wait(uint32_t a, uint32_t ph) {
  uint32_t ok; int it = 0;
#pragma unroll 1
  do {
    asm volatile("{.reg .pred p; mbarrier.try_wait.parity.shared::cta.b64 p, [%1], %2; selp.u32 %0,1,0,p;}" : "=r"(ok) : "r"(a), "r"(ph) : "memory");
  } while (!ok && ++it < (1 << 18));
}
__device__ __forceinline__ void tma2d(uint32_t dst, const CUtensorMap* m, int c0, int c1, uint32_t bar) {
  asm volatile("cp.async.bulk.tensor.2d.shared::cluster.global.mbarrier::complete_tx::bytes [%0], [%1, {%3,%4}], [%2];" ::"r"(dst), "l"(m), "r"(bar), "r"(c0), "r"(c1) : "memory");
}
__device__ __forceinline__ void tma2d_mc(uint32_t dst, const CUtensorMap* m, int c0, int c1, uint32_t bar) {
  asm volatile("cp.async.bulk.tensor.2d.shared::cluster.global.mbarrier::complete_tx::bytes.multicast::cluster [%0], [%1, {%3,%4}], [%2], %5;" ::"r"(dst), "l"(m), "r"(bar), "r"(c0), "r"(c1), "h"((uint16_t)3) : "memory");
}
__device__ __forceinline__ void cluster_arrive_relaxed() { asm volatile("barrier.cluster.arrive.relaxed.aligned;" ::: "memory"); }
__device__ __forceinline__ void cluster_wait() { asm volatile("barrier.cluster.wait.acquire.aligned;" ::: "memory"); }
__device__ __forceinline__ void wg_fence() { asm volatile("wgmma.fence.sync.aligned;" ::: "memory"); }
__device__ __forceinline__ void wg_commit() { asm volatile("wgmma.commit_group.sync.aligned;" ::: "memory"); }
template <int n> __device__ __forceinline__ void wg_wait() { asm volatile("wgmma.wait_group.sync.aligned %0;" ::"n"(n) : "memory"); }
__device__ __forceinline__ uint32_t ld_acquire(const uint32_t* p) { uint32_t v; asm volatile("ld.acquire.gpu.global.u32 %0, [%1];" : "=r"(v) : "l"(p) : "memory"); return v; }
__device__ __forceinline__ void flag_wait(const uint32_t* p, uint32_t target) {
  int it = 0;
#pragma unroll 1
  while ((int)(ld_acquire(p) - target) < 0 && ++it < (1 << 20)) __nanosleep(300);
}
__device__ __forceinline__ void hint_signal(uint32_t* p) {
  if ((threadIdx.x & 31) == 0) asm volatile("red.relaxed.gpu.global.add.u32 [%0], 1;" ::"l"(p) : "memory");
}
__device__ __forceinline__ void hint_wait(const uint32_t* p, uint32_t target, uint32_t ns = 400) {
  int it = 0; uint32_t v;
#pragma unroll 1
  do { asm volatile("ld.relaxed.gpu.global.u32 %0, [%1];" : "=r"(v) : "l"(p) : "memory"); if ((int)(v - target) >= 0) break; __nanosleep(ns); } while (++it < (1 << 20));
}
__device__ __forceinline__ uint32_t tag(uint32_t x, uint32_t par) { uint32_t r; asm("lop3.b32 %0, %1, 0xfffffffe, %2, 0xea;" : "=r"(r) : "r"(x), "r"(par)); return r; }
__device__ __forceinline__ void st_ll(uint4* p, uint32_t x, uint32_t y, uint32_t z, uint32_t w, uint32_t par) {
  asm volatile("{.reg .b64 a, b; mov.b64 a, {%1,%2}; mov.b64 b, {%3,%4}; st.relaxed.gpu.global.v2.b64 [%0], {a, b};}"
               ::"l"(p), "r"(tag(x, par)), "r"(y), "r"(tag(z, par)), "r"(w) : "memory");
}
__device__ __forceinline__ uint4 ld_ll(const uint4* p) {
  uint4 v;
  asm volatile("{.reg .b64 a, b; ld.relaxed.gpu.global.v2.b64 {a, b}, [%4]; mov.b64 {%0,%1}, a; mov.b64 {%2,%3}, b;}"
               : "=r"(v.x), "=r"(v.y), "=r"(v.z), "=r"(v.w) : "l"(p) : "memory");
  return v;
}
__device__ __forceinline__ void st_ll64(uint2* p, uint32_t x, uint32_t y, uint32_t par) {
  asm volatile("{.reg .b64 a; mov.b64 a, {%1,%2}; st.relaxed.gpu.global.b64 [%0], a;}" ::"l"(p), "r"(tag(x, par)), "r"(y) : "memory");
}
__device__ __forceinline__ uint2 ld_ca64(const void* p) {
  uint2 v;
  asm volatile("{.reg .b64 a; ld.global.ca.b64 a, [%2]; mov.b64 {%0,%1}, a;}" : "=r"(v.x), "=r"(v.y) : "l"(p) : "memory");
  return v;
}
__device__ __forceinline__ uint2 ld_ll64(const void* p) {
  uint2 v;
  asm volatile("{.reg .b64 a; ld.relaxed.gpu.global.b64 a, [%2]; mov.b64 {%0,%1}, a;}" : "=r"(v.x), "=r"(v.y) : "l"(p) : "memory");
  return v;
}
__device__ __forceinline__ void ll_chk(uint32_t& bad, uint32_t a, uint32_t b, uint32_t par) {
  uint32_t u; asm("lop3.b32 %0, %1, %2, %3, 0x7e;" : "=r"(u) : "r"(a), "r"(b), "r"(par));
  asm("or.b32 %0, %0, %1;" : "+r"(bad) : "r"(u));
}
__device__ __forceinline__ uint32_t hadd2(uint32_t a, uint32_t b) { uint32_t d; asm("add.rn.bf16x2 %0, %1, %2;" : "=r"(d) : "r"(a), "r"(b)); return d; }
__device__ __forceinline__ uint32_t hfma2(uint32_t a, uint32_t b, uint32_t c) { uint32_t d; asm("fma.rn.bf16x2 %0, %1, %2, %3;" : "=r"(d) : "r"(a), "r"(b), "r"(c)); return d; }
__device__ __forceinline__ uint32_t pack_bf16(float lo, float hi) { uint32_t r; asm("cvt.rn.bf16x2.f32 %0, %1, %2;" : "=r"(r) : "f"(hi), "f"(lo)); return r; }
__device__ __forceinline__ float bf_lo(uint32_t v) { return __uint_as_float(v << 16); }
__device__ __forceinline__ float bf_hi(uint32_t v) { return __uint_as_float(v & 0xffff0000u); }
__device__ __forceinline__ uint32_t movmat(uint32_t a) { uint32_t d; asm volatile("movmatrix.sync.aligned.m8n8.trans.b16 %0, %1;" : "=r"(d) : "r"(a)); return d; }
__device__ __forceinline__ void mma16816(float* c, uint32_t a0, uint32_t a1, uint32_t a2, uint32_t a3, uint32_t b0, uint32_t b1) {
  asm volatile("mma.sync.aligned.m16n8k16.row.col.f32.bf16.bf16.f32 {%0,%1,%2,%3}, {%4,%5,%6,%7}, {%8,%9}, {%0,%1,%2,%3};"
               : "+f"(c[0]), "+f"(c[1]), "+f"(c[2]), "+f"(c[3]) : "r"(a0), "r"(a1), "r"(a2), "r"(a3), "r"(b0), "r"(b1));
}
__device__ __forceinline__ uint4 ldcg128(const void* p) { uint4 v; asm volatile("ld.global.cg.v4.u32 {%0,%1,%2,%3}, [%4];" : "=r"(v.x), "=r"(v.y), "=r"(v.z), "=r"(v.w) : "l"(p) : "memory"); return v; }

template <int N> __device__ __forceinline__ void wgmma_ss(float* d, uint32_t alo, int aimm, uint32_t blo, int bimm, uint32_t bhi, int sc);
template <> __device__ __forceinline__ void wgmma_ss<96>(float* d, uint32_t alo, int aimm, uint32_t blo, int bimm, uint32_t bhi, int sc) {
  asm volatile("{.reg .pred p; .reg .b32 x, y; .reg .b64 da, db; setp.ne.b32 p, %53, 0; add.u32 x, %48, %49; add.u32 y, %50, %51; mov.b64 da, {x, 0x40000040}; mov.b64 db, {y, %52}; "
               "wgmma.mma_async.sync.aligned.m64n96k16.f32.bf16.bf16 {%0, %1, %2, %3, %4, %5, %6, %7, %8, %9, %10, %11, %12, %13, %14, %15, %16, %17, %18, %19, %20, %21, %22, %23, %24, %25, %26, %27, %28, %29, %30, %31, %32, %33, %34, %35, %36, %37, %38, %39, %40, %41, %42, %43, %44, %45, %46, %47}, da, db, p, 1, 1, 0, 1;}"
   : "+f"(d[0]), "+f"(d[1]), "+f"(d[2]), "+f"(d[3]), "+f"(d[4]), "+f"(d[5]), "+f"(d[6]), "+f"(d[7]), "+f"(d[8]), "+f"(d[9]), "+f"(d[10]), "+f"(d[11]), "+f"(d[12]), "+f"(d[13]), "+f"(d[14]), "+f"(d[15]), "+f"(d[16]), "+f"(d[17]), "+f"(d[18]), "+f"(d[19]), "+f"(d[20]), "+f"(d[21]), "+f"(d[22]), "+f"(d[23]), "+f"(d[24]), "+f"(d[25]), "+f"(d[26]), "+f"(d[27]), "+f"(d[28]), "+f"(d[29]), "+f"(d[30]), "+f"(d[31]), "+f"(d[32]), "+f"(d[33]), "+f"(d[34]), "+f"(d[35]), "+f"(d[36]), "+f"(d[37]), "+f"(d[38]), "+f"(d[39]), "+f"(d[40]), "+f"(d[41]), "+f"(d[42]), "+f"(d[43]), "+f"(d[44]), "+f"(d[45]), "+f"(d[46]), "+f"(d[47]) : "r"(alo), "r"(aimm), "r"(blo), "r"(bimm), "r"(bhi), "r"(sc));
}
template <> __device__ __forceinline__ void wgmma_ss<192>(float* d, uint32_t alo, int aimm, uint32_t blo, int bimm, uint32_t bhi, int sc) {
  asm volatile("{.reg .pred p; .reg .b32 x, y; .reg .b64 da, db; setp.ne.b32 p, %101, 0; add.u32 x, %96, %97; add.u32 y, %98, %99; mov.b64 da, {x, 0x40000040}; mov.b64 db, {y, %100}; "
               "wgmma.mma_async.sync.aligned.m64n192k16.f32.bf16.bf16 {%0, %1, %2, %3, %4, %5, %6, %7, %8, %9, %10, %11, %12, %13, %14, %15, %16, %17, %18, %19, %20, %21, %22, %23, %24, %25, %26, %27, %28, %29, %30, %31, %32, %33, %34, %35, %36, %37, %38, %39, %40, %41, %42, %43, %44, %45, %46, %47, %48, %49, %50, %51, %52, %53, %54, %55, %56, %57, %58, %59, %60, %61, %62, %63, %64, %65, %66, %67, %68, %69, %70, %71, %72, %73, %74, %75, %76, %77, %78, %79, %80, %81, %82, %83, %84, %85, %86, %87, %88, %89, %90, %91, %92, %93, %94, %95}, da, db, p, 1, 1, 0, 1;}"
   : "+f"(d[0]), "+f"(d[1]), "+f"(d[2]), "+f"(d[3]), "+f"(d[4]), "+f"(d[5]), "+f"(d[6]), "+f"(d[7]), "+f"(d[8]), "+f"(d[9]), "+f"(d[10]), "+f"(d[11]), "+f"(d[12]), "+f"(d[13]), "+f"(d[14]), "+f"(d[15]), "+f"(d[16]), "+f"(d[17]), "+f"(d[18]), "+f"(d[19]), "+f"(d[20]), "+f"(d[21]), "+f"(d[22]), "+f"(d[23]), "+f"(d[24]), "+f"(d[25]), "+f"(d[26]), "+f"(d[27]), "+f"(d[28]), "+f"(d[29]), "+f"(d[30]), "+f"(d[31]), "+f"(d[32]), "+f"(d[33]), "+f"(d[34]), "+f"(d[35]), "+f"(d[36]), "+f"(d[37]), "+f"(d[38]), "+f"(d[39]), "+f"(d[40]), "+f"(d[41]), "+f"(d[42]), "+f"(d[43]), "+f"(d[44]), "+f"(d[45]), "+f"(d[46]), "+f"(d[47]), "+f"(d[48]), "+f"(d[49]), "+f"(d[50]), "+f"(d[51]), "+f"(d[52]), "+f"(d[53]), "+f"(d[54]), "+f"(d[55]), "+f"(d[56]), "+f"(d[57]), "+f"(d[58]), "+f"(d[59]), "+f"(d[60]), "+f"(d[61]), "+f"(d[62]), "+f"(d[63]), "+f"(d[64]), "+f"(d[65]), "+f"(d[66]), "+f"(d[67]), "+f"(d[68]), "+f"(d[69]), "+f"(d[70]), "+f"(d[71]), "+f"(d[72]), "+f"(d[73]), "+f"(d[74]), "+f"(d[75]), "+f"(d[76]), "+f"(d[77]), "+f"(d[78]), "+f"(d[79]), "+f"(d[80]), "+f"(d[81]), "+f"(d[82]), "+f"(d[83]), "+f"(d[84]), "+f"(d[85]), "+f"(d[86]), "+f"(d[87]), "+f"(d[88]), "+f"(d[89]), "+f"(d[90]), "+f"(d[91]), "+f"(d[92]), "+f"(d[93]), "+f"(d[94]), "+f"(d[95]) : "r"(alo), "r"(aimm), "r"(blo), "r"(bimm), "r"(bhi), "r"(sc));
}

constexpr uint32_t DESC_HI = (1024u >> 4) | (1u << 30);
constexpr uint32_t DESC_HI64 = (512u >> 4) | (2u << 30);
template <int n> __device__ __forceinline__ void fence_regs(float* a) {
#pragma unroll
  for (int i = 0; i < n; i++) asm volatile("" : "+f"(a[i])::"memory");
}

struct Ctx {
  uint32_t full, emb;
  bool sig;
  uint32_t o0, o1;
  uint32_t p0, p1;
  uint32_t dB, dA;
  int budget;
  __device__ __forceinline__ static int m6(int s) { return s >= 12 ? s - 12 : (s >= 6 ? s - 6 : s); }
  __device__ __forceinline__ uint32_t hb(int s) const { return m6(s) < 3 ? o0 : o1; }
  __device__ __forceinline__ static int m3(int s) { return m6(s) < 3 ? m6(s) : m6(s) - 3; }
  __device__ __forceinline__ void release(int s) { if (sig) mbar_arrive_cl(emb + 8 * hb(s) + 8 * m3(s)); }
  __device__ __forceinline__ void wait(uint32_t a, uint32_t ph) {
    uint32_t ok;
#pragma unroll 1
    do {
      asm volatile("{.reg .pred p; mbarrier.try_wait.parity.shared::cta.b64 p, [%1], %2; selp.u32 %0,1,0,p;}" : "=r"(ok) : "r"(a), "r"(ph) : "memory");
      budget--;
    } while ((ok == 0) & (budget > 0));
  }
  __device__ __forceinline__ void wait_full(int s) {
    const uint32_t a = full + 8 * hb(s) + 8 * m3(s), ph = (m6(s) < 3 ? p0 : p1) ^ ((s >= 6 && s < 12) ? 1u : 0u);
    wait(a, ph);
    wg_fence();
  }
  __device__ __forceinline__ void set(uint32_t sw, uint32_t second) { o0 = sw ? 3 : 0; o1 = 3 - o0; p0 = second; p1 = second ^ sw; }
};

__device__ __forceinline__ void issue192(float* acc, Ctx& c, int s, bool first = false) {
  c.wait_full(s);
  const uint32_t db = c.dB + c.hb(s) * (STAGE_BYTES >> 4);
  wgmma_ss<192>(acc, c.dA, (s >> 1) * 1024 + (s & 1) * 4, db, Ctx::m3(s) * (STAGE_BYTES >> 4), DESC_HI, first ? 0 : 1);
  wgmma_ss<192>(acc, c.dA, (s >> 1) * 1024 + (s & 1) * 4 + 2, db, Ctx::m3(s) * (STAGE_BYTES >> 4) + 128, DESC_HI, 1);
  wg_commit();
}
__device__ __forceinline__ void issue96(float* acc, Ctx& c, int k, bool first) {
  c.wait_full(k);
  const uint32_t db = c.dB + c.hb(k) * (STAGE_BYTES >> 4);
  if (first) { wgmma_ss<192>(acc, c.dA, k * 1024, db, Ctx::m3(k) * (STAGE_BYTES >> 4), DESC_HI64, 0); wg_fence(); }
#pragma unroll
  for (int kk = first ? 1 : 0; kk < 4; kk++) wgmma_ss<96>(acc, c.dA, k * 1024 + 2 * kk, db, Ctx::m3(k) * (STAGE_BYTES >> 4) + 64 * kk, DESC_HI64, 1);
  wg_commit();
}
__device__ __forceinline__ void retire(Ctx& c, int prev) {
  wg_wait<1>();
  c.release(prev);
}

constexpr float GK = 0.32920349f;
__device__ __forceinline__ uint32_t gelu_pair(uint32_t y) {
  uint32_t u, th;
  asm("mul.rn.bf16x2 %0, %1, %2;" : "=r"(u) : "r"(hfma2(y, y, 0x401b401bu)), "r"(y));
  asm("tanh.approx.bf16x2 %0, %1;" : "=r"(th) : "r"(u));
  return hfma2(y, th, y);
}
__device__ __forceinline__ uint4 gelu_group(const uint32_t* a) { return make_uint4(gelu_pair(a[0]), gelu_pair(a[1]), gelu_pair(a[2]), gelu_pair(a[3])); }
__device__ __forceinline__ void lds_bias(float2* b, uint32_t addr) {
#pragma unroll
  for (int j = 0; j < 2; j++) asm volatile("ld.shared.v2.f32 {%0,%1}, [%2];" : "=f"(b[j].x), "=f"(b[j].y) : "r"(addr + 32 * j));
}
__device__ __forceinline__ int opaque(int v) { asm volatile("" : "+r"(v)); return v; }
__device__ __forceinline__ void stsm4(uint32_t addr, uint4 r) {
  asm volatile("stmatrix.sync.aligned.m8n8.x4.shared.b16 [%0], {%1,%2,%3,%4};" ::"r"(addr), "r"(r.x), "r"(r.y), "r"(r.z), "r"(r.w) : "memory");
}
__device__ __forceinline__ float ex2f(float x) { float r; asm("ex2.approx.ftz.f32 %0, %1;" : "=f"(r) : "f"(x)); return r; }
__device__ __forceinline__ uint32_t phi_pack(uint32_t tp, float a0, float a1, uint32_t c1, uint32_t c2) {
  uint32_t x, y;
  asm("max.bf16x2 %0, %1, %2;" : "=r"(x) : "r"(tp), "r"(c1));
  asm("min.bf16x2 %0, %1, %2;" : "=r"(y) : "r"(pack_bf16(ex2f(a0), ex2f(a1))), "r"(c2));
  return hadd2(x, y);
}
template <int q0, int q1>
__device__ __forceinline__ void part_groups(const float* a, uint4* p, uint32_t par) {
#pragma unroll
  for (int q = q0; q < q1; q++)
    st_ll(p + q * 32, pack_bf16(a[8 * q], a[8 * q + 1]), pack_bf16(a[8 * q + 2], a[8 * q + 3]), pack_bf16(a[8 * q + 4], a[8 * q + 5]), pack_bf16(a[8 * q + 6], a[8 * q + 7]), par);
}
__device__ __forceinline__ float rcpf(float x) { float r; asm("rcp.approx.ftz.f32 %0, %1;" : "=f"(r) : "f"(x)); return r; }
__device__ __forceinline__ float silu_h(float h) { float r; asm("tanh.approx.f32 %0, %1;" : "=f"(r) : "f"(h)); return fmaf(h, r, h); }
__device__ __forceinline__ int pairoff(int p, int g) { return (p >> 2) * 32 + g * 4 + (p & 3); }
template <bool STRONG> __device__ __forceinline__ void d1_load(uint32_t* W, int rb0, int head, int ln) {
  const uint2* qf = g_qkv + rb0 * 216 * 32 + pairoff(288 + head * 9 + (ln & 3), ln >> 2);
#pragma unroll
  for (int b = 0; b < 3; b++) {
#pragma unroll
    for (int j = 0; j < 4; j++) {
      const uint2* p = qf + j * 216 * 32 + 32 * b;
      const uint2 kk = STRONG ? ld_ll64(p) : ld_ca64(p), vv = STRONG ? ld_ll64(p + 72 * 32) : ld_ca64(p + 72 * 32);
      W[6 * j + 2 * b] = kk.x; W[6 * j + 2 * b + 1] = kk.y; W[24 + 6 * j + 2 * b] = vv.x; W[24 + 6 * j + 2 * b + 1] = vv.y;
    }
  }
}
__device__ __forceinline__ bool d1_bad(const uint32_t* W, int t, uint32_t par) {
  uint32_t bad = 0, bad2 = 0;
#pragma unroll
  for (int q = 0; q < 12; q++) ll_chk((q % 3) != 2 ? bad : bad2, W[2 * q], W[24 + 2 * q], par);
  return __any_sync(0xffffffffu, (bad | (t == 0 ? bad2 : 0u)) & 1);
}
__device__ __forceinline__ void d1_mov(uint32_t* W, int j, int t) {
  if (t != 0) { W[6 * j + 4] = W[6 * j + 5] = 0u; W[24 + 6 * j + 4] = W[24 + 6 * j + 5] = (t == 1 ? 0x00003f80u : 0u); }
#pragma unroll
  for (int q = 0; q < 6; q++) { W[6 * j + q] = movmat(W[6 * j + q]); W[24 + 6 * j + q] = movmat(W[24 + 6 * j + q]); }
}
__device__ __forceinline__ void d1_mma(const uint32_t* W, float* R) {
  float c1[3][4];
#pragma unroll
  for (int j = 0; j < 12; j++) { R[j] = 0.f; c1[j >> 2][j & 3] = 0.f; }
#pragma unroll
  for (int ks = 0; ks < 4; ks++)
#pragma unroll
    for (int j = 0; j < 3; j++) {
      mma16816(R + 4 * j, W[24 + 6 * ks], W[24 + 6 * ks + 2], W[24 + 6 * ks + 1], W[24 + 6 * ks + 3], W[6 * ks + 2 * j], W[6 * ks + 2 * j + 1]);
      mma16816(c1[j], W[24 + 6 * ks + 4], 0u, W[24 + 6 * ks + 5], 0u, W[6 * ks + 2 * j], W[6 * ks + 2 * j + 1]);
    }
#pragma unroll
  for (int j = 0; j < 3; j++) { R[12 + 2 * j] = c1[j][0]; R[13 + 2 * j] = c1[j][1]; }
}
__device__ __forceinline__ bool kv_valid(int w, int ln) { return (w < 3 || ln < 12) && ((w != 2 && w != 4) || (ln & 3) == 0); }

struct Params {
  CUtensorMap tm_wqkv, tm_w1, tm_w2, tm_m, tm_wqkv64, tm_m64, tm_a, tm_ast;
  const __nv_bfloat16 *x, *b1, *b2, *wqkv, *w1, *w2, *wo;
  __nv_bfloat16* out;
};

__global__ void __cluster_dims__(2, 1, 1) __launch_bounds__(NTHREADS, 1) fused_kernel(const __grid_constant__ Params P) {
  extern __shared__ __align__(1024) uint8_t smem[];
  const uint32_t sbase = smem_u32(smem);
  const int tid = threadIdx.x, lane = tid & 31;
  const int warp = __shfl_sync(0xffffffffu, tid >> 5, 0);
  const int g = lane >> 2, t = lane & 3;
  const uint32_t ep = __shfl_sync(0xffffffffu, g_epoch[blockIdx.x], 0) + 1;
  const uint32_t par = ep & 1;
  STAMPW(0, 0);

  if (blockIdx.x >= 128) {
    const int a = blockIdx.x - 128;
    constexpr int WP = 1168, SM_T = 152 * WP, SM_HB = SM_T + 8 * 32 * 80;
    if (tid == 0) {
      mbar_init(sbase + SM_HB, 1);
      asm volatile("fence.mbarrier_init.release.cluster;" ::: "memory");
      mbar_expect(sbase + SM_HB, 144 * 1152);
    }
    for (int i = tid; i < (8 * WP + 8 * 32 * 80) / 4; i += NTHREADS) reinterpret_cast<uint32_t*>(smem + 144 * WP)[i] = 0u;
    __syncthreads();
    __nanosleep(1500);
    if (tid < 144)
      asm volatile("cp.async.bulk.shared::cluster.global.mbarrier::complete_tx::bytes [%0], [%1], %2, [%3];" ::"r"(sbase + tid * WP), "l"(P.wo + (a * 144 + tid) * D_), "r"(1152), "r"(sbase + SM_HB) : "memory");
    if (warp >= 8 && lane == 0) {
      const int id = a * 4 + (warp - 8);
      constexpr uint32_t CH = 9216 * 2;
#pragma unroll 1
      for (int i = id; i < 576; i += 16) {
        const char* p = i < 288 ? (const char*)P.w1 + (size_t)i * CH : (const char*)P.w2 + (size_t)(i - 288) * CH;
        asm volatile("cp.async.bulk.prefetch.L2.global [%0], %1;" ::"l"(p), "r"(CH) : "memory");
      }
    }
    __syncwarp();
    if (lane < 8) hint_wait(&g_f_kvp[a * 8 + lane], 16 * ep, 50);
    __syncwarp();
    STAMPW(0, 1);
#pragma unroll 1
    for (int u = warp; u < 40; u += 12) {
      const int hh = u & 7, w = 4 - (u >> 3), head = a * 8 + hh;
      uint4 v[16];
      int tries = 0;
      uint32_t bad;
      const bool val = kv_valid(w, lane);
#pragma unroll 1
      do {
        bad = 0;
#pragma unroll
        for (int j = 0; j < 16; j++) v[j] = val ? ld_ll(&g_kvp[((head * 5 + w) * 16 + j) * 32 + lane]) : make_uint4(par, 0u, par, 0u);
#pragma unroll
        for (int j = 0; j < 16; j++) ll_chk(bad, v[j].x, v[j].z, par);
      } while (__any_sync(0xffffffffu, bad & 1) && ++tries < (1 << 20));
      float s0 = 0.f, s1 = 0.f, s2 = 0.f, s3 = 0.f;
#pragma unroll
      for (int j = 0; j < 16; j++) { s0 += __uint_as_float(v[j].x); s1 += __uint_as_float(v[j].y); s2 += __uint_as_float(v[j].z); s3 += __uint_as_float(v[j].w); }
      if (w >= 3) {
        if (g == 2) st_ll(&g_z[(head * 2 + w - 3) * 4 + t], __float_as_uint(s0), __float_as_uint(s1), __float_as_uint(s2), __float_as_uint(s3), par);
        __syncwarp();
        hint_signal(&g_f_z[head]);
      }
      const int e0 = w < 3 ? g : 16 + g, e1 = w < 3 ? g + 8 : 16 + g, d0 = (w < 3 ? 8 * w : (w == 3 ? 0 : 16)) + 2 * t, d1 = w < 3 ? d0 : d0 + 8;
      __nv_bfloat16* T = reinterpret_cast<__nv_bfloat16*>(smem + SM_T) + hh * 32 * 40;
      if (e0 < 18) {
        T[d0 * 40 + e0] = __float2bfloat16(s0); T[(d0 + 1) * 40 + e0] = __float2bfloat16(s1);
        T[d1 * 40 + e1] = __float2bfloat16(s2); T[(d1 + 1) * 40 + e1] = __float2bfloat16(s3);
      }
    }
    __syncthreads();
    STAMPW(0, 2);
    mbar_wait(sbase + SM_HB, 0);
#pragma unroll 1
    for (int u = warp; u < 24; u += 12) {
      const int hh = u / 3, c0 = (u % 3) * 192;
      const uint32_t* T = reinterpret_cast<const uint32_t*>(smem + SM_T) + hh * 32 * 20 + g * 20 + t;
      const uint32_t a00 = T[0], a01 = T[160], a02 = T[4], a03 = T[164], a10 = T[8], a11 = T[168], b00 = T[320], b02 = T[324], b10 = T[328];
      const uint32_t rowa = sbase + (hh * 18 + (lane & 15)) * WP + (c0 + (lane >> 4) * 8) * 2, rowb = sbase + (hh * 18 + 16 + (lane & 7)) * WP + (c0 + ((lane >> 3) & 1) * 8) * 2;
#pragma unroll 3
      for (int j = 0; j < 12; j++) {
        uint32_t w0, w1, w2, w3, w4, w5;
        asm volatile("ldmatrix.sync.aligned.m8n8.x4.trans.shared.b16 {%0,%1,%2,%3}, [%4];" : "=r"(w0), "=r"(w1), "=r"(w2), "=r"(w3) : "r"(rowa + j * 32));
        asm volatile("ldmatrix.sync.aligned.m8n8.x2.trans.shared.b16 {%0,%1}, [%2];" : "=r"(w4), "=r"(w5) : "r"(rowb + j * 32));
        float p[4][4];
#pragma unroll
        for (int q = 0; q < 4; q++) p[q][0] = p[q][1] = p[q][2] = p[q][3] = 0.f;
        mma16816(p[0], a00, a01, a02, a03, w0, w1); mma16816(p[1], a00, a01, a02, a03, w2, w3);
        mma16816(p[2], b00, 0u, b02, 0u, w0, w1); mma16816(p[3], b00, 0u, b02, 0u, w2, w3);
        mma16816(p[0], a10, a11, 0u, 0u, w4, 0u); mma16816(p[1], a10, a11, 0u, 0u, w5, 0u);
        mma16816(p[2], b10, 0u, 0u, 0u, w4, 0u); mma16816(p[3], b10, 0u, 0u, 0u, w5, 0u);
        stsm4(rowa + j * 32, make_uint4(pack_bf16(p[0][0], p[0][1]), pack_bf16(p[0][2], p[0][3]), pack_bf16(p[1][0], p[1][1]), pack_bf16(p[1][2], p[1][3])));
        if (g < 2) {
          uint32_t* r = reinterpret_cast<uint32_t*>(smem + (hh * 18 + 16 + g) * WP + (c0 + j * 16 + 2 * t) * 2);
          r[0] = pack_bf16(p[2][0], p[2][1]); r[4] = pack_bf16(p[3][0], p[3][1]);
        }
      }
      asm volatile("fence.proxy.async.shared::cta;" ::: "memory");
      __syncwarp();
      if (lane < 18) {
        asm volatile("cp.async.bulk.global.shared::cta.bulk_group [%0], [%1], %2;" ::"l"(g_m + (a * 144 + hh * 18 + lane) * D_ + c0), "r"(sbase + (hh * 18 + lane) * WP + c0 * 2), "r"(384) : "memory");
        asm volatile("cp.async.bulk.commit_group;" ::: "memory");
      }
    }
    asm volatile("cp.async.bulk.wait_group 0;" ::: "memory");
    asm volatile("fence.proxy.async.global;" ::: "memory");
    __syncwarp();
    if (lane == 0) asm volatile("red.release.gpu.global.add.u32 [%0], 1;" ::"l"(g_f_m) : "memory");
    STAMPW(0, 3);
    __syncthreads();
    if (tid == 0) g_epoch[blockIdx.x] = ep;
    return;
  }

  const int cl = blockIdx.x >> 1, rank = blockIdx.x & 1;
  const int f = cl & 7, m = (cl >> 3) * 2 + rank;
  const int srole = f >= 6 ? 1 : 0;
  const uint32_t bar_full = sbase + SM_BAR, bar_empty = bar_full + 8 * NSTAGE, bar_xfree = bar_empty + 8 * NSTAGE, bar_ofull = bar_xfree + 72,
                 bar_d = bar_ofull + 72;

  if (tid == 0) {
#pragma unroll 1
    for (int i = 0; i < NSTAGE; i++) { mbar_init(bar_full + 8 * i, 1); mbar_init(bar_empty + 8 * i, 4); }
#pragma unroll 1
    for (int i = 0; i < 9; i++) { mbar_init(bar_xfree + 8 * i, 2); mbar_init(bar_ofull + 8 * i, 1); }
    mbar_init(bar_d, 1);
    asm volatile("fence.mbarrier_init.release.cluster;" ::: "memory");
  }
  __syncwarp();
  cluster_arrive_relaxed();

  if (warp >= 8) {
    const int srow = m * 128 + f * 16 + (warp - 8) * 4 + (lane >> 3);
    uint4 xs[9];
#pragma unroll
    for (int kb = 0; kb < 9; kb++) xs[kb] = __ldg(reinterpret_cast<const uint4*>(P.x + srow * D_) + (lane & 7) + kb * 8);
    auto stats = [&]() {
      const uint32_t* w = reinterpret_cast<const uint32_t*>(xs);
      float s0 = 0.f, s1 = 0.f;
#pragma unroll
      for (int i = 0; i < 36; i++) { s0 += bf_lo(w[i]); s1 += bf_hi(w[i]); }
      float sum = s0 + s1;
      sum += __shfl_xor_sync(0xffffffffu, sum, 1); sum += __shfl_xor_sync(0xffffffffu, sum, 2); sum += __shfl_xor_sync(0xffffffffu, sum, 4);
      const float mean = sum * (1.f / 576.f);
      s0 = 0.f; s1 = 0.f;
#pragma unroll
      for (int i = 0; i < 36; i++) { const float a = bf_lo(w[i]) - mean, b = bf_hi(w[i]) - mean; s0 = fmaf(a, a, s0); s1 = fmaf(b, b, s1); }
      float sq = s0 + s1;
      sq += __shfl_xor_sync(0xffffffffu, sq, 1); sq += __shfl_xor_sync(0xffffffffu, sq, 2); sq += __shfl_xor_sync(0xffffffffu, sq, 4);
      const float rstd = rsqrtf(sq * (1.f / 576.f) + 1e-5f);
      if ((lane & 7) == 0)
        st_ll64(&g_stat[srow], __float_as_uint(rstd), pack_bf16(-mean, -mean), par);
    };
    stats();
    asm volatile("setmaxnreg.dec.sync.aligned.u32 40;");
    cluster_wait();
    if (warp == 8) {
      if (lane == 0) {
        uint32_t stage = 0, phase = 1;
        const uint32_t sb = sbase + SM_B;
#pragma unroll 1
        for (int tl = 2 * srole; tl < 8 + 2 * srole; tl++) {
          const CUtensorMap* map = tl == 0 ? &P.tm_wqkv : (tl == 1 ? &P.tm_wqkv64 : (tl < 5 ? &P.tm_w1 : (tl < 8 ? &P.tm_w2 : (tl == 8 ? &P.tm_m : &P.tm_m64))));
          const int col = tl < 2 ? 288 * f + 192 * tl : (tl < 5 ? 576 * f + 192 * (tl - 2) : (tl < 8 ? 192 * ((tl - 5 + f) % 3) : (tl == 8 ? 192 * (f - 5) : 96 * (f - 6))));
          const bool perm = tl >= 5 && tl < 8;
          const bool z = (tl & 7) == 1;
          if (tl == 8) { flag_wait(g_f_m, 48 * ep); asm volatile("fence.proxy.async.global;" ::: "memory"); }
          const int cs = z ? 32 : 64, rs = z ? 64 : 32, nst = z ? 9 : 18;
#pragma unroll 1
          for (int st = 0; st < nst; st++) {
            int row = st * rs;
            if (perm) row += 576 * f + ((st < 6) ? 192 : (st < 12 ? -192 : 0));
            mbar_wait(bar_empty + 8 * stage, phase);
            mbar_expect(bar_full + 8 * stage, 12288);
            const uint32_t dst = sb + stage * STAGE_BYTES;
            if (((st ^ rank) & 1) == 0) {
              tma2d_mc(dst, map, col, row, bar_full + 8 * stage);
              tma2d_mc(dst + 8192, map, col + 2 * cs, row, bar_full + 8 * stage);
            } else {
              tma2d_mc(dst + 4096, map, col + cs, row, bar_full + 8 * stage);
            }
            if (++stage == NSTAGE) { stage = 0; phase ^= 1; }
          }
        }
      }
      __syncwarp();
    } else {
      const int aw = warp - 9;
      const int hi = f >> 2;
      if (aw == 0) {
        if (lane < 2) hint_wait(&g_f_qkv[m * 8 + 2 + 2 * lane + hi], 16 * ep, 200);
        __syncwarp();
        if (lane == 0) mbar_arrive(bar_d);
        STAMP(20);
      }
      if (lane < 5) hint_wait(lane < 4 ? &g_f_z[4 * f + lane] : &g_f_qkv[m * 8 + hi], lane < 4 ? 2 * ep : 16 * ep);
      __syncwarp();
      STAMPW(9, 22);
      uint32_t* stg = reinterpret_cast<uint32_t*>(smem + SM_SCR + aw * 2304);
#pragma unroll 1
      for (int u = aw * 2; u < 16; u += (u & 1) ? 5 : 1) {
        const int rbl = u >> 1, hp = (u & 1) * 2;
        const uint2* qf = g_qkv + (m * 8 + rbl) * 216 * 32;
        const uint2* zp = reinterpret_cast<const uint2*>(&g_z[(4 * f + hp) * 8 + t]);
        uint2 q[2][3];
        float d[4];
        int tries = 0;
        uint32_t bad;
#pragma unroll 1
        do {
          bad = tries ? ld_acquire(g_f_m) & 0u : 0u;
#pragma unroll
          for (int j = 0; j < 2; j++)
#pragma unroll
            for (int b = 0; b < 3; b++) q[j][b] = ld_ca64(qf + pairoff((4 * f + hp + j) * 9 + t, g) + 32 * b);
#pragma unroll
          for (int j = 0; j < 2; j++) {
            const uint2 z0 = ld_ca64(zp + 16 * j), z1 = ld_ca64(zp + 16 * j + 1), z2 = ld_ca64(zp + 16 * j + 8);
            if (t != 0) q[j][2] = make_uint2(par, 0u);
            ll_chk(bad, z0.x, z1.x, par); ll_chk(bad, z2.x, q[j][2].x, par); ll_chk(bad, q[j][0].x, q[j][1].x, par);
            d[2 * j] = bf_lo(q[j][0].x) * __uint_as_float(z0.x) + bf_hi(q[j][0].x) * __uint_as_float(z0.y) + bf_lo(q[j][1].x) * __uint_as_float(z1.x) + bf_hi(q[j][1].x) * __uint_as_float(z1.y) +
                       bf_lo(q[j][2].x) * __uint_as_float(z2.x) + bf_hi(q[j][2].x) * __uint_as_float(z2.y);
            d[2 * j + 1] = bf_lo(q[j][0].y) * __uint_as_float(z0.x) + bf_hi(q[j][0].y) * __uint_as_float(z0.y) + bf_lo(q[j][1].y) * __uint_as_float(z1.x) + bf_hi(q[j][1].y) * __uint_as_float(z1.y) +
                           bf_lo(q[j][2].y) * __uint_as_float(z2.x) + bf_hi(q[j][2].y) * __uint_as_float(z2.y);
          }
        } while (__any_sync(0xffffffffu, bad & 1) && ++tries < (1 << 20));
#pragma unroll
        for (int j = 0; j < 4; j++) d[j] += __shfl_xor_sync(0xffffffffu, d[j], 1);
#pragma unroll
        for (int j = 0; j < 4; j++) d[j] = rcpf(d[j] + __shfl_xor_sync(0xffffffffu, d[j], 2) + 1e-6f);
        if (hp == 0) { asm volatile("cp.async.bulk.wait_group.read 0;" ::: "memory"); __syncwarp(); }
#pragma unroll
        for (int j = 0; j < 2; j++) {
          const uint32_t r0 = pack_bf16(d[2 * j], d[2 * j]), r1 = pack_bf16(d[2 * j + 1], d[2 * j + 1]);
#pragma unroll
          for (int b = 0; b < 3; b++)
            if (b < 2 || t == 0) {
              stg[g * 36 + (hp + j) * 9 + 4 * b + t] = hfma2(q[j][b].x, r0, 0x80008000u);
              stg[(g + 8) * 36 + (hp + j) * 9 + 4 * b + t] = hfma2(q[j][b].y, r1, 0x80008000u);
            }
        }
        if (hp != 0) {
          asm volatile("fence.proxy.async.shared::cta;" ::: "memory");
          __syncwarp();
          if (lane == 0) {
            asm volatile("cp.async.bulk.tensor.2d.global.shared::cta.bulk_group [%0, {%2, %3}], [%1];" ::"l"(&P.tm_ast), "r"(smem_u32(stg)), "r"(72 * f), "r"(m * 128 + rbl * 16) : "memory");
            asm volatile("cp.async.bulk.commit_group;" ::: "memory");
          }
        }
      }
      asm volatile("cp.async.bulk.wait_group 0;" ::: "memory");
      asm volatile("fence.proxy.async.global;" ::: "memory");
      STAMPW(9, 26);
      asm volatile("bar.sync 5, 96;" ::: "memory");
      if (tid == 288) asm volatile("red.release.gpu.global.add.u32 [%0], 1;" ::"l"(&g_f_a[m]) : "memory");
      __syncwarp();
      STAMPW(9, 23);
      if (srole && aw == 2) {
        if (lane == 0) {
          flag_wait(&g_f_a[m], 8 * ep);
          asm volatile("fence.proxy.async.global;" ::: "memory");
#pragma unroll 1
          for (int kb = 0; kb < 9; kb++) {
            mbar_wait(bar_xfree + 8 * kb, 0);
            mbar_expect(bar_ofull + 8 * kb, 16384);
            tma2d(sbase + SM_A + kb * 16384, &P.tm_a, kb * 64, m * 128, bar_ofull + 8 * kb);
          }
        }
        __syncwarp();
      }
    }
    cluster_arrive_relaxed();
    cluster_wait();
  } else {
    const int wg = warp >> 2;
    {
      const int rs = lane >> 3, j = lane & 7;
      uint4 xv[4][9];
#pragma unroll
      for (int it = 0; it < 4; it++)
#pragma unroll
        for (int kb = 0; kb < 9; kb++) xv[it][kb] = __ldg(reinterpret_cast<const uint4*>(P.x + (m * 128 + warp * 16 + it * 4 + rs) * D_) + j + kb * 8);
      uint32_t bw0 = __ldg(reinterpret_cast<const uint32_t*>(P.b1 + 576 * f) + tid), bw1 = tid < 32 ? __ldg(reinterpret_cast<const uint32_t*>(P.b1 + 576 * f) + 256 + tid) : 0u;
      uint2 st[4];
      int tries = 0;
      uint32_t bad;
#pragma unroll 1
      do {
        bad = 0;
#pragma unroll
        for (int it = 0; it < 4; it++) st[it] = ld_ll64(&g_stat[m * 128 + warp * 16 + it * 4 + rs]);
        ll_chk(bad, st[0].x, st[1].x, par); ll_chk(bad, st[2].x, st[3].x, par);
      } while (__any_sync(0xffffffffu, bad & 1) && ++tries < (1 << 22));
      STAMPW(0, 19);
#pragma unroll
      for (int it = 0; it < 4; it++) {
        const uint32_t nm = st[it].y;
        uint8_t* dst = smem + SM_A + (warp * 16 + it * 4 + rs) * 128 + ((j ^ ((it * 4 + rs) & 7)) << 4);
#pragma unroll
        for (int kb = 0; kb < 9; kb++) {
          const uint4 w = xv[it][kb];
          *reinterpret_cast<uint4*>(dst + kb * 16384) = make_uint4(hadd2(w.x, nm), hadd2(w.y, nm), hadd2(w.z, nm), hadd2(w.w, nm));
        }
        if (j == 0) reinterpret_cast<uint32_t*>(smem + SM_RSTD)[warp * 16 + it * 4 + rs] = st[it].x;
      }
      reinterpret_cast<float2*>(smem + SM_BIAS)[tid] = make_float2(bf_lo(bw0) * GK, bf_hi(bw0) * GK);
      if (tid < 48) reinterpret_cast<float2*>(smem + SM_BIAS)[256 + tid] = make_float2(bf_lo(bw1) * GK, bf_hi(bw1) * GK);
      asm volatile("fence.proxy.async.shared::cta;" ::: "memory");
    }
    asm volatile("setmaxnreg.inc.sync.aligned.u32 232;");
    cluster_wait();
    asm volatile("bar.sync 1, 256;" ::: "memory");
    STAMPW(0, 1);
    Ctx c;
    c.full = bar_full; c.budget = 1 << 22;
    c.emb = __shfl_sync(0xffffffffu, mapa(bar_empty, (warp & 3) == 0 ? rank : (rank ^ 1)), 0);
    c.sig = lane == 0 && (warp & 3) < 2;
    c.dB = (((sbase + SM_B) & 0x3FFFF) >> 4) | ((4096u >> 4) << 16);
    c.dA = (((sbase + SM_A + wg * 8192) & 0x3FFFF) >> 4) | (1u << 16);
    const bool leader = (lane == 0) && ((warp & 3) == 0);

    const int rb = m * 8 + warp;
    const uint32_t bias_t = sbase + SM_BIAS + 8 * t;
    const uint32_t hst = sbase + SM_A + (warp * 16 + (lane & 7) + ((lane >> 3) & 1) * 8) * 128 + (((lane >> 4) ^ (lane & 7)) << 4);
    auto wg_sync = [&]() {
      asm volatile("fence.proxy.async.shared::cta;" ::: "memory");
      if (wg == 0) asm volatile("bar.sync 2, 128;" ::: "memory"); else asm volatile("bar.sync 3, 128;" ::: "memory");
    };
    float A[96], B[96];
#pragma unroll
    for (int i = 0; i < 96; i++) B[i] = 0.f;
#define EXB(ACC, U) uint32_t E[4]; _Pragma("unroll") for (int q = 0; q < 4; q++) E[q] = pack_bf16(fmaf(ACC[8 * (U) + 2 * q], (q & 1) ? r1 : r0, bs[q >> 1].x), fmaf(ACC[8 * (U) + 2 * q + 1], (q & 1) ? r1 : r0, bs[q >> 1].y));
#define ST_QKV(ACC, U, DST) { uint32_t E[4]; _Pragma("unroll") for (int q = 0; q < 4; q++) \
      E[q] = phi_pack(pack_bf16(ACC[8 * (U) + 2 * q] * ((q & 1) ? r1 : r0), ACC[8 * (U) + 2 * q + 1] * ((q & 1) ? r1 : r0)), ACC[8 * (U) + 2 * q] * ((q & 1) ? l1 : l0), ACC[8 * (U) + 2 * q + 1] * ((q & 1) ? l1 : l0), pc1, pc2); \
    st_ll64(reinterpret_cast<uint2*>(DST) + 64 * (U), E[0], E[1], par); st_ll64(reinterpret_cast<uint2*>(DST) + 64 * (U) + 32, E[2], E[3], par); }
#define PHI_SETUP const float l0 = r0 * 1.4426950408889634f, l1 = r1 * 1.4426950408889634f; const uint32_t pc1 = f < 4 ? 0x35863586u : 0xff80ff80u, pc2 = f < 4 ? 0x3f803f80u : 0u;
#define HADDR(KB0, U) ((hst ^ (((U) & 3) << 5)) + ((KB0) + ((U) >> 2)) * 16384)
#define LDS_R(SC) float r0, r1; asm volatile("ld.shared.f32 %0, [%1];" : "=f"(r0) : "r"(rst)); asm volatile("ld.shared.f32 %0, [%1];" : "=f"(r1) : "r"(rst + 32)); r0 *= (SC); r1 *= (SC);
    const uint32_t rst = sbase + SM_RSTD + (warp * 16 + g) * 4;
    const int fr = f % 3;
#pragma unroll 1
    for (int i = srole;; i++) {
      {
        c.set((!srole && i >= 1) ? 1u : 0u, 0u);
        const uint32_t ow = i == 4 ? bar_ofull : 0u;
        if (ow) c.wait(ow, 0);
        issue192(A, c, 0, true);
        const int ln = opaque(lane);
        uint4* dst = i == 1 ? reinterpret_cast<uint4*>(g_qkv + (rb * 216 + 36 * f + 24) * 32 + ln) : g_part + ((rb * 8 + f) * 36 + 12 * (i == 3 ? fr : (fr + 2) % 3)) * 32 + ln;
        LDS_R(i == 2 ? GK : 1.f)
        wg_wait<1>();
        if (i != srole) c.release(5);
        if (ow && leader) mbar_arrive(bar_xfree + 64);
        fence_regs<96>(B);
        int s = 1;
        if (i == 2) {
#pragma unroll
          for (int k = 1; k < 9; k++) {
            float2 b0[2], b1[2];
            if (k >= 3) { lds_bias(b0, bias_t + (192 + 32 * (k - 3)) * 4); lds_bias(b1, bias_t + (208 + 32 * (k - 3)) * 4); }
            issue192(A, c, k);
            if (k >= 3) {
              const int u = k >= 3 ? 2 * (k - 3) : 0;
              { const float2* bs = b0; EXB(B, u) stsm4(HADDR(0, u), gelu_group(E)); }
              { const float2* bs = b1; EXB(B, u + 1) stsm4(HADDR(0, u + 1), gelu_group(E)); }
            }
            retire(c, k - 1);
          }
          s = 9;
        } else if (i >= 3) {
#pragma unroll
          for (int u = 0; u < 12; u++) {
            if ((u & 1) && ow) c.wait(ow + 4 * (u + 1), 0);
            issue192(A, c, u + 1);
            part_groups<0, 1>(&B[8 * u], dst + u * 32, par);
            retire(c, u);
          }
          s = 13;
        } else if (i > srole) {
          PHI_SETUP
#pragma unroll
          for (int u = 0; u < 6; u++) {
            issue192(A, c, u + 1);
            ST_QKV(B, u, dst)
            retire(c, u);
          }
          hint_signal(&g_f_qkv[m * 8 + f]);
          s = 7;
        }
        const bool d1 = i == 1 + srole;
        const int send = d1 ? 11 : 15;
#pragma unroll 1
        for (; s < send; s++) {
          if (ow && !(s & 1)) c.wait(ow + 4 * s, 0);
          issue192(A, c, s);
          retire(c, s - 1);
        }
        uint32_t W[48];
        if (d1) {
          const int head = 4 * f + (warp >> 1), rb0 = m * 8 + (warp & 1) * 4;
          issue192(A, c, 11);
          c.wait(bar_d, 0);
          d1_load<false>(W, rb0, head, opaque(lane));
          retire(c, 10);
          issue192(A, c, 12);
          retire(c, 11);
          issue192(A, c, 13);
          int tries = 0;
#pragma unroll 1
          while (d1_bad(W, t, par) && ++tries < (1 << 20)) d1_load<true>(W, rb0, head, opaque(lane));
          d1_mov(W, 0, t); d1_mov(W, 1, t);
          retire(c, 12);
          issue192(A, c, 14);
          d1_mov(W, 2, t); d1_mov(W, 3, t);
          wg_wait<0>();
          asm volatile("bar.sync 4, 256;" ::: "memory");
          float R[18];
          d1_mma(W, R);
          float2* xch = reinterpret_cast<float2*>(smem + SM_SCR + (warp >> 1) * 1792) + opaque(lane);
          if (warp & 1) {
#pragma unroll
            for (int q = 0; q < 6; q++) xch[q * 32] = make_float2(R[2 * q], R[2 * q + 1]);
            if (lane < 12) { xch[192] = make_float2(R[12], R[13]); xch[204] = make_float2(R[14], R[15]); if (t == 0) xch[216 - lane + g] = make_float2(R[16], R[17]); }
          } else if (R[17] == 1.2345e-30f) R[16] = 0.f;
          asm volatile("bar.sync 4, 256;" ::: "memory");
          retire(c, 13);
          issue192(A, c, 15);
          if (!(warp & 1)) {
            const int l2 = opaque(lane);
#pragma unroll
            for (int q = 0; q < 6; q++) { const float2 o = xch[q * 32]; R[2 * q] += o.x; R[2 * q + 1] += o.y; }
            if (l2 < 12) {
              const float2 o0 = xch[192], o1 = xch[204], o2 = xch[216 - l2 + (l2 >> 2)];
              R[12] += o0.x; R[13] += o0.y; R[14] += o1.x; R[15] += o1.y; R[16] += o2.x; R[17] += o2.y;
            }
            uint4* dkv = &g_kvp[(head * 80 + m) * 32 + l2];
#pragma unroll
            for (int w = 0; w < 5; w++)
              if (kv_valid(w, l2)) st_ll(dkv + w * 512, __float_as_uint(R[4 * w]), __float_as_uint(R[4 * w + 1]), w < 4 ? __float_as_uint(R[4 * w + 2]) : 0u, w < 4 ? __float_as_uint(R[4 * w + 3]) : 0u, par);
            __syncwarp();
            hint_signal(&g_f_kvp[head]);
          }
          STAMPW(0, 21);
        } else issue192(A, c, 15);
        if (i == 2) {
          const uint4* hsp = g_hsp + (blockIdx.x * 8 + warp) * 12 * 32 + opaque(lane);
#pragma unroll
          for (int q = 0; q < 12; q++) { const uint4 v = ldcg128(hsp + q * 32); W[4 * q] = v.x; W[4 * q + 1] = v.y; W[4 * q + 2] = v.z; W[4 * q + 3] = v.w; }
          retire(c, 14);
          issue192(A, c, 16);
          wg_sync();
          retire(c, 15);
          issue192(A, c, 17);
#pragma unroll
          for (int q = 0; q < 12; q++) stsm4(HADDR(3, q), make_uint4(W[4 * q], W[4 * q + 1], W[4 * q + 2], W[4 * q + 3]));
        } else {
          retire(c, 14);
          if (ow) c.wait(ow + 64, 0);
          issue192(A, c, 16);
          retire(c, 15);
          issue192(A, c, 17);
        }
        retire(c, 16);
      }
      STAMPW(0, 2 + 2 * i);
      c.set((!srole && i >= 1) ? 1u : 0u, 1u);
      if ((i & 3) == 0) {
        issue96(B, c, 0, true);
        const int ln = opaque(lane);
        uint2* dst = i == 0 ? g_qkv + (rb * 216 + 36 * f) * 32 + ln : g_s + (rb * 72 + 24 * (f - 5)) * 32 + ln;
        LDS_R(1.f)
        if (i != 0) { r0 = 1.f; r1 = 1.f; }
        PHI_SETUP
        retire(c, 5);
        fence_regs<96>(A);
#pragma unroll
        for (int k = 1; k < 9; k++) {
          issue96(B, c, k, false);
#pragma unroll
          for (int u = (3 * (k - 1) + 1) / 2; u < (3 * k + 1) / 2; u++) ST_QKV(A, u, dst)
          retire(c, k - 1);
        }
        if (i == 4) {
          STAMPW(0, 11);
          wg_wait<0>();
          c.release(8);
          fence_regs<48>(B);
          uint2* d2 = g_s + (rb * 72 + 12 * (f - 6)) * 32 + opaque(lane);
#pragma unroll
          for (int q = 0; q < 12; q++) st_ll64(d2 + q * 32, pack_bf16(B[4 * q], B[4 * q + 1]), pack_bf16(B[4 * q + 2], B[4 * q + 3]), par);
          break;
        }
        hint_signal(&g_f_qkv[m * 8 + f]);
      } else {
        issue192(B, c, 0, true);
        const int ln = opaque(lane);
        uint4* dst = i == 1 ? g_hsp + (blockIdx.x * 8 + warp) * 12 * 32 + ln : g_part + ((rb * 8 + f) * 36 + 12 * ((fr + 1) % 3)) * 32 + ln;
        const bool xf = i == 3 && srole && leader;
        const uint32_t bsa = bias_t + (i == 1 ? 0 : 384) * 4;
        LDS_R(GK)
        retire(c, 5);
        fence_regs<96>(A);
        int s;
        if (i != 3) {
#pragma unroll
          for (int u = 0; u < 12; u++) {
            float2 bs[2];
            lds_bias(bs, bsa + 16 * u * 4);
            issue192(B, c, u + 1);
            EXB(A, u)
            const uint4 h = gelu_group(E);
            asm volatile("{.reg .pred p; setp.eq.s32 p, %6, 1; @p st.global.v4.u32 [%0], {%2,%3,%4,%5}; @!p stmatrix.sync.aligned.m8n8.x4.shared.b16 [%1], {%2,%3,%4,%5};}"
                         ::"l"(dst + u * 32), "r"(HADDR(6, u)), "r"(h.x), "r"(h.y), "r"(h.z), "r"(h.w), "r"(i) : "memory");
            if (u == 3 || u == 9) wg_sync();
            retire(c, u);
          }
          s = 13;
        } else {
#pragma unroll
          for (int u = 0; u < 6; u++) {
            issue192(B, c, u + 1);
            part_groups<0, 2>(&A[16 * u], dst + 2 * u * 32, par);
            retire(c, u);
            if ((u & 1) && xf) mbar_arrive(bar_xfree + 4 * u - 4);
          }
          s = 7;
        }
        if (i == 3 && !srole) {
          const int c2 = (fr + 2) % 3, v0 = 12 * c2 + (f < 3 ? 0 : 6), fo = f < 3 ? f + 3 : f - 3;
          const int l2 = opaque(lane);
          const uint4* pb = g_part + (rb * 8 * 36 + v0) * 32 + l2;
          uint4 p[12];
          uint32_t S[24];
#pragma unroll
          for (int q = 0; q < 24; q++) S[q] = 0u;
          auto ldp = [&](const uint4* a0, const uint4* a1) {
#pragma unroll
            for (int q = 0; q < 6; q++) { p[q] = ld_ll(a0 + q * 32); p[6 + q] = ld_ll(a1 + q * 32); }
          };
          auto badp = [&]() {
            uint32_t bad = 0;
#pragma unroll
            for (int q = 0; q < 12; q++) ll_chk(bad, p[q].x, p[q].z, par);
            return __any_sync(0xffffffffu, bad & 1);
          };
#pragma unroll 1
          for (int w = 0; w < 3; w++) {
            const uint4* a0 = pb + (w == 0 ? c2 : (w == 1 ? 6 : (fr + 1) % 3)) * 36 * 32;
            const uint4* a1 = a0 + (w == 1 ? 1 : 3) * 36 * 32;
            issue192(B, c, 7 + 3 * w);
            ldp(a0, a1);
            retire(c, 6 + 3 * w);
            issue192(B, c, 8 + 3 * w);
            retire(c, 7 + 3 * w);
            issue192(B, c, 9 + 3 * w);
            int tries = 0;
#pragma unroll 1
            while (badp() && ++tries < (1 << 20)) ldp(a0, a1);
#pragma unroll
            for (int q = 0; q < 24; q++) S[q] = hadd2(S[q], hadd2(reinterpret_cast<const uint32_t*>(p)[q], reinterpret_cast<const uint32_t*>(p)[24 + q]));
            retire(c, 8 + 3 * w);
          }
          uint4 xx[6];
          uint32_t bb[12];
          int ro[6];
          issue192(B, c, 16);
#pragma unroll
          for (int j = 0; j < 6; j++) {
            const int k = l2 + 32 * j, r = (k * 171) >> 11;
            ro[j] = (rb * 16 + r) * D_ + 16 * v0 + (k - 12 * r) * 8;
            xx[j] = __ldg(reinterpret_cast<const uint4*>(P.x + ro[j]));
          }
#pragma unroll
          for (int j = 0; j < 12; j++) bb[j] = __ldg(reinterpret_cast<const uint32_t*>(P.b2 + 16 * v0 + 8 * j + 2 * (l2 & 3)));
          retire(c, 15);
          issue192(B, c, 17);
          retire(c, 16);
          STAMPW(0, 9);
          wg_wait<0>();
          c.release(17);
          fence_regs<96>(B);
          uint4* snd = g_part + ((rb * 8 + f) * 36 + 12 * c2 + (f < 3 ? 6 : 0)) * 32 + l2;
          if (f < 3) part_groups<0, 6>(B + 48, snd, par);
          else {
            part_groups<0, 6>(B, snd, par);
#pragma unroll
            for (int q = 0; q < 48; q++) B[q] = B[48 + q];
          }
          asm volatile("bar.sync 4, 256;" ::: "memory");
          STAMPW(0, 12);
#pragma unroll
          for (int q = 0; q < 24; q++) {
            B[2 * q] = fmaf(B[2 * q] + bf_lo(S[q]), 0.25f / GK, 0.5f * bf_lo(bb[q >> 1])); B[2 * q + 1] = fmaf(B[2 * q + 1] + bf_hi(S[q]), 0.25f / GK, 0.5f * bf_hi(bb[q >> 1]));
          }
          const uint2* sp = g_s + (rb * 72 + 2 * v0) * 32 + l2;
          int tries = 0;
#pragma unroll 1
          while (++tries < (1 << 20)) {
            const uint2 u0 = ld_ll64(pb + (fo * 36 + 5) * 32), u1 = ld_ll64(sp + 11 * 32);
            if (!__any_sync(0xffffffffu, ((u0.x ^ par) | (u1.x ^ par)) & 1)) break;
            __nanosleep(40);
          }
          tries = 0;
#pragma unroll 1
          do {
#pragma unroll
            for (int q = 0; q < 6; q++) {
              p[q] = ld_ll(pb + (fo * 36 + q) * 32);
              const uint2 s0 = ld_ll64(sp + 2 * q * 32), s1 = ld_ll64(sp + (2 * q + 1) * 32);
              p[6 + q] = make_uint4(s0.x, s0.y, s1.x, s1.y);
            }
          } while (badp() && ++tries < (1 << 20));
          STAMPW(0, 14);
          const uint32_t tb = sbase + SM_A + warp * 3328;
#pragma unroll
          for (int v = 0; v < 6; v++) {
            uint32_t o[4];
#pragma unroll
            for (int k = 0; k < 4; k++) {
              const int q = 4 * v + k;
              const uint32_t w = reinterpret_cast<const uint32_t*>(p)[q];
              const uint32_t gt = pack_bf16(silu_h(fmaf(bf_lo(w), 0.25f / GK, B[2 * q])), silu_h(fmaf(bf_hi(w), 0.25f / GK, B[2 * q + 1])));
              o[k] = hfma2(reinterpret_cast<const uint32_t*>(p)[24 + q], gt, 0x80008000u);
            }
            stsm4(tb + (l2 & 15) * 208 + (l2 >> 4) * 16 + v * 32, make_uint4(o[0], o[1], o[2], o[3]));
          }
          __syncwarp();
#pragma unroll
          for (int j = 0; j < 6; j++) {
            const int k = l2 + 32 * j, r = (k * 171) >> 11;
            uint4 o;
            asm volatile("ld.shared.v4.u32 {%0,%1,%2,%3}, [%4];" : "=r"(o.x), "=r"(o.y), "=r"(o.z), "=r"(o.w) : "r"(tb + r * 208 + (k - 12 * r) * 16) : "memory");
            *reinterpret_cast<uint4*>(P.out + ro[j]) = make_uint4(hadd2(o.x, xx[j].x), hadd2(o.y, xx[j].y), hadd2(o.z, xx[j].z), hadd2(o.w, xx[j].w));
          }
          break;
        }
#pragma unroll 1
        for (; s < 17; s++) {
          issue192(B, c, s);
          if (s == 14 && i == 2) wg_sync();
          retire(c, s - 1);
          if ((s & 1) == 0 && xf) mbar_arrive(bar_xfree + 4 * s - 8);
        }
        issue192(B, c, 17);
        retire(c, 16);
      }
      STAMPW(0, 3 + 2 * i);
    }
    STAMPW(0, 15);
    cluster_arrive_relaxed();
    cluster_wait();
    STAMPW(0, 16);
    if (tid == 0) g_epoch[blockIdx.x] = ep;
  }
}

typedef CUresult (*EncFn)(CUtensorMap*, CUtensorMapDataType, cuuint32_t, void*, const cuuint64_t*, const cuuint64_t*, const cuuint32_t*, const cuuint32_t*,
                          CUtensorMapInterleave, CUtensorMapSwizzle, CUtensorMapL2promotion, CUtensorMapFloatOOBfill);

void make_map(EncFn enc, CUtensorMap* tm, const void* ptr, int rows, int cols, int box_rows, int mode = 0) {
  cuuint64_t gd[2] = {(cuuint64_t)cols, (cuuint64_t)rows};
  cuuint64_t gs[1] = {(cuuint64_t)cols * 2};
  cuuint32_t bx[2] = {mode == 1 ? 32u : (mode == 2 ? 72u : 64u), (cuuint32_t)box_rows};
  cuuint32_t es[2] = {1, 1};
  enc(tm, CU_TENSOR_MAP_DATA_TYPE_BFLOAT16, 2, const_cast<void*>(ptr), gd, gs, bx, es, CU_TENSOR_MAP_INTERLEAVE_NONE, mode == 1 ? CU_TENSOR_MAP_SWIZZLE_64B : (mode == 2 ? CU_TENSOR_MAP_SWIZZLE_NONE : CU_TENSOR_MAP_SWIZZLE_128B),
      CU_TENSOR_MAP_L2_PROMOTION_L2_256B, CU_TENSOR_MAP_FLOAT_OOB_FILL_NONE);
}

}

extern "C" void kernel_launch(void* const* d_in, const int* in_sizes, int n_in, void* d_out, int out_size) {
  (void)in_sizes; (void)n_in; (void)out_size;
  static EncFn enc = nullptr;
  static void *a_ptr = nullptr, *m_ptr = nullptr;
  if (!enc) {
    void* fn = nullptr; cudaDriverEntryPointQueryResult q;
    cudaGetDriverEntryPoint("cuTensorMapEncodeTiled", &fn, cudaEnableDefault, &q);
    enc = (EncFn)fn;
    cudaFuncSetAttribute(fused_kernel, cudaFuncAttributeMaxDynamicSharedMemorySize, SMEM_BYTES);
    cudaGetSymbolAddress(&a_ptr, g_a);
    cudaGetSymbolAddress(&m_ptr, g_m);
  }
  Params P;
  P.x = (const __nv_bfloat16*)d_in[0];
  P.wqkv = (const __nv_bfloat16*)d_in[1];
  P.wo = (const __nv_bfloat16*)d_in[2];
  P.w1 = (const __nv_bfloat16*)d_in[4];
  P.b1 = (const __nv_bfloat16*)d_in[5];
  P.w2 = (const __nv_bfloat16*)d_in[6];
  P.b2 = (const __nv_bfloat16*)d_in[7];
  P.out = (__nv_bfloat16*)d_out;
  make_map(enc, &P.tm_wqkv, P.wqkv, D_, Q3_, 32);
  make_map(enc, &P.tm_w1, P.w1, D_, F_, 32);
  make_map(enc, &P.tm_w2, P.w2, F_, D_, 32);
  make_map(enc, &P.tm_m, m_ptr, D_, D_, 32);
  make_map(enc, &P.tm_wqkv64, P.wqkv, D_, Q3_, 64, 1);
  make_map(enc, &P.tm_m64, m_ptr, D_, D_, 64, 1);
  make_map(enc, &P.tm_a, a_ptr, S_, D_, 128);
  make_map(enc, &P.tm_ast, a_ptr, S_, D_, 16, 2);
  fused_kernel<<<NCTAS, NTHREADS, SMEM_BYTES, cudaStreamPerThread>>>(P);
}
```

```cpp
#include <cuda_runtime.h>
#include <cuda.h>
#include <cuda_bf16.h>
#include <stdint.h>

namespace {

constexpr int S_ = 2048, D_ = 576, F_ = 4608, Q3_ = 1728;
constexpr int NSTAGE = 6, STAGE_BYTES = 12288;
constexpr int SM_A = 0, SM_B = 147456, SM_BIAS = SM_B + NSTAGE * STAGE_BYTES, SM_RSTD = SM_BIAS + 2304 + 128, SM_SCR = SM_RSTD + 512, SM_BAR = SM_SCR + 7168;
constexpr int SMEM_BYTES = SM_BAR + 320;
constexpr int NTHREADS = 384;
constexpr int NCTAS = 132;

__device__ uint2 g_qkv[(128 * 216 + 2) * 32];
__device__ __align__(1024) __nv_bfloat16 g_a[S_ * D_];
__device__ __align__(1024) __nv_bfloat16 g_m[D_ * D_];
__device__ uint4 g_kvp[32 * 5 * 16 * 32];
__device__ uint4 g_z[32 * 2 * 4];
__device__ uint4 g_part[128 * 8 * 36 * 32];
__device__ uint2 g_s[128 * 72 * 32];
__device__ uint4 g_hsp[128 * 12 * 256];
__device__ uint32_t g_f_qkv[16 * 8];
__device__ uint32_t g_f_kvp[32];
__device__ uint32_t g_f_z[32];
__device__ uint32_t g_f_a[16];
__device__ uint32_t g_f_m[1];
__device__ uint2 g_stat[S_];
__device__ uint32_t g_epoch[NCTAS];

#define STAMP(i)
#define STAMPW(w, i)
#define WSTAMP(i)
__device__ __forceinline__ uint32_t smem_u32(const void* p) { return (uint32_t)__cvta_generic_to_shared(p); }
__device__ __forceinline__ void mbar_init(uint32_t a, int c) { asm volatile("mbarrier.init.shared::cta.b64 [%0], %1;" ::"r"(a), "r"(c)); }
__device__ __forceinline__ void mbar_expect(uint32_t a, uint32_t b) { asm volatile("mbarrier.arrive.expect_tx.shared::cta.b64 _, [%0], %1;" ::"r"(a), "r"(b) : "memory"); }
__device__ __forceinline__ void mbar_arrive(uint32_t a) { asm volatile("mbarrier.arrive.shared::cta.b64 _, [%0];" ::"r"(a) : "memory"); }
__device__ __forceinline__ void mbar_arrive_cl(uint32_t a) { asm volatile("mbarrier.arrive.shared::cluster.b64 _, [%0];" ::"r"(a) : "memory"); }
__device__ __forceinline__ uint32_t mapa(uint32_t a, uint32_t cta) { uint32_t r; asm volatile("mapa.shared::cluster.u32 %0, %1, %2;" : "=r"(r) : "r"(a), "r"(cta)); return r; }
__device__ __forceinline__ void mbar_wait(uint32_t a, uint32_t ph) {
  uint32_t ok; int it = 0;
#pragma unroll 1
  do {
    asm volatile("{.reg .pred p; mbarrier.try_wait.parity.shared::cta.b64 p, [%1], %2; selp.u32 %0,1,0,p;}" : "=r"(ok) : "r"(a), "r"(ph) : "memory");
  } while (!ok && ++it < (1 << 18));
}
__device__ __forceinline__ void tma2d(uint32_t dst, const CUtensorMap* m, int c0, int c1, uint32_t bar) {
  asm volatile("cp.async.bulk.tensor.2d.shared::cluster.global.mbarrier::complete_tx::bytes [%0], [%1, {%3,%4}], [%2];" ::"r"(dst), "l"(m), "r"(bar), "r"(c0), "r"(c1) : "memory");
}
__device__ __forceinline__ void tma2d_mc(uint32_t dst, const CUtensorMap* m, int c0, int c1, uint32_t bar) {
  asm volatile("cp.async.bulk.tensor.2d.shared::cluster.global.mbarrier::complete_tx::bytes.multicast::cluster [%0], [%1, {%3,%4}], [%2], %5;" ::"r"(dst), "l"(m), "r"(bar), "r"(c0), "r"(c1), "h"((uint16_t)3) : "memory");
}
__device__ __forceinline__ void cluster_arrive_relaxed() { asm volatile("barrier.cluster.arrive.relaxed.aligned;" ::: "memory"); }
__device__ __forceinline__ void cluster_wait() { asm volatile("barrier.cluster.wait.acquire.aligned;" ::: "memory"); }
__device__ __forceinline__ void wg_fence() { asm volatile("wgmma.fence.sync.aligned;" ::: "memory"); }
__device__ __forceinline__ void wg_commit() { asm volatile("wgmma.commit_group.sync.aligned;" ::: "memory"); }
template <int n> __device__ __forceinline__ void wg_wait() { asm volatile("wgmma.wait_group.sync.aligned %0;" ::"n"(n) : "memory"); }
__device__ __forceinline__ uint32_t ld_acquire(const uint32_t* p) { uint32_t v; asm volatile("ld.acquire.gpu.global.u32 %0, [%1];" : "=r"(v) : "l"(p) : "memory"); return v; }
__device__ __forceinline__ void flag_wait(const uint32_t* p, uint32_t target) {
  int it = 0;
#pragma unroll 1
  while ((int)(ld_acquire(p) - target) < 0 && ++it < (1 << 20)) __nanosleep(300);
}
__device__ __forceinline__ void hint_signal(uint32_t* p) {
  if ((threadIdx.x & 31) == 0) asm volatile("red.relaxed.gpu.global.add.u32 [%0], 1;" ::"l"(p) : "memory");
}
__device__ __forceinline__ void hint_wait(const uint32_t* p, uint32_t target, uint32_t ns = 400) {
  int it = 0; uint32_t v;
#pragma unroll 1
  do { asm volatile("ld.relaxed.gpu.global.u32 %0, [%1];" : "=r"(v) : "l"(p) : "memory"); if ((int)(v - target) >= 0) break; __nanosleep(ns); } while (++it < (1 << 20));
}
__device__ __forceinline__ uint32_t tag(uint32_t x, uint32_t par) { uint32_t r; asm("lop3.b32 %0, %1, 0xfffffffe, %2, 0xea;" : "=r"(r) : "r"(x), "r"(par)); return r; }
__device__ __forceinline__ void st_ll(uint4* p, uint32_t x, uint32_t y, uint32_t z, uint32_t w, uint32_t par) {
  asm volatile("{.reg .b64 a, b; mov.b64 a, {%1,%2}; mov.b64 b, {%3,%4}; st.relaxed.gpu.global.v2.b64 [%0], {a, b};}"
               ::"l"(p), "r"(tag(x, par)), "r"(y), "r"(tag(z, par)), "r"(w) : "memory");
}
__device__ __forceinline__ uint4 ld_ll(const uint4* p) {
  uint4 v;
  asm volatile("{.reg .b64 a, b; ld.relaxed.gpu.global.v2.b64 {a, b}, [%4]; mov.b64 {%0,%1}, a; mov.b64 {%2,%3}, b;}"
               : "=r"(v.x), "=r"(v.y), "=r"(v.z), "=r"(v.w) : "l"(p) : "memory");
  return v;
}
__device__ __forceinline__ void st_ll64(uint2* p, uint32_t x, uint32_t y, uint32_t par) {
  asm volatile("{.reg .b64 a; mov.b64 a, {%1,%2}; st.relaxed.gpu.global.b64 [%0], a;}" ::"l"(p), "r"(tag(x, par)), "r"(y) : "memory");
}
__device__ __forceinline__ uint2 ld_ca64(const void* p) {
  uint2 v;
  asm volatile("{.reg .b64 a; ld.global.ca.b64 a, [%2]; mov.b64 {%0,%1}, a;}" : "=r"(v.x), "=r"(v.y) : "l"(p) : "memory");
  return v;
}
__device__ __forceinline__ uint2 ld_ll64(const void* p) {
  uint2 v;
  asm volatile("{.reg .b64 a; ld.relaxed.gpu.global.b64 a, [%2]; mov.b64 {%0,%1}, a;}" : "=r"(v.x), "=r"(v.y) : "l"(p) : "memory");
  return v;
}
__device__ __forceinline__ void ll_chk(uint32_t& bad, uint32_t a, uint32_t b, uint32_t par) {
  uint32_t u; asm("lop3.b32 %0, %1, %2, %3, 0x7e;" : "=r"(u) : "r"(a), "r"(b), "r"(par));
  asm("or.b32 %0, %0, %1;" : "+r"(bad) : "r"(u));
}
__device__ __forceinline__ uint32_t hadd2(uint32_t a, uint32_t b) { uint32_t d; asm("add.rn.bf16x2 %0, %1, %2;" : "=r"(d) : "r"(a), "r"(b)); return d; }
__device__ __forceinline__ uint32_t hfma2(uint32_t a, uint32_t b, uint32_t c) { uint32_t d; asm("fma.rn.bf16x2 %0, %1, %2, %3;" : "=r"(d) : "r"(a), "r"(b), "r"(c)); return d; }
__device__ __forceinline__ uint32_t pack_bf16(float lo, float hi) { uint32_t r; asm("cvt.rn.bf16x2.f32 %0, %1, %2;" : "=r"(r) : "f"(hi), "f"(lo)); return r; }
__device__ __forceinline__ float bf_lo(uint32_t v) { return __uint_as_float(v << 16); }
__device__ __forceinline__ float bf_hi(uint32_t v) { return __uint_as_float(v & 0xffff0000u); }
__device__ __forceinline__ uint32_t movmat(uint32_t a) { uint32_t d; asm volatile("movmatrix.sync.aligned.m8n8.trans.b16 %0, %1;" : "=r"(d) : "r"(a)); return d; }
__device__ __forceinline__ void mma16816(float* c, uint32_t a0, uint32_t a1, uint32_t a2, uint32_t a3, uint32_t b0, uint32_t b1) {
  asm volatile("mma.sync.aligned.m16n8k16.row.col.f32.bf16.bf16.f32 {%0,%1,%2,%3}, {%4,%5,%6,%7}, {%8,%9}, {%0,%1,%2,%3};"
               : "+f"(c[0]), "+f"(c[1]), "+f"(c[2]), "+f"(c[3]) : "r"(a0), "r"(a1), "r"(a2), "r"(a3), "r"(b0), "r"(b1));
}
__device__ __forceinline__ uint4 ldcg128(const void* p) { uint4 v; asm volatile("ld.global.cg.v4.u32 {%0,%1,%2,%3}, [%4];" : "=r"(v.x), "=r"(v.y), "=r"(v.z), "=r"(v.w) : "l"(p) : "memory"); return v; }

template <int N> __device__ __forceinline__ void wgmma_ss(float* d, uint32_t alo, int aimm, uint32_t blo, int bimm, uint32_t bhi, int sc);
template <> __device__ __forceinline__ void wgmma_ss<96>(float* d, uint32_t alo, int aimm, uint32_t blo, int bimm, uint32_t bhi, int sc) {
  asm volatile("{.reg .pred p; .reg .b32 x, y; .reg .b64 da, db; setp.ne.b32 p, %53, 0; add.u32 x, %48, %49; add.u32 y, %50, %51; mov.b64 da, {x, 0x40000040}; mov.b64 db, {y, %52}; "
               "wgmma.mma_async.sync.aligned.m64n96k16.f32.bf16.bf16 {%0, %1, %2, %3, %4, %5, %6, %7, %8, %9, %10, %11, %12, %13, %14, %15, %16, %17, %18, %19, %20, %21, %22, %23, %24, %25, %26, %27, %28, %29, %30, %31, %32, %33, %34, %35, %36, %37, %38, %39, %40, %41, %42, %43, %44, %45, %46, %47}, da, db, p, 1, 1, 0, 1;}"
   : "+f"(d[0]), "+f"(d[1]), "+f"(d[2]), "+f"(d[3]), "+f"(d[4]), "+f"(d[5]), "+f"(d[6]), "+f"(d[7]), "+f"(d[8]), "+f"(d[9]), "+f"(d[10]), "+f"(d[11]), "+f"(d[12]), "+f"(d[13]), "+f"(d[14]), "+f"(d[15]), "+f"(d[16]), "+f"(d[17]), "+f"(d[18]), "+f"(d[19]), "+f"(d[20]), "+f"(d[21]), "+f"(d[22]), "+f"(d[23]), "+f"(d[24]), "+f"(d[25]), "+f"(d[26]), "+f"(d[27]), "+f"(d[28]), "+f"(d[29]), "+f"(d[30]), "+f"(d[31]), "+f"(d[32]), "+f"(d[33]), "+f"(d[34]), "+f"(d[35]), "+f"(d[36]), "+f"(d[37]), "+f"(d[38]), "+f"(d[39]), "+f"(d[40]), "+f"(d[41]), "+f"(d[42]), "+f"(d[43]), "+f"(d[44]), "+f"(d[45]), "+f"(d[46]), "+f"(d[47]) : "r"(alo), "r"(aimm), "r"(blo), "r"(bimm), "r"(bhi), "r"(sc));
}
template <> __device__ __forceinline__ void wgmma_ss<192>(float* d, uint32_t alo, int aimm, uint32_t blo, int bimm, uint32_t bhi, int sc) {
  asm volatile("{.reg .pred p; .reg .b32 x, y; .reg .b64 da, db; setp.ne.b32 p, %101, 0; add.u32 x, %96, %97; add.u32 y, %98, %99; mov.b64 da, {x, 0x40000040}; mov.b64 db, {y, %100}; "
               "wgmma.mma_async.sync.aligned.m64n192k16.f32.bf16.bf16 {%0, %1, %2, %3, %4, %5, %6, %7, %8, %9, %10, %11, %12, %13, %14, %15, %16, %17, %18, %19, %20, %21, %22, %23, %24, %25, %26, %27, %28, %29, %30, %31, %32, %33, %34, %35, %36, %37, %38, %39, %40, %41, %42, %43, %44, %45, %46, %47, %48, %49, %50, %51, %52, %53, %54, %55, %56, %57, %58, %59, %60, %61, %62, %63, %64, %65, %66, %67, %68, %69, %70, %71, %72, %73, %74, %75, %76, %77, %78, %79, %80, %81, %82, %83, %84, %85, %86, %87, %88, %89, %90, %91, %92, %93, %94, %95}, da, db, p, 1, 1, 0, 1;}"
   : "+f"(d[0]), "+f"(d[1]), "+f"(d[2]), "+f"(d[3]), "+f"(d[4]), "+f"(d[5]), "+f"(d[6]), "+f"(d[7]), "+f"(d[8]), "+f"(d[9]), "+f"(d[10]), "+f"(d[11]), "+f"(d[12]), "+f"(d[13]), "+f"(d[14]), "+f"(d[15]), "+f"(d[16]), "+f"(d[17]), "+f"(d[18]), "+f"(d[19]), "+f"(d[20]), "+f"(d[21]), "+f"(d[22]), "+f"(d[23]), "+f"(d[24]), "+f"(d[25]), "+f"(d[26]), "+f"(d[27]), "+f"(d[28]), "+f"(d[29]), "+f"(d[30]), "+f"(d[31]), "+f"(d[32]), "+f"(d[33]), "+f"(d[34]), "+f"(d[35]), "+f"(d[36]), "+f"(d[37]), "+f"(d[38]), "+f"(d[39]), "+f"(d[40]), "+f"(d[41]), "+f"(d[42]), "+f"(d[43]), "+f"(d[44]), "+f"(d[45]), "+f"(d[46]), "+f"(d[47]), "+f"(d[48]), "+f"(d[49]), "+f"(d[50]), "+f"(d[51]), "+f"(d[52]), "+f"(d[53]), "+f"(d[54]), "+f"(d[55]), "+f"(d[56]), "+f"(d[57]), "+f"(d[58]), "+f"(d[59]), "+f"(d[60]), "+f"(d[61]), "+f"(d[62]), "+f"(d[63]), "+f"(d[64]), "+f"(d[65]), "+f"(d[66]), "+f"(d[67]), "+f"(d[68]), "+f"(d[69]), "+f"(d[70]), "+f"(d[71]), "+f"(d[72]), "+f"(d[73]), "+f"(d[74]), "+f"(d[75]), "+f"(d[76]), "+f"(d[77]), "+f"(d[78]), "+f"(d[79]), "+f"(d[80]), "+f"(d[81]), "+f"(d[82]), "+f"(d[83]), "+f"(d[84]), "+f"(d[85]), "+f"(d[86]), "+f"(d[87]), "+f"(d[88]), "+f"(d[89]), "+f"(d[90]), "+f"(d[91]), "+f"(d[92]), "+f"(d[93]), "+f"(d[94]), "+f"(d[95]) : "r"(alo), "r"(aimm), "r"(blo), "r"(bimm), "r"(bhi), "r"(sc));
}

constexpr uint32_t DESC_HI = (1024u >> 4) | (1u << 30);
constexpr uint32_t DESC_HI64 = (512u >> 4) | (2u << 30);
template <int n> __device__ __forceinline__ void fence_regs(float* a) {
#pragma unroll
  for (int i = 0; i < n; i++) asm volatile("" : "+f"(a[i])::"memory");
}

struct Ctx {
  uint32_t full, emb;
  bool sig;
  uint32_t o0, o1;
  uint32_t p0, p1;
  uint32_t dB, dA;
  int budget;
  __device__ __forceinline__ static int m6(int s) { return s >= 12 ? s - 12 : (s >= 6 ? s - 6 : s); }
  __device__ __forceinline__ uint32_t hb(int s) const { return m6(s) < 3 ? o0 : o1; }
  __device__ __forceinline__ static int m3(int s) { return m6(s) < 3 ? m6(s) : m6(s) - 3; }
  __device__ __forceinline__ void release(int s) { if (sig) mbar_arrive_cl(emb + 8 * hb(s) + 8 * m3(s)); }
  __device__ __forceinline__ void wait(uint32_t a, uint32_t ph) {
    uint32_t ok;
#pragma unroll 1
    do {
      asm volatile("{.reg .pred p; mbarrier.try_wait.parity.shared::cta.b64 p, [%1], %2; selp.u32 %0,1,0,p;}" : "=r"(ok) : "r"(a), "r"(ph) : "memory");
      budget--;
    } while ((ok == 0) & (budget > 0));
  }
  __device__ __forceinline__ void wait_full(int s) {
    const uint32_t a = full + 8 * hb(s) + 8 * m3(s), ph = (m6(s) < 3 ? p0 : p1) ^ ((s >= 6 && s < 12) ? 1u : 0u);
    wait(a, ph);
    wg_fence();
  }
  __device__ __forceinline__ void set(uint32_t sw, uint32_t second) { o0 = sw ? 3 : 0; o1 = 3 - o0; p0 = second; p1 = second ^ sw; }
};

__device__ __forceinline__ void issue192(float* acc, Ctx& c, int s, bool first = false) {
  c.wait_full(s);
  const uint32_t db = c.dB + c.hb(s) * (STAGE_BYTES >> 4);
  wgmma_ss<192>(acc, c.dA, (s >> 1) * 1024 + (s & 1) * 4, db, Ctx::m3(s) * (STAGE_BYTES >> 4), DESC_HI, first ? 0 : 1);
  wgmma_ss<192>(acc, c.dA, (s >> 1) * 1024 + (s & 1) * 4 + 2, db, Ctx::m3(s) * (STAGE_BYTES >> 4) + 128, DESC_HI, 1);
  wg_commit();
}
template <class Pre, class Post>
__device__ __forceinline__ void plain192(float* acc, Ctx& c, int s, int e, Pre pre, Post post) {
  uint32_t st = c.hb(s) + Ctx::m3(s), pst = c.hb(s - 1) + Ctx::m3(s - 1), ph = (Ctx::m6(s) < 3 ? c.p0 : c.p1) ^ ((s >= 6 && s < 12) ? 1u : 0u);
  uint32_t da = c.dA + (s >> 1) * 1024 + (s & 1) * 4;
#pragma unroll 1
  for (; s < e; s++) {
    pre(s);
    c.wait(c.full + 8 * st, ph);
    wg_fence();
    const uint32_t db = c.dB + st * (STAGE_BYTES >> 4);
    wgmma_ss<192>(acc, da, 0, db, 0, DESC_HI, 1);
    wgmma_ss<192>(acc, da, 2, db, 128, DESC_HI, 1);
    wg_commit();
    const uint32_t rel = c.emb + 8 * pst;
    pst = st;
    st = st == 5 ? 0 : st + 1;
    ph ^= st == 0 ? 1u : 0u;
    da += (s & 1) ? 1020 : 4;
    wg_wait<1>();
    if (c.sig) mbar_arrive_cl(rel);
    post(s);
  }
}
__device__ __forceinline__ void issue96(float* acc, Ctx& c, int k, bool first) {
  c.wait_full(k);
  const uint32_t db = c.dB + c.hb(k) * (STAGE_BYTES >> 4);
  if (first) { wgmma_ss<192>(acc, c.dA, k * 1024, db, Ctx::m3(k) * (STAGE_BYTES >> 4), DESC_HI64, 0); wg_fence(); }
#pragma unroll
  for (int kk = first ? 1 : 0; kk < 4; kk++) wgmma_ss<96>(acc, c.dA, k * 1024 + 2 * kk, db, Ctx::m3(k) * (STAGE_BYTES >> 4) + 64 * kk, DESC_HI64, 1);
  wg_commit();
}
__device__ __forceinline__ void retire(Ctx& c, int prev) {
  wg_wait<1>();
  c.release(prev);
}

constexpr float GK = 0.32920349f;
__device__ __forceinline__ uint32_t gelu_pair(uint32_t y) {
  uint32_t u, th;
  asm("mul.rn.bf16x2 %0, %1, %2;" : "=r"(u) : "r"(hfma2(y, y, 0x401b401bu)), "r"(y));
  asm("tanh.approx.bf16x2 %0, %1;" : "=r"(th) : "r"(u));
  return hfma2(y, th, y);
}
__device__ __forceinline__ uint4 gelu_group(const uint32_t* a) { return make_uint4(gelu_pair(a[0]), gelu_pair(a[1]), gelu_pair(a[2]), gelu_pair(a[3])); }
__device__ __forceinline__ void lds_bias(float2* b, uint32_t addr) {
#pragma unroll
  for (int j = 0; j < 2; j++) asm volatile("ld.shared.v2.f32 {%0,%1}, [%2];" : "=f"(b[j].x), "=f"(b[j].y) : "r"(addr + 32 * j));
}
__device__ __forceinline__ int opaque(int v) { asm volatile("" : "+r"(v)); return v; }
__device__ __forceinline__ void stsm4(uint32_t addr, uint4 r) {
  asm volatile("stmatrix.sync.aligned.m8n8.x4.shared.b16 [%0], {%1,%2,%3,%4};" ::"r"(addr), "r"(r.x), "r"(r.y), "r"(r.z), "r"(r.w) : "memory");
}
__device__ __forceinline__ float ex2f(float x) { float r; asm("ex2.approx.ftz.f32 %0, %1;" : "=f"(r) : "f"(x)); return r; }
__device__ __forceinline__ uint32_t phi_pack(uint32_t tp, float a0, float a1, uint32_t c1, uint32_t c2) {
  uint32_t x, y;
  asm("max.bf16x2 %0, %1, %2;" : "=r"(x) : "r"(tp), "r"(c1));
  asm("min.bf16x2 %0, %1, %2;" : "=r"(y) : "r"(pack_bf16(ex2f(a0), ex2f(a1))), "r"(c2));
  return hadd2(x, y);
}
template <int q0, int q1>
__device__ __forceinline__ void part_groups(const float* a, uint4* p, uint32_t par) {
#pragma unroll
  for (int q = q0; q < q1; q++)
    st_ll(p + q * 32, pack_bf16(a[8 * q], a[8 * q + 1]), pack_bf16(a[8 * q + 2], a[8 * q + 3]), pack_bf16(a[8 * q + 4], a[8 * q + 5]), pack_bf16(a[8 * q + 6], a[8 * q + 7]), par);
}
__device__ __forceinline__ float rcpf(float x) { float r; asm("rcp.approx.ftz.f32 %0, %1;" : "=f"(r) : "f"(x)); return r; }
__device__ __forceinline__ float silu_h(float h) { float r; asm("tanh.approx.f32 %0, %1;" : "=f"(r) : "f"(h)); return fmaf(h, r, h); }
__device__ __forceinline__ int pairoff(int p, int g) { return (p >> 2) * 32 + g * 4 + (p & 3); }
template <bool STRONG, int J0, int J1> __device__ __forceinline__ void d1_load(uint32_t* W, int rb0, int head, int ln) {
  const uint2* qf = g_qkv + rb0 * 216 * 32 + pairoff(288 + head * 9 + (ln & 3), ln >> 2);
#pragma unroll
  for (int b = 0; b < 3; b++) {
#pragma unroll
    for (int j = J0; j < J1; j++) {
      const uint2* p = qf + j * 216 * 32 + 32 * b;
      const uint2 kk = STRONG ? ld_ll64(p) : ld_ca64(p), vv = STRONG ? ld_ll64(p + 72 * 32) : ld_ca64(p + 72 * 32);
      W[6 * j + 2 * b] = kk.x; W[6 * j + 2 * b + 1] = kk.y; W[24 + 6 * j + 2 * b] = vv.x; W[24 + 6 * j + 2 * b + 1] = vv.y;
    }
  }
}
__device__ __forceinline__ bool d1_bad(const uint32_t* W, int t, uint32_t par) {
  uint32_t bad = 0, bad2 = 0;
#pragma unroll
  for (int q = 0; q < 12; q++) ll_chk((q % 3) != 2 ? bad : bad2, W[2 * q], W[24 + 2 * q], par);
  return __any_sync(0xffffffffu, (bad | (t == 0 ? bad2 : 0u)) & 1);
}
__device__ __forceinline__ void d1_mov(uint32_t* W, int j, int t) {
  if (t != 0) { W[6 * j + 4] = W[6 * j + 5] = 0u; W[24 + 6 * j + 4] = W[24 + 6 * j + 5] = (t == 1 ? 0x00003f80u : 0u); }
#pragma unroll
  for (int q = 0; q < 6; q++) { W[6 * j + q] = movmat(W[6 * j + q]); W[24 + 6 * j + q] = movmat(W[24 + 6 * j + q]); }
}
__device__ __forceinline__ void d1_mma(const uint32_t* W, float* R) {
  float c1[3][4];
#pragma unroll
  for (int j = 0; j < 12; j++) { R[j] = 0.f; c1[j >> 2][j & 3] = 0.f; }
#pragma unroll
  for (int ks = 0; ks < 4; ks++)
#pragma unroll
    for (int j = 0; j < 3; j++) {
      mma16816(R + 4 * j, W[24 + 6 * ks], W[24 + 6 * ks + 2], W[24 + 6 * ks + 1], W[24 + 6 * ks + 3], W[6 * ks + 2 * j], W[6 * ks + 2 * j + 1]);
      mma16816(c1[j], W[24 + 6 * ks + 4], 0u, W[24 + 6 * ks + 5], 0u, W[6 * ks + 2 * j], W[6 * ks + 2 * j + 1]);
    }
#pragma unroll
  for (int j = 0; j < 3; j++) { R[12 + 2 * j] = c1[j][0]; R[13 + 2 * j] = c1[j][1]; }
}
__device__ __forceinline__ bool kv_valid(int w, int ln) { return (w < 3 || ln < 12) && ((w != 2 && w != 4) || (ln & 3) == 0); }

struct Params {
  CUtensorMap tm_wqkv, tm_w1, tm_w2, tm_m, tm_wqkv64, tm_m64, tm_a, tm_ast;
  const __nv_bfloat16 *x, *b1, *b2, *wqkv, *w1, *w2, *wo;
  __nv_bfloat16* out;
};

__global__ void __cluster_dims__(2, 1, 1) __launch_bounds__(NTHREADS, 1) fused_kernel(const __grid_constant__ Params P) {
  extern __shared__ __align__(1024) uint8_t smem[];
  const uint32_t sbase = smem_u32(smem);
  const int tid = threadIdx.x, lane = tid & 31;
  const int warp = __shfl_sync(0xffffffffu, tid >> 5, 0);
  const int g = lane >> 2, t = lane & 3;
  const uint32_t ep = __shfl_sync(0xffffffffu, g_epoch[blockIdx.x], 0) + 1;
  const uint32_t par = ep & 1;
  STAMPW(0, 0);

  if (blockIdx.x >= 128) {
    const int a = blockIdx.x - 128;
    constexpr int WP = 1168, SM_T = 152 * WP, SM_HB = SM_T + 8 * 32 * 80;
    if (tid == 0) {
      mbar_init(sbase + SM_HB, 1);
      asm volatile("fence.mbarrier_init.release.cluster;" ::: "memory");
      mbar_expect(sbase + SM_HB, 144 * 1152);
    }
    for (int i = tid; i < (8 * WP + 8 * 32 * 80) / 4; i += NTHREADS) reinterpret_cast<uint32_t*>(smem + 144 * WP)[i] = 0u;
    __syncthreads();
    __nanosleep(1500);
    if (tid < 144)
      asm volatile("cp.async.bulk.shared::cluster.global.mbarrier::complete_tx::bytes [%0], [%1], %2, [%3];" ::"r"(sbase + tid * WP), "l"(P.wo + (a * 144 + tid) * D_), "r"(1152), "r"(sbase + SM_HB) : "memory");
    if (warp >= 8 && lane == 0) {
      const int id = a * 4 + (warp - 8);
      constexpr uint32_t CH = 9216 * 2;
#pragma unroll 1
      for (int i = id; i < 576; i += 16) {
        const char* p = i < 288 ? (const char*)P.w1 + (size_t)i * CH : (const char*)P.w2 + (size_t)(i - 288) * CH;
        asm volatile("cp.async.bulk.prefetch.L2.global [%0], %1;" ::"l"(p), "r"(CH) : "memory");
      }
    }
    __syncwarp();
    if (lane < 8) hint_wait(&g_f_kvp[a * 8 + lane], 16 * ep, 50);
    __syncwarp();
    STAMPW(0, 1);
#pragma unroll 1
    for (int u = warp; u < 40; u += 12) {
      const int hh = u & 7, w = 4 - (u >> 3), head = a * 8 + hh;
      uint4 v[16];
      int tries = 0;
      uint32_t bad;
      const bool val = kv_valid(w, lane);
#pragma unroll 1
      do {
        bad = 0;
#pragma unroll
        for (int j = 0; j < 16; j++) v[j] = val ? ld_ll(&g_kvp[((head * 5 + w) * 16 + j) * 32 + lane]) : make_uint4(par, 0u, par, 0u);
#pragma unroll
        for (int j = 0; j < 16; j++) ll_chk(bad, v[j].x, v[j].z, par);
      } while (__any_sync(0xffffffffu, bad & 1) && ++tries < (1 << 20));
      float s0 = 0.f, s1 = 0.f, s2 = 0.f, s3 = 0.f;
#pragma unroll
      for (int j = 0; j < 16; j++) { s0 += __uint_as_float(v[j].x); s1 += __uint_as_float(v[j].y); s2 += __uint_as_float(v[j].z); s3 += __uint_as_float(v[j].w); }
      if (w >= 3) {
        if (g == 2) st_ll(&g_z[(head * 2 + w - 3) * 4 + t], __float_as_uint(s0), __float_as_uint(s1), __float_as_uint(s2), __float_as_uint(s3), par);
        __syncwarp();
        hint_signal(&g_f_z[head]);
      }
      const int e0 = w < 3 ? g : 16 + g, e1 = w < 3 ? g + 8 : 16 + g, d0 = (w < 3 ? 8 * w : (w == 3 ? 0 : 16)) + 2 * t, d1 = w < 3 ? d0 : d0 + 8;
      __nv_bfloat16* T = reinterpret_cast<__nv_bfloat16*>(smem + SM_T) + hh * 32 * 40;
      if (e0 < 18) {
        T[d0 * 40 + e0] = __float2bfloat16(s0); T[(d0 + 1) * 40 + e0] = __float2bfloat16(s1);
        T[d1 * 40 + e1] = __float2bfloat16(s2); T[(d1 + 1) * 40 + e1] = __float2bfloat16(s3);
      }
    }
    __syncthreads();
    STAMPW(0, 2);
    mbar_wait(sbase + SM_HB, 0);
#pragma unroll 1
    for (int u = warp; u < 24; u += 12) {
      const int hh = u / 3, c0 = (u % 3) * 192;
      const uint32_t* T = reinterpret_cast<const uint32_t*>(smem + SM_T) + hh * 32 * 20 + g * 20 + t;
      const uint32_t a00 = T[0], a01 = T[160], a02 = T[4], a03 = T[164], a10 = T[8], a11 = T[168], b00 = T[320], b02 = T[324], b10 = T[328];
      const uint32_t rowa = sbase + (hh * 18 + (lane & 15)) * WP + (c0 + (lane >> 4) * 8) * 2, rowb = sbase + (hh * 18 + 16 + (lane & 7)) * WP + (c0 + ((lane >> 3) & 1) * 8) * 2;
#pragma unroll 3
      for (int j = 0; j < 12; j++) {
        uint32_t w0, w1, w2, w3, w4, w5;
        asm volatile("ldmatrix.sync.aligned.m8n8.x4.trans.shared.b16 {%0,%1,%2,%3}, [%4];" : "=r"(w0), "=r"(w1), "=r"(w2), "=r"(w3) : "r"(rowa + j * 32));
        asm volatile("ldmatrix.sync.aligned.m8n8.x2.trans.shared.b16 {%0,%1}, [%2];" : "=r"(w4), "=r"(w5) : "r"(rowb + j * 32));
        float p[4][4];
#pragma unroll
        for (int q = 0; q < 4; q++) p[q][0] = p[q][1] = p[q][2] = p[q][3] = 0.f;
        mma16816(p[0], a00, a01, a02, a03, w0, w1); mma16816(p[1], a00, a01, a02, a03, w2, w3);
        mma16816(p[2], b00, 0u, b02, 0u, w0, w1); mma16816(p[3], b00, 0u, b02, 0u, w2, w3);
        mma16816(p[0], a10, a11, 0u, 0u, w4, 0u); mma16816(p[1], a10, a11, 0u, 0u, w5, 0u);
        mma16816(p[2], b10, 0u, 0u, 0u, w4, 0u); mma16816(p[3], b10, 0u, 0u, 0u, w5, 0u);
        stsm4(rowa + j * 32, make_uint4(pack_bf16(p[0][0], p[0][1]), pack_bf16(p[0][2], p[0][3]), pack_bf16(p[1][0], p[1][1]), pack_bf16(p[1][2], p[1][3])));
        if (g < 2) {
          uint32_t* r = reinterpret_cast<uint32_t*>(smem + (hh * 18 + 16 + g) * WP + (c0 + j * 16 + 2 * t) * 2);
          r[0] = pack_bf16(p[2][0], p[2][1]); r[4] = pack_bf16(p[3][0], p[3][1]);
        }
      }
      asm volatile("fence.proxy.async.shared::cta;" ::: "memory");
      __syncwarp();
      if (lane < 18) {
        asm volatile("cp.async.bulk.global.shared::cta.bulk_group [%0], [%1], %2;" ::"l"(g_m + (a * 144 + hh * 18 + lane) * D_ + c0), "r"(sbase + (hh * 18 + lane) * WP + c0 * 2), "r"(384) : "memory");
        asm volatile("cp.async.bulk.commit_group;" ::: "memory");
      }
    }
    asm volatile("cp.async.bulk.wait_group 0;" ::: "memory");
    asm volatile("fence.proxy.async.global;" ::: "memory");
    __syncwarp();
    if (lane == 0) asm volatile("red.release.gpu.global.add.u32 [%0], 1;" ::"l"(g_f_m) : "memory");
    STAMPW(0, 3);
    __syncthreads();
    if (tid == 0) g_epoch[blockIdx.x] = ep;
    return;
  }

  const int cl = blockIdx.x >> 1, rank = blockIdx.x & 1;
  const int f = cl & 7, m = (cl >> 3) * 2 + rank;
  const int srole = f >= 6 ? 1 : 0;
  const uint32_t bar_full = sbase + SM_BAR, bar_empty = bar_full + 8 * NSTAGE, bar_xfree = bar_empty + 8 * NSTAGE, bar_ofull = bar_xfree + 72,
                 bar_d = bar_ofull + 72;

  if (tid == 0) {
#pragma unroll 1
    for (int i = 0; i < NSTAGE; i++) { mbar_init(bar_full + 8 * i, 1); mbar_init(bar_empty + 8 * i, 4); }
#pragma unroll 1
    for (int i = 0; i < 9; i++) { mbar_init(bar_xfree + 8 * i, 2); mbar_init(bar_ofull + 8 * i, 1); }
    mbar_init(bar_d, 1);
    asm volatile("fence.mbarrier_init.release.cluster;" ::: "memory");
  }
  __syncwarp();
  cluster_arrive_relaxed();

  if (warp >= 8) {
    const int srow = m * 128 + f * 16 + (warp - 8) * 4 + (lane >> 3);
    uint4 xs[9];
#pragma unroll
    for (int kb = 0; kb < 9; kb++) xs[kb] = __ldg(reinterpret_cast<const uint4*>(P.x + srow * D_) + (lane & 7) + kb * 8);
    auto stats = [&]() {
      const uint32_t* w = reinterpret_cast<const uint32_t*>(xs);
      float s0 = 0.f, s1 = 0.f;
#pragma unroll
      for (int i = 0; i < 36; i++) { s0 += bf_lo(w[i]); s1 += bf_hi(w[i]); }
      float sum = s0 + s1;
      sum += __shfl_xor_sync(0xffffffffu, sum, 1); sum += __shfl_xor_sync(0xffffffffu, sum, 2); sum += __shfl_xor_sync(0xffffffffu, sum, 4);
      const float mean = sum * (1.f / 576.f);
      s0 = 0.f; s1 = 0.f;
#pragma unroll
      for (int i = 0; i < 36; i++) { const float a = bf_lo(w[i]) - mean, b = bf_hi(w[i]) - mean; s0 = fmaf(a, a, s0); s1 = fmaf(b, b, s1); }
      float sq = s0 + s1;
      sq += __shfl_xor_sync(0xffffffffu, sq, 1); sq += __shfl_xor_sync(0xffffffffu, sq, 2); sq += __shfl_xor_sync(0xffffffffu, sq, 4);
      const float rstd = rsqrtf(sq * (1.f / 576.f) + 1e-5f);
      if ((lane & 7) == 0)
        st_ll64(&g_stat[srow], __float_as_uint(rstd), pack_bf16(-mean, -mean), par);
    };
    stats();
    asm volatile("setmaxnreg.dec.sync.aligned.u32 40;");
    cluster_wait();
    if (warp == 8) {
      if (lane == 0) {
        uint32_t stage = 0, phase = 1;
        const uint32_t sb = sbase + SM_B;
#pragma unroll 1
        for (int tl = 2 * srole; tl < 8 + 2 * srole; tl++) {
          const CUtensorMap* map = tl == 0 ? &P.tm_wqkv : (tl == 1 ? &P.tm_wqkv64 : (tl < 5 ? &P.tm_w1 : (tl < 8 ? &P.tm_w2 : (tl == 8 ? &P.tm_m : &P.tm_m64))));
          const int col = tl < 2 ? 288 * f + 192 * tl : (tl < 5 ? 576 * f + 192 * (tl - 2) : (tl < 8 ? 192 * ((tl - 5 + f) % 3) : (tl == 8 ? 192 * (f - 5) : 96 * (f - 6))));
          const bool perm = tl >= 5 && tl < 8;
          const bool z = (tl & 7) == 1;
          if (tl == 8) { flag_wait(g_f_m, 48 * ep); asm volatile("fence.proxy.async.global;" ::: "memory"); }
          const int cs = z ? 32 : 64, rs = z ? 64 : 32, nst = z ? 9 : 18;
#pragma unroll 1
          for (int st = 0; st < nst; st++) {
            int row = st * rs;
            if (perm) row += 576 * f + ((st < 6) ? 192 : (st < 12 ? -192 : 0));
            mbar_wait(bar_empty + 8 * stage, phase);
            mbar_expect(bar_full + 8 * stage, 12288);
            const uint32_t dst = sb + stage * STAGE_BYTES;
            if (((st ^ rank) & 1) == 0) {
              tma2d_mc(dst, map, col, row, bar_full + 8 * stage);
              tma2d_mc(dst + 8192, map, col + 2 * cs, row, bar_full + 8 * stage);
            } else {
              tma2d_mc(dst + 4096, map, col + cs, row, bar_full + 8 * stage);
            }
            if (++stage == NSTAGE) { stage = 0; phase ^= 1; }
          }
        }
      }
      __syncwarp();
    } else {
      const int aw = warp - 9;
      const int hi = f >> 2;
      if (aw == 0) {
        if (lane < 2) hint_wait(&g_f_qkv[m * 8 + 2 + 2 * lane + hi], 16 * ep, 200);
        __syncwarp();
        if (lane == 0) mbar_arrive(bar_d);
        STAMP(20);
      }
      if (lane < 5) hint_wait(lane < 4 ? &g_f_z[4 * f + lane] : &g_f_qkv[m * 8 + hi], lane < 4 ? 2 * ep : 16 * ep);
      __syncwarp();
      STAMPW(9, 22);
      uint32_t* stg = reinterpret_cast<uint32_t*>(smem + SM_SCR + aw * 2304);
#pragma unroll 1
      for (int u = aw * 2; u < 16; u += (u & 1) ? 5 : 1) {
        const int rbl = u >> 1, hp = (u & 1) * 2;
        const uint2* qf = g_qkv + (m * 8 + rbl) * 216 * 32;
        const uint2* zp = reinterpret_cast<const uint2*>(&g_z[(4 * f + hp) * 8 + t]);
        uint2 q[2][3];
        float d[4];
        int tries = 0;
        uint32_t bad;
#pragma unroll 1
        do {
          bad = tries ? ld_acquire(g_f_m) & 0u : 0u;
#pragma unroll
          for (int j = 0; j < 2; j++)
#pragma unroll
            for (int b = 0; b < 3; b++) q[j][b] = ld_ca64(qf + pairoff((4 * f + hp + j) * 9 + t, g) + 32 * b);
#pragma unroll
          for (int j = 0; j < 2; j++) {
            const uint2 z0 = ld_ca64(zp + 16 * j), z1 = ld_ca64(zp + 16 * j + 1), z2 = ld_ca64(zp + 16 * j + 8);
            if (t != 0) q[j][2] = make_uint2(par, 0u);
            ll_chk(bad, z0.x, z1.x, par); ll_chk(bad, z2.x, q[j][2].x, par); ll_chk(bad, q[j][0].x, q[j][1].x, par);
            d[2 * j] = bf_lo(q[j][0].x) * __uint_as_float(z0.x) + bf_hi(q[j][0].x) * __uint_as_float(z0.y) + bf_lo(q[j][1].x) * __uint_as_float(z1.x) + bf_hi(q[j][1].x) * __uint_as_float(z1.y) +
                       bf_lo(q[j][2].x) * __uint_as_float(z2.x) + bf_hi(q[j][2].x) * __uint_as_float(z2.y);
            d[2 * j + 1] = bf_lo(q[j][0].y) * __uint_as_float(z0.x) + bf_hi(q[j][0].y) * __uint_as_float(z0.y) + bf_lo(q[j][1].y) * __uint_as_float(z1.x) + bf_hi(q[j][1].y) * __uint_as_float(z1.y) +
                           bf_lo(q[j][2].y) * __uint_as_float(z2.x) + bf_hi(q[j][2].y) * __uint_as_float(z2.y);
          }
        } while (__any_sync(0xffffffffu, bad & 1) && ++tries < (1 << 20));
#pragma unroll
        for (int j = 0; j < 4; j++) d[j] += __shfl_xor_sync(0xffffffffu, d[j], 1);
#pragma unroll
        for (int j = 0; j < 4; j++) d[j] = rcpf(d[j] + __shfl_xor_sync(0xffffffffu, d[j], 2) + 1e-6f);
        if (hp == 0) { asm volatile("cp.async.bulk.wait_group.read 0;" ::: "memory"); __syncwarp(); }
#pragma unroll
        for (int j = 0; j < 2; j++) {
          const uint32_t r0 = pack_bf16(d[2 * j], d[2 * j]), r1 = pack_bf16(d[2 * j + 1], d[2 * j + 1]);
#pragma unroll
          for (int b = 0; b < 3; b++)
            if (b < 2 || t == 0) {
              stg[g * 36 + (hp + j) * 9 + 4 * b + t] = hfma2(q[j][b].x, r0, 0x80008000u);
              stg[(g + 8) * 36 + (hp + j) * 9 + 4 * b + t] = hfma2(q[j][b].y, r1, 0x80008000u);
            }
        }
        if (hp != 0) {
          asm volatile("fence.proxy.async.shared::cta;" ::: "memory");
          __syncwarp();
          if (lane == 0) {
            asm volatile("cp.async.bulk.tensor.2d.global.shared::cta.bulk_group [%0, {%2, %3}], [%1];" ::"l"(&P.tm_ast), "r"(smem_u32(stg)), "r"(72 * f), "r"(m * 128 + rbl * 16) : "memory");
            asm volatile("cp.async.bulk.commit_group;" ::: "memory");
          }
        }
      }
      asm volatile("cp.async.bulk.wait_group 0;" ::: "memory");
      asm volatile("fence.proxy.async.global;" ::: "memory");
      STAMPW(9, 26);
      asm volatile("bar.sync 5, 96;" ::: "memory");
      if (tid == 288) asm volatile("red.release.gpu.global.add.u32 [%0], 1;" ::"l"(&g_f_a[m]) : "memory");
      __syncwarp();
      STAMPW(9, 23);
      if (srole && aw == 2) {
        if (lane == 0) {
          flag_wait(&g_f_a[m], 8 * ep);
          asm volatile("fence.proxy.async.global;" ::: "memory");
#pragma unroll 1
          for (int kb = 0; kb < 9; kb++) {
            mbar_wait(bar_xfree + 8 * kb, 0);
            mbar_expect(bar_ofull + 8 * kb, 16384);
            tma2d(sbase + SM_A + kb * 16384, &P.tm_a, kb * 64, m * 128, bar_ofull + 8 * kb);
          }
        }
        __syncwarp();
      }
    }
    cluster_arrive_relaxed();
    cluster_wait();
  } else {
    const int wg = warp >> 2;
    {
      const int rs = lane >> 3, j = lane & 7;
      uint4 xv[4][9];
#pragma unroll
      for (int it = 0; it < 4; it++)
#pragma unroll
        for (int kb = 0; kb < 9; kb++) xv[it][kb] = __ldg(reinterpret_cast<const uint4*>(P.x + (m * 128 + warp * 16 + it * 4 + rs) * D_) + j + kb * 8);
      uint32_t bw0 = __ldg(reinterpret_cast<const uint32_t*>(P.b1 + 576 * f) + tid), bw1 = tid < 32 ? __ldg(reinterpret_cast<const uint32_t*>(P.b1 + 576 * f) + 256 + tid) : 0u;
      uint2 st[4];
      int tries = 0;
      uint32_t bad;
#pragma unroll 1
      do {
        bad = 0;
#pragma unroll
        for (int it = 0; it < 4; it++) st[it] = ld_ll64(&g_stat[m * 128 + warp * 16 + it * 4 + rs]);
        ll_chk(bad, st[0].x, st[1].x, par); ll_chk(bad, st[2].x, st[3].x, par);
      } while (__any_sync(0xffffffffu, bad & 1) && ++tries < (1 << 22));
      STAMPW(0, 19);
#pragma unroll
      for (int it = 0; it < 4; it++) {
        const uint32_t nm = st[it].y;
        uint8_t* dst = smem + SM_A + (warp * 16 + it * 4 + rs) * 128 + ((j ^ ((it * 4 + rs) & 7)) << 4);
#pragma unroll
        for (int kb = 0; kb < 9; kb++) {
          const uint4 w = xv[it][kb];
          *reinterpret_cast<uint4*>(dst + kb * 16384) = make_uint4(hadd2(w.x, nm), hadd2(w.y, nm), hadd2(w.z, nm), hadd2(w.w, nm));
        }
        if (j == 0) reinterpret_cast<uint32_t*>(smem + SM_RSTD)[warp * 16 + it * 4 + rs] = st[it].x;
      }
      reinterpret_cast<float2*>(smem + SM_BIAS)[tid] = make_float2(bf_lo(bw0) * GK, bf_hi(bw0) * GK);
      if (tid < 48) reinterpret_cast<float2*>(smem + SM_BIAS)[256 + tid] = make_float2(bf_lo(bw1) * GK, bf_hi(bw1) * GK);
      asm volatile("fence.proxy.async.shared::cta;" ::: "memory");
    }
    asm volatile("setmaxnreg.inc.sync.aligned.u32 232;");
    cluster_wait();
    asm volatile("bar.sync 1, 256;" ::: "memory");
    STAMPW(0, 1);
    Ctx c;
    c.full = bar_full; c.budget = 1 << 22;
    c.emb = __shfl_sync(0xffffffffu, mapa(bar_empty, (warp & 3) == 0 ? rank : (rank ^ 1)), 0);
    c.sig = lane == 0 && (warp & 3) < 2;
    c.dB = (((sbase + SM_B) & 0x3FFFF) >> 4) | ((4096u >> 4) << 16);
    c.dA = (((sbase + SM_A + wg * 8192) & 0x3FFFF) >> 4) | (1u << 16);
    const bool leader = (lane == 0) && ((warp & 3) == 0);

    const int rb = m * 8 + warp;
    const uint32_t bias_t = sbase + SM_BIAS + 8 * t;
    const uint32_t hst = sbase + SM_A + (warp * 16 + (lane & 7) + ((lane >> 3) & 1) * 8) * 128 + (((lane >> 4) ^ (lane & 7)) << 4);
    auto wg_sync = [&]() {
      asm volatile("fence.proxy.async.shared::cta;" ::: "memory");
      if (wg == 0) asm volatile("bar.sync 2, 128;" ::: "memory"); else asm volatile("bar.sync 3, 128;" ::: "memory");
    };
    float A[96], B[96];
#pragma unroll
    for (int i = 0; i < 96; i++) B[i] = 0.f;
#define EXB(ACC, U) uint32_t E[4]; _Pragma("unroll") for (int q = 0; q < 4; q++) E[q] = pack_bf16(fmaf(ACC[8 * (U) + 2 * q], (q & 1) ? r1 : r0, bs[q >> 1].x), fmaf(ACC[8 * (U) + 2 * q + 1], (q & 1) ? r1 : r0, bs[q >> 1].y));
#define ST_QKV(ACC, U, DST) { uint32_t E[4]; _Pragma("unroll") for (int q = 0; q < 4; q++) \
      E[q] = phi_pack(pack_bf16(ACC[8 * (U) + 2 * q] * ((q & 1) ? r1 : r0), ACC[8 * (U) + 2 * q + 1] * ((q & 1) ? r1 : r0)), ACC[8 * (U) + 2 * q] * ((q & 1) ? l1 : l0), ACC[8 * (U) + 2 * q + 1] * ((q & 1) ? l1 : l0), pc1, pc2); \
    st_ll64(reinterpret_cast<uint2*>(DST) + 64 * (U), E[0], E[1], par); st_ll64(reinterpret_cast<uint2*>(DST) + 64 * (U) + 32, E[2], E[3], par); }
#define PHI_SETUP const float l0 = r0 * 1.4426950408889634f, l1 = r1 * 1.4426950408889634f; const uint32_t pc1 = f < 4 ? 0x35863586u : 0xff80ff80u, pc2 = f < 4 ? 0x3f803f80u : 0u;
#define HADDR(KB0, U) ((hst ^ (((U) & 3) << 5)) + ((KB0) + ((U) >> 2)) * 16384)
#define LDS_R(SC) float r0, r1; asm volatile("ld.shared.f32 %0, [%1];" : "=f"(r0) : "r"(rst)); asm volatile("ld.shared.f32 %0, [%1];" : "=f"(r1) : "r"(rst + 32)); r0 *= (SC); r1 *= (SC);
    const uint32_t rst = sbase + SM_RSTD + (warp * 16 + g) * 4;
    const int fr = f % 3;
#pragma unroll 1
    for (int i = srole;; i++) {
      {
        c.set((!srole && i >= 1) ? 1u : 0u, 0u);
        const uint32_t owp = i == 4 ? 0u : 1u;
        c.wait(bar_ofull, owp);
        issue192(A, c, 0, true);
        const int ln = opaque(lane);
        uint4* dst = i == 1 ? reinterpret_cast<uint4*>(g_qkv + (rb * 216 + 36 * f + 24) * 32 + ln) : g_part + ((rb * 8 + f) * 36 + 12 * (i == 3 ? fr : (fr + 2) % 3)) * 32 + ln;
        LDS_R(i == 2 ? GK : 1.f)
#define HEAD(ACC) wg_wait<1>(); c.release(4); c.release(5); fence_regs<96>(ACC);
        int s = 1;
        if (i == 2) {
          HEAD(B)
#pragma unroll
          for (int k = 1; k < 9; k++) {
            float2 b0[2], b1[2];
            if (k >= 3) { lds_bias(b0, bias_t + (192 + 32 * (k - 3)) * 4); lds_bias(b1, bias_t + (208 + 32 * (k - 3)) * 4); }
            issue192(A, c, k);
            if (k >= 3) {
              const int u = k >= 3 ? 2 * (k - 3) : 0;
              { const float2* bs = b0; EXB(B, u) stsm4(HADDR(0, u), gelu_group(E)); }
              { const float2* bs = b1; EXB(B, u + 1) stsm4(HADDR(0, u + 1), gelu_group(E)); }
            }
            retire(c, k - 1);
          }
          s = 9;
        } else if (i >= 3) {
          HEAD(B)
          if (i == 4 && leader) mbar_arrive(bar_xfree + 64);
#pragma unroll
          for (int u = 0; u < 12; u++) {
            if (u & 1) c.wait(bar_ofull + 4 * (u + 1), owp);
            issue192(A, c, u + 1);
            part_groups<0, 1>(&B[8 * u], dst + u * 32, par);
            retire(c, u);
          }
          s = 13;
        } else if (i > srole) {
          PHI_SETUP
          HEAD(B)
#pragma unroll
          for (int u = 0; u < 6; u++) {
            issue192(A, c, u + 1);
            ST_QKV(B, u, dst)
            retire(c, u);
          }
          hint_signal(&g_f_qkv[m * 8 + f]);
          s = 7;
        } else wg_wait<1>();
        const bool d1 = i == 1 + srole;
        const int send = d1 ? 10 : 15;
        plain192(A, c, s, send, [&](int k) { if (k == 14) c.wait(bar_ofull + 56, owp); }, [](int) {});
        uint32_t W[48];
        if (d1) {
          const int head = 4 * f + (warp >> 1), rb0 = m * 8 + (warp & 1) * 4;
          issue192(A, c, 10);
          c.wait(bar_d, 0);
          d1_load<false, 0, 2>(W, rb0, head, opaque(lane));
          retire(c, 9);
          issue192(A, c, 11);
          d1_load<false, 2, 4>(W, rb0, head, opaque(lane));
          retire(c, 10);
          issue192(A, c, 12);
          retire(c, 11);
          issue192(A, c, 13);
          int tries = 0;
#pragma unroll 1
          while (d1_bad(W, t, par) && ++tries < (1 << 20)) d1_load<true, 0, 4>(W, rb0, head, opaque(lane));
          d1_mov(W, 0, t); d1_mov(W, 1, t);
          retire(c, 12);
          issue192(A, c, 14);
          d1_mov(W, 2, t); d1_mov(W, 3, t);
          wg_wait<0>();
          asm volatile("bar.sync 4, 256;" ::: "memory");
          float R[18];
          d1_mma(W, R);
          const int l2 = opaque(lane);
          float2* xch = reinterpret_cast<float2*>(smem + SM_SCR + (warp >> 1) * 1792) + l2;
          float2* xc2 = xch + 192 - l2 + (l2 < 12 ? l2 : 31);
          if (warp & 1) {
#pragma unroll
            for (int q = 0; q < 6; q++) xch[q * 32] = make_float2(R[2 * q], R[2 * q + 1]);
            if (l2 < 12) { xc2[0] = make_float2(R[12], R[13]); xc2[12] = make_float2(R[14], R[15]); }
            if (l2 < 12 && (l2 & 3) == 0) xc2[24 - l2 + (l2 >> 2)] = make_float2(R[16], R[17]);
          } else if (R[17] == 1.2345e-30f) R[16] = 0.f;
          asm volatile("bar.sync 4, 256;" ::: "memory");
          c.release(13);
          issue192(A, c, 15);
          if (!(warp & 1)) {
#pragma unroll
            for (int q = 0; q < 6; q++) { const float2 o = xch[q * 32]; R[2 * q] += o.x; R[2 * q + 1] += o.y; }
            const float2 o0 = xc2[0], o1 = xc2[l2 < 12 ? 12 : 0], o2 = xc2[l2 < 12 ? 24 - l2 + (l2 >> 2) : 0];
            uint4* dkv = &g_kvp[(head * 80 + m) * 32 + l2];
#pragma unroll
            for (int w = 0; w < 3; w++) st_ll(dkv + w * 512, __float_as_uint(R[4 * w]), __float_as_uint(R[4 * w + 1]), __float_as_uint(R[4 * w + 2]), __float_as_uint(R[4 * w + 3]), par);
            st_ll(dkv + 1536, __float_as_uint(R[12] + o0.x), __float_as_uint(R[13] + o0.y), __float_as_uint(R[14] + o1.x), __float_as_uint(R[15] + o1.y), par);
            st_ll(dkv + 2048, __float_as_uint(R[16] + o2.x), __float_as_uint(R[17] + o2.y), 0u, 0u, par);
            hint_signal(&g_f_kvp[head]);
          }
          STAMPW(0, 21);
        } else issue192(A, c, 15);
        if (i == 2) {
          const uint4* hsp = g_hsp + (blockIdx.x * 8 + warp) * 12 * 32 + opaque(lane);
#pragma unroll
          for (int q = 0; q < 12; q++) { const uint4 v = ldcg128(hsp + q * 32); W[4 * q] = v.x; W[4 * q + 1] = v.y; W[4 * q + 2] = v.z; W[4 * q + 3] = v.w; }
          retire(c, 14);
          issue192(A, c, 16);
          wg_sync();
          retire(c, 15);
          issue192(A, c, 17);
#pragma unroll
          for (int q = 0; q < 12; q++) stsm4(HADDR(3, q), make_uint4(W[4 * q], W[4 * q + 1], W[4 * q + 2], W[4 * q + 3]));
        } else {
          retire(c, 14);
          c.wait(bar_ofull + 64, owp);
          issue192(A, c, 16);
          retire(c, 15);
          issue192(A, c, 17);
        }
      }
      STAMPW(0, 2 + 2 * i);
      c.set((!srole && i >= 1) ? 1u : 0u, 1u);
      if ((i & 3) == 0) {
        issue96(B, c, 0, true);
        const int ln = opaque(lane);
        uint2* dst = i == 0 ? g_qkv + (rb * 216 + 36 * f) * 32 + ln : g_s + (rb * 72 + 24 * (f - 5)) * 32 + ln;
        LDS_R(1.f)
        if (i != 0) { r0 = 1.f; r1 = 1.f; }
        PHI_SETUP
        HEAD(A)
#pragma unroll
        for (int k = 1; k < 9; k++) {
          issue96(B, c, k, false);
#pragma unroll
          for (int u = (3 * (k - 1) + 1) / 2; u < (3 * k + 1) / 2; u++) ST_QKV(A, u, dst)
          if (k < 8) retire(c, k - 1);
        }
        if (i == 4) {
          STAMPW(0, 11);
          wg_wait<0>();
          c.release(7); c.release(8);
          fence_regs<48>(B);
          uint2* d2 = g_s + (rb * 72 + 12 * (f - 6)) * 32 + opaque(lane);
#pragma unroll
          for (int q = 0; q < 12; q++) st_ll64(d2 + q * 32, pack_bf16(B[4 * q], B[4 * q + 1]), pack_bf16(B[4 * q + 2], B[4 * q + 3]), par);
          break;
        }
        hint_signal(&g_f_qkv[m * 8 + f]);
      } else {
        issue192(B, c, 0, true);
        const int ln = opaque(lane);
        uint4* dst = i == 1 ? g_hsp + (blockIdx.x * 8 + warp) * 12 * 32 + ln : g_part + ((rb * 8 + f) * 36 + 12 * ((fr + 1) % 3)) * 32 + ln;
        const bool xf = i == 3 && srole && leader;
        const uint32_t bsa = bias_t + (i == 1 ? 0 : 384) * 4;
        LDS_R(GK)
        int s;
        if (i != 3) {
          HEAD(A)
#pragma unroll
          for (int u = 0; u < 12; u++) {
            float2 bs[2];
            lds_bias(bs, bsa + 16 * u * 4);
            issue192(B, c, u + 1);
            EXB(A, u)
            const uint4 h = gelu_group(E);
            asm volatile("{.reg .pred p; setp.eq.s32 p, %6, 1; @p st.global.v4.u32 [%0], {%2,%3,%4,%5}; @!p stmatrix.sync.aligned.m8n8.x4.shared.b16 [%1], {%2,%3,%4,%5};}"
                         ::"l"(dst + u * 32), "r"(HADDR(6, u)), "r"(h.x), "r"(h.y), "r"(h.z), "r"(h.w), "r"(i) : "memory");
            if (u == 3 || u == 9) wg_sync();
            retire(c, u);
          }
          s = 13;
        } else {
          HEAD(A)
#pragma unroll
          for (int u = 0; u < 6; u++) {
            issue192(B, c, u + 1);
            part_groups<0, 2>(&A[16 * u], dst + 2 * u * 32, par);
            retire(c, u);
            if ((u & 1) && xf) mbar_arrive(bar_xfree + 4 * u - 4);
          }
          s = 7;
        }
        if (i == 3 && !srole) {
          const int c2 = (fr + 2) % 3, v0 = 12 * c2 + (f < 3 ? 0 : 6), fo = f < 3 ? f + 3 : f - 3;
          const int l2 = opaque(lane);
          const uint4* pb = g_part + (rb * 8 * 36 + v0) * 32 + l2;
          uint4 p[12];
          uint32_t S[24];
#pragma unroll
          for (int q = 0; q < 24; q++) S[q] = 0u;
          auto ldp = [&](const uint4* a0, const uint4* a1) {
#pragma unroll
            for (int q = 0; q < 6; q++) { p[q] = ld_ll(a0 + q * 32); p[6 + q] = ld_ll(a1 + q * 32); }
          };
          auto badp = [&]() {
            uint32_t bad = 0;
#pragma unroll
            for (int q = 0; q < 12; q++) ll_chk(bad, p[q].x, p[q].z, par);
            return __any_sync(0xffffffffu, bad & 1);
          };
#pragma unroll 1
          for (int w = 0; w < 3; w++) {
            const uint4* a0 = pb + (w == 0 ? c2 : (w == 1 ? 6 : (fr + 1) % 3)) * 36 * 32;
            const uint4* a1 = a0 + (w == 1 ? 1 : 3) * 36 * 32;
            issue192(B, c, 7 + 3 * w);
            ldp(a0, a1);
            retire(c, 6 + 3 * w);
            issue192(B, c, 8 + 3 * w);
            retire(c, 7 + 3 * w);
            issue192(B, c, 9 + 3 * w);
            int tries = 0;
#pragma unroll 1
            while (badp() && ++tries < (1 << 20)) ldp(a0, a1);
#pragma unroll
            for (int q = 0; q < 24; q++) S[q] = hadd2(S[q], hadd2(reinterpret_cast<const uint32_t*>(p)[q], reinterpret_cast<const uint32_t*>(p)[24 + q]));
            retire(c, 8 + 3 * w);
          }
          uint4 xx[6];
          uint32_t bb[12];
          int ro[6];
          issue192(B, c, 16);
#pragma unroll
          for (int j = 0; j < 6; j++) {
            const int k = l2 + 32 * j, r = (k * 171) >> 11;
            ro[j] = (rb * 16 + r) * D_ + 16 * v0 + (k - 12 * r) * 8;
            xx[j] = __ldg(reinterpret_cast<const uint4*>(P.x + ro[j]));
          }
#pragma unroll
          for (int j = 0; j < 12; j++) bb[j] = __ldg(reinterpret_cast<const uint32_t*>(P.b2 + 16 * v0 + 8 * j + 2 * (l2 & 3)));
          retire(c, 15);
          issue192(B, c, 17);
          retire(c, 16);
          STAMPW(0, 9);
          wg_wait<0>();
          c.release(17);
          fence_regs<96>(B);
          uint4* snd = g_part + ((rb * 8 + f) * 36 + 12 * c2 + (f < 3 ? 6 : 0)) * 32 + l2;
          if (f < 3) part_groups<0, 6>(B + 48, snd, par);
          else {
            part_groups<0, 6>(B, snd, par);
#pragma unroll
            for (int q = 0; q < 48; q++) B[q] = B[48 + q];
          }
          asm volatile("bar.sync 4, 256;" ::: "memory");
          STAMPW(0, 12);
#pragma unroll
          for (int q = 0; q < 24; q++) {
            B[2 * q] = fmaf(B[2 * q] + bf_lo(S[q]), 0.25f / GK, 0.5f * bf_lo(bb[q >> 1])); B[2 * q + 1] = fmaf(B[2 * q + 1] + bf_hi(S[q]), 0.25f / GK, 0.5f * bf_hi(bb[q >> 1]));
          }
          const uint2* sp = g_s + (rb * 72 + 2 * v0) * 32 + l2;
          int tries = 0;
#pragma unroll 1
          while (++tries < (1 << 20)) {
            const uint2 u0 = ld_ll64(pb + (fo * 36 + 5) * 32), u1 = ld_ll64(sp + 11 * 32);
            if (!__any_sync(0xffffffffu, ((u0.x ^ par) | (u1.x ^ par)) & 1)) break;
            __nanosleep(40);
          }
          tries = 0;
#pragma unroll 1
          do {
#pragma unroll
            for (int q = 0; q < 6; q++) {
              p[q] = ld_ll(pb + (fo * 36 + q) * 32);
              const uint2 s0 = ld_ll64(sp + 2 * q * 32), s1 = ld_ll64(sp + (2 * q + 1) * 32);
              p[6 + q] = make_uint4(s0.x, s0.y, s1.x, s1.y);
            }
          } while (badp() && ++tries < (1 << 20));
          STAMPW(0, 14);
          const uint32_t tb = sbase + SM_A + warp * 3328;
#pragma unroll
          for (int v = 0; v < 6; v++) {
            uint32_t o[4];
#pragma unroll
            for (int k = 0; k < 4; k++) {
              const int q = 4 * v + k;
              const uint32_t w = reinterpret_cast<const uint32_t*>(p)[q];
              const uint32_t gt = pack_bf16(silu_h(fmaf(bf_lo(w), 0.25f / GK, B[2 * q])), silu_h(fmaf(bf_hi(w), 0.25f / GK, B[2 * q + 1])));
              o[k] = hfma2(reinterpret_cast<const uint32_t*>(p)[24 + q], gt, 0x80008000u);
            }
            stsm4(tb + (l2 & 15) * 208 + (l2 >> 4) * 16 + v * 32, make_uint4(o[0], o[1], o[2], o[3]));
          }
          __syncwarp();
#pragma unroll
          for (int j = 0; j < 6; j++) {
            const int k = l2 + 32 * j, r = (k * 171) >> 11;
            uint4 o;
            asm volatile("ld.shared.v4.u32 {%0,%1,%2,%3}, [%4];" : "=r"(o.x), "=r"(o.y), "=r"(o.z), "=r"(o.w) : "r"(tb + r * 208 + (k - 12 * r) * 16) : "memory");
            *reinterpret_cast<uint4*>(P.out + ro[j]) = make_uint4(hadd2(o.x, xx[j].x), hadd2(o.y, xx[j].y), hadd2(o.z, xx[j].z), hadd2(o.w, xx[j].w));
          }
          break;
        }
        plain192(B, c, s, 17, [&](int k) { if (k == 15) wg_sync(); }, [&](int k) { if (!(k & 1) && xf) mbar_arrive(bar_xfree + 4 * k - 8); });
        issue192(B, c, 17);
      }
      STAMPW(0, 3 + 2 * i);
    }
    STAMPW(0, 15);
    cluster_arrive_relaxed();
    cluster_wait();
    STAMPW(0, 16);
    if (tid == 0) g_epoch[blockIdx.x] = ep;
  }
}

typedef CUresult (*EncFn)(CUtensorMap*, CUtensorMapDataType, cuuint32_t, void*, const cuuint64_t*, const cuuint64_t*, const cuuint32_t*, const cuuint32_t*,
                          CUtensorMapInterleave, CUtensorMapSwizzle, CUtensorMapL2promotion, CUtensorMapFloatOOBfill);

void make_map(EncFn enc, CUtensorMap* tm, const void* ptr, int rows, int cols, int box_rows, int mode = 0) {
  cuuint64_t gd[2] = {(cuuint64_t)cols, (cuuint64_t)rows};
  cuuint64_t gs[1] = {(cuuint64_t)cols * 2};
  cuuint32_t bx[2] = {mode == 1 ? 32u : (mode == 2 ? 72u : 64u), (cuuint32_t)box_rows};
  cuuint32_t es[2] = {1, 1};
  enc(tm, CU_TENSOR_MAP_DATA_TYPE_BFLOAT16, 2, const_cast<void*>(ptr), gd, gs, bx, es, CU_TENSOR_MAP_INTERLEAVE_NONE, mode == 1 ? CU_TENSOR_MAP_SWIZZLE_64B : (mode == 2 ? CU_TENSOR_MAP_SWIZZLE_NONE : CU_TENSOR_MAP_SWIZZLE_128B),
      CU_TENSOR_MAP_L2_PROMOTION_L2_256B, CU_TENSOR_MAP_FLOAT_OOB_FILL_NONE);
}

}

extern "C" void kernel_launch(void* const* d_in, const int* in_sizes, int n_in, void* d_out, int out_size) {
  (void)in_sizes; (void)n_in; (void)out_size;
  static EncFn enc = nullptr;
  static void *a_ptr = nullptr, *m_ptr = nullptr;
  if (!enc) {
    void* fn = nullptr; cudaDriverEntryPointQueryResult q;
    cudaGetDriverEntryPoint("cuTensorMapEncodeTiled", &fn, cudaEnableDefault, &q);
    enc = (EncFn)fn;
    cudaFuncSetAttribute(fused_kernel, cudaFuncAttributeMaxDynamicSharedMemorySize, SMEM_BYTES);
    cudaGetSymbolAddress(&a_ptr, g_a);
    cudaGetSymbolAddress(&m_ptr, g_m);
  }
  Params P;
  P.x = (const __nv_bfloat16*)d_in[0];
  P.wqkv = (const __nv_bfloat16*)d_in[1];
  P.wo = (const __nv_bfloat16*)d_in[2];
  P.w1 = (const __nv_bfloat16*)d_in[4];
  P.b1 = (const __nv_bfloat16*)d_in[5];
  P.w2 = (const __nv_bfloat16*)d_in[6];
  P.b2 = (const __nv_bfloat16*)d_in[7];
  P.out = (__nv_bfloat16*)d_out;
  make_map(enc, &P.tm_wqkv, P.wqkv, D_, Q3_, 32);
  make_map(enc, &P.tm_w1, P.w1, D_, F_, 32);
  make_map(enc, &P.tm_w2, P.w2, F_, D_, 32);
  make_map(enc, &P.tm_m, m_ptr, D_, D_, 32);
  make_map(enc, &P.tm_wqkv64, P.wqkv, D_, Q3_, 64, 1);
  make_map(enc, &P.tm_m64, m_ptr, D_, D_, 64, 1);
  make_map(enc, &P.tm_a, a_ptr, S_, D_, 128);
  make_map(enc, &P.tm_ast, a_ptr, S_, D_, 16, 2);
  fused_kernel<<<NCTAS, NTHREADS, SMEM_BYTES, cudaStreamPerThread>>>(P);
}
```

```cpp
#include <cuda_runtime.h>
#include <cuda.h>
#include <cuda_bf16.h>
#include <stdint.h>

namespace {

constexpr int S_ = 2048, D_ = 576, F_ = 4608, Q3_ = 1728;
constexpr int NSTAGE = 6, STAGE_BYTES = 12288;
constexpr int SM_A = 0, SM_B = 147456, SM_BIAS = SM_B + NSTAGE * STAGE_BYTES, SM_RSTD = SM_BIAS + 2304 + 128, SM_SCR = SM_RSTD + 512, SM_BAR = SM_SCR + 7168;
constexpr int SMEM_BYTES = SM_BAR + 320;
constexpr int NTHREADS = 384;
constexpr int NCTAS = 132;

__device__ uint2 g_qkv[(128 * 216 + 2) * 32];
__device__ __align__(1024) __nv_bfloat16 g_a[S_ * D_];
__device__ __align__(1024) __nv_bfloat16 g_m[D_ * D_];
__device__ uint4 g_kvp[32 * 5 * 16 * 32];
__device__ uint4 g_z[32 * 2 * 4];
__device__ uint4 g_part[128 * 8 * 36 * 32];
__device__ uint2 g_s[128 * 72 * 32];
__device__ uint4 g_hsp[128 * 12 * 256];
__device__ uint32_t g_f_qkv[16 * 8];
__device__ uint32_t g_f_kvp[32];
__device__ uint32_t g_f_z[32];
__device__ uint32_t g_f_a[16];
__device__ uint32_t g_f_m[1];
__device__ uint2 g_stat[S_];
__device__ uint32_t g_epoch[NCTAS];

#define STAMP(i)
#define STAMPW(w, i)
#define WSTAMP(i)
__device__ __forceinline__ uint32_t smem_u32(const void* p) { return (uint32_t)__cvta_generic_to_shared(p); }
__device__ __forceinline__ void mbar_init(uint32_t a, int c) { asm volatile("mbarrier.init.shared::cta.b64 [%0], %1;" ::"r"(a), "r"(c)); }
__device__ __forceinline__ void mbar_expect(uint32_t a, uint32_t b) { asm volatile("mbarrier.arrive.expect_tx.shared::cta.b64 _, [%0], %1;" ::"r"(a), "r"(b) : "memory"); }
__device__ __forceinline__ void mbar_arrive(uint32_t a) { asm volatile("mbarrier.arrive.shared::cta.b64 _, [%0];" ::"r"(a) : "memory"); }
__device__ __forceinline__ void mbar_arrive_cl(uint32_t a) { asm volatile("mbarrier.arrive.shared::cluster.b64 _, [%0];" ::"r"(a) : "memory"); }
__device__ __forceinline__ uint32_t mapa(uint32_t a, uint32_t cta) { uint32_t r; asm volatile("mapa.shared::cluster.u32 %0, %1, %2;" : "=r"(r) : "r"(a), "r"(cta)); return r; }
__device__ __forceinline__ void mbar_wait(uint32_t a, uint32_t ph) {
  uint32_t ok; int it = 0;
#pragma unroll 1
  do {
    asm volatile("{.reg .pred p; mbarrier.try_wait.parity.shared::cta.b64 p, [%1], %2; selp.u32 %0,1,0,p;}" : "=r"(ok) : "r"(a), "r"(ph) : "memory");
  } while (!ok && ++it < (1 << 18));
}
__device__ __forceinline__ void tma2d(uint32_t dst, const CUtensorMap* m, int c0, int c1, uint32_t bar) {
  asm volatile("cp.async.bulk.tensor.2d.shared::cluster.global.mbarrier::complete_tx::bytes [%0], [%1, {%3,%4}], [%2];" ::"r"(dst), "l"(m), "r"(bar), "r"(c0), "r"(c1) : "memory");
}
__device__ __forceinline__ void tma2d_mc(uint32_t dst, const CUtensorMap* m, int c0, int c1, uint32_t bar) {
  asm volatile("cp.async.bulk.tensor.2d.shared::cluster.global.mbarrier::complete_tx::bytes.multicast::cluster [%0], [%1, {%3,%4}], [%2], %5;" ::"r"(dst), "l"(m), "r"(bar), "r"(c0), "r"(c1), "h"((uint16_t)3) : "memory");
}
__device__ __forceinline__ void cluster_arrive_relaxed() { asm volatile("barrier.cluster.arrive.relaxed.aligned;" ::: "memory"); }
__device__ __forceinline__ void cluster_wait() { asm volatile("barrier.cluster.wait.acquire.aligned;" ::: "memory"); }
__device__ __forceinline__ void wg_fence() { asm volatile("wgmma.fence.sync.aligned;" ::: "memory"); }
__device__ __forceinline__ void wg_commit() { asm volatile("wgmma.commit_group.sync.aligned;" ::: "memory"); }
template <int n> __device__ __forceinline__ void wg_wait() { asm volatile("wgmma.wait_group.sync.aligned %0;" ::"n"(n) : "memory"); }
__device__ __forceinline__ uint32_t ld_acquire(const uint32_t* p) { uint32_t v; asm volatile("ld.acquire.gpu.global.u32 %0, [%1];" : "=r"(v) : "l"(p) : "memory"); return v; }
__device__ __forceinline__ void flag_wait(const uint32_t* p, uint32_t target) {
  int it = 0;
#pragma unroll 1
  while ((int)(ld_acquire(p) - target) < 0 && ++it < (1 << 20)) __nanosleep(300);
}
__device__ __forceinline__ void hint_signal(uint32_t* p) {
  if ((threadIdx.x & 31) == 0) asm volatile("red.relaxed.gpu.global.add.u32 [%0], 1;" ::"l"(p) : "memory");
}
__device__ __forceinline__ void hint_wait(const uint32_t* p, uint32_t target, uint32_t ns = 400) {
  int it = 0; uint32_t v;
#pragma unroll 1
  do { asm volatile("ld.relaxed.gpu.global.u32 %0, [%1];" : "=r"(v) : "l"(p) : "memory"); if ((int)(v - target) >= 0) break; __nanosleep(ns); } while (++it < (1 << 20));
}
__device__ __forceinline__ uint32_t tag(uint32_t x, uint32_t par) { uint32_t r; asm("lop3.b32 %0, %1, 0xfffffffe, %2, 0xea;" : "=r"(r) : "r"(x), "r"(par)); return r; }
__device__ __forceinline__ void st_ll(uint4* p, uint32_t x, uint32_t y, uint32_t z, uint32_t w, uint32_t par) {
  asm volatile("{.reg .b64 a, b; mov.b64 a, {%1,%2}; mov.b64 b, {%3,%4}; st.relaxed.gpu.global.v2.b64 [%0], {a, b};}"
               ::"l"(p), "r"(tag(x, par)), "r"(y), "r"(tag(z, par)), "r"(w) : "memory");
}
__device__ __forceinline__ uint4 ld_ll(const uint4* p) {
  uint4 v;
  asm volatile("{.reg .b64 a, b; ld.relaxed.gpu.global.v2.b64 {a, b}, [%4]; mov.b64 {%0,%1}, a; mov.b64 {%2,%3}, b;}"
               : "=r"(v.x), "=r"(v.y), "=r"(v.z), "=r"(v.w) : "l"(p) : "memory");
  return v;
}
__device__ __forceinline__ void st_ll64(uint2* p, uint32_t x, uint32_t y, uint32_t par) {
  asm volatile("{.reg .b64 a; mov.b64 a, {%1,%2}; st.relaxed.gpu.global.b64 [%0], a;}" ::"l"(p), "r"(tag(x, par)), "r"(y) : "memory");
}
__device__ __forceinline__ uint2 ld_ca64(const void* p) {
  uint2 v;
  asm volatile("{.reg .b64 a; ld.global.ca.b64 a, [%2]; mov.b64 {%0,%1}, a;}" : "=r"(v.x), "=r"(v.y) : "l"(p) : "memory");
  return v;
}
__device__ __forceinline__ uint2 ld_ll64(const void* p) {
  uint2 v;
  asm volatile("{.reg .b64 a; ld.relaxed.gpu.global.b64 a, [%2]; mov.b64 {%0,%1}, a;}" : "=r"(v.x), "=r"(v.y) : "l"(p) : "memory");
  return v;
}
__device__ __forceinline__ void ll_chk(uint32_t& bad, uint32_t a, uint32_t b, uint32_t par) {
  uint32_t u; asm("lop3.b32 %0, %1, %2, %3, 0x7e;" : "=r"(u) : "r"(a), "r"(b), "r"(par));
  asm("or.b32 %0, %0, %1;" : "+r"(bad) : "r"(u));
}
__device__ __forceinline__ uint32_t hadd2(uint32_t a, uint32_t b) { uint32_t d; asm("add.rn.bf16x2 %0, %1, %2;" : "=r"(d) : "r"(a), "r"(b)); return d; }
__device__ __forceinline__ uint32_t hfma2(uint32_t a, uint32_t b, uint32_t c) { uint32_t d; asm("fma.rn.bf16x2 %0, %1, %2, %3;" : "=r"(d) : "r"(a), "r"(b), "r"(c)); return d; }
__device__ __forceinline__ uint32_t pack_bf16(float lo, float hi) { uint32_t r; asm("cvt.rn.bf16x2.f32 %0, %1, %2;" : "=r"(r) : "f"(hi), "f"(lo)); return r; }
__device__ __forceinline__ float bf_lo(uint32_t v) { return __uint_as_float(v << 16); }
__device__ __forceinline__ float bf_hi(uint32_t v) { return __uint_as_float(v & 0xffff0000u); }
__device__ __forceinline__ uint32_t movmat(uint32_t a) { uint32_t d; asm volatile("movmatrix.sync.aligned.m8n8.trans.b16 %0, %1;" : "=r"(d) : "r"(a)); return d; }
__device__ __forceinline__ void mma16816(float* c, uint32_t a0, uint32_t a1, uint32_t a2, uint32_t a3, uint32_t b0, uint32_t b1) {
  asm volatile("mma.sync.aligned.m16n8k16.row.col.f32.bf16.bf16.f32 {%0,%1,%2,%3}, {%4,%5,%6,%7}, {%8,%9}, {%0,%1,%2,%3};"
               : "+f"(c[0]), "+f"(c[1]), "+f"(c[2]), "+f"(c[3]) : "r"(a0), "r"(a1), "r"(a2), "r"(a3), "r"(b0), "r"(b1));
}
__device__ __forceinline__ uint4 ldcg128(const void* p) { uint4 v; asm volatile("ld.global.cg.v4.u32 {%0,%1,%2,%3}, [%4];" : "=r"(v.x), "=r"(v.y), "=r"(v.z), "=r"(v.w) : "l"(p) : "memory"); return v; }

template <int N> __device__ __forceinline__ void wgmma_ss(float* d, uint32_t alo, int aimm, uint32_t blo, int bimm, uint32_t bhi, int sc);
template <> __device__ __forceinline__ void wgmma_ss<96>(float* d, uint32_t alo, int aimm, uint32_t blo, int bimm, uint32_t bhi, int sc) {
  asm volatile("{.reg .pred p; .reg .b32 x, y; .reg .b64 da, db; setp.ne.b32 p, %53, 0; add.u32 x, %48, %49; add.u32 y, %50, %51; mov.b64 da, {x, 0x40000040}; mov.b64 db, {y, %52}; "
               "wgmma.mma_async.sync.aligned.m64n96k16.f32.bf16.bf16 {%0, %1, %2, %3, %4, %5, %6, %7, %8, %9, %10, %11, %12, %13, %14, %15, %16, %17, %18, %19, %20, %21, %22, %23, %24, %25, %26, %27, %28, %29, %30, %31, %32, %33, %34, %35, %36, %37, %38, %39, %40, %41, %42, %43, %44, %45, %46, %47}, da, db, p, 1, 1, 0, 1;}"
   : "+f"(d[0]), "+f"(d[1]), "+f"(d[2]), "+f"(d[3]), "+f"(d[4]), "+f"(d[5]), "+f"(d[6]), "+f"(d[7]), "+f"(d[8]), "+f"(d[9]), "+f"(d[10]), "+f"(d[11]), "+f"(d[12]), "+f"(d[13]), "+f"(d[14]), "+f"(d[15]), "+f"(d[16]), "+f"(d[17]), "+f"(d[18]), "+f"(d[19]), "+f"(d[20]), "+f"(d[21]), "+f"(d[22]), "+f"(d[23]), "+f"(d[24]), "+f"(d[25]), "+f"(d[26]), "+f"(d[27]), "+f"(d[28]), "+f"(d[29]), "+f"(d[30]), "+f"(d[31]), "+f"(d[32]), "+f"(d[33]), "+f"(d[34]), "+f"(d[35]), "+f"(d[36]), "+f"(d[37]), "+f"(d[38]), "+f"(d[39]), "+f"(d[40]), "+f"(d[41]), "+f"(d[42]), "+f"(d[43]), "+f"(d[44]), "+f"(d[45]), "+f"(d[46]), "+f"(d[47]) : "r"(alo), "r"(aimm), "r"(blo), "r"(bimm), "r"(bhi), "r"(sc));
}
template <> __device__ __forceinline__ void wgmma_ss<192>(float* d, uint32_t alo, int aimm, uint32_t blo, int bimm, uint32_t bhi, int sc) {
  asm volatile("{.reg .pred p; .reg .b32 x, y; .reg .b64 da, db; setp.ne.b32 p, %101, 0; add.u32 x, %96, %97; add.u32 y, %98, %99; mov.b64 da, {x, 0x40000040}; mov.b64 db, {y, %100}; "
               "wgmma.mma_async.sync.aligned.m64n192k16.f32.bf16.bf16 {%0, %1, %2, %3, %4, %5, %6, %7, %8, %9, %10, %11, %12, %13, %14, %15, %16, %17, %18, %19, %20, %21, %22, %23, %24, %25, %26, %27, %28, %29, %30, %31, %32, %33, %34, %35, %36, %37, %38, %39, %40, %41, %42, %43, %44, %45, %46, %47, %48, %49, %50, %51, %52, %53, %54, %55, %56, %57, %58, %59, %60, %61, %62, %63, %64, %65, %66, %67, %68, %69, %70, %71, %72, %73, %74, %75, %76, %77, %78, %79, %80, %81, %82, %83, %84, %85, %86, %87, %88, %89, %90, %91, %92, %93, %94, %95}, da, db, p, 1, 1, 0, 1;}"
   : "+f"(d[0]), "+f"(d[1]), "+f"(d[2]), "+f"(d[3]), "+f"(d[4]), "+f"(d[5]), "+f"(d[6]), "+f"(d[7]), "+f"(d[8]), "+f"(d[9]), "+f"(d[10]), "+f"(d[11]), "+f"(d[12]), "+f"(d[13]), "+f"(d[14]), "+f"(d[15]), "+f"(d[16]), "+f"(d[17]), "+f"(d[18]), "+f"(d[19]), "+f"(d[20]), "+f"(d[21]), "+f"(d[22]), "+f"(d[23]), "+f"(d[24]), "+f"(d[25]), "+f"(d[26]), "+f"(d[27]), "+f"(d[28]), "+f"(d[29]), "+f"(d[30]), "+f"(d[31]), "+f"(d[32]), "+f"(d[33]), "+f"(d[34]), "+f"(d[35]), "+f"(d[36]), "+f"(d[37]), "+f"(d[38]), "+f"(d[39]), "+f"(d[40]), "+f"(d[41]), "+f"(d[42]), "+f"(d[43]), "+f"(d[44]), "+f"(d[45]), "+f"(d[46]), "+f"(d[47]), "+f"(d[48]), "+f"(d[49]), "+f"(d[50]), "+f"(d[51]), "+f"(d[52]), "+f"(d[53]), "+f"(d[54]), "+f"(d[55]), "+f"(d[56]), "+f"(d[57]), "+f"(d[58]), "+f"(d[59]), "+f"(d[60]), "+f"(d[61]), "+f"(d[62]), "+f"(d[63]), "+f"(d[64]), "+f"(d[65]), "+f"(d[66]), "+f"(d[67]), "+f"(d[68]), "+f"(d[69]), "+f"(d[70]), "+f"(d[71]), "+f"(d[72]), "+f"(d[73]), "+f"(d[74]), "+f"(d[75]), "+f"(d[76]), "+f"(d[77]), "+f"(d[78]), "+f"(d[79]), "+f"(d[80]), "+f"(d[81]), "+f"(d[82]), "+f"(d[83]), "+f"(d[84]), "+f"(d[85]), "+f"(d[86]), "+f"(d[87]), "+f"(d[88]), "+f"(d[89]), "+f"(d[90]), "+f"(d[91]), "+f"(d[92]), "+f"(d[93]), "+f"(d[94]), "+f"(d[95]) : "r"(alo), "r"(aimm), "r"(blo), "r"(bimm), "r"(bhi), "r"(sc));
}

constexpr uint32_t DESC_HI = (1024u >> 4) | (1u << 30);
constexpr uint32_t DESC_HI64 = (512u >> 4) | (2u << 30);
template <int n> __device__ __forceinline__ void fence_regs(float* a) {
#pragma unroll
  for (int i = 0; i < n; i++) asm volatile("" : "+f"(a[i])::"memory");
}

struct Ctx {
  uint32_t full, emb;
  bool sig;
  uint32_t o0, o1;
  uint32_t p0, p1;
  uint32_t dB, dA;
  int budget;
  __device__ __forceinline__ static int m6(int s) { return s >= 12 ? s - 12 : (s >= 6 ? s - 6 : s); }
  __device__ __forceinline__ uint32_t hb(int s) const { return m6(s) < 3 ? o0 : o1; }
  __device__ __forceinline__ static int m3(int s) { return m6(s) < 3 ? m6(s) : m6(s) - 3; }
  __device__ __forceinline__ void release(int s) { if (sig) mbar_arrive_cl(emb + 8 * hb(s) + 8 * m3(s)); }
  __device__ __forceinline__ void wait(uint32_t a, uint32_t ph) {
    uint32_t ok;
#pragma unroll 1
    do {
      asm volatile("{.reg .pred p; mbarrier.try_wait.parity.shared::cta.b64 p, [%1], %2; selp.u32 %0,1,0,p;}" : "=r"(ok) : "r"(a), "r"(ph) : "memory");
      budget--;
    } while ((ok == 0) & (budget > 0));
  }
  __device__ __forceinline__ void wait_full(int s) {
    const uint32_t a = full + 8 * hb(s) + 8 * m3(s), ph = (m6(s) < 3 ? p0 : p1) ^ ((s >= 6 && s < 12) ? 1u : 0u);
    wait(a, ph);
    wg_fence();
  }
  __device__ __forceinline__ void set(uint32_t sw, uint32_t second) { o0 = sw ? 3 : 0; o1 = 3 - o0; p0 = second; p1 = second ^ sw; }
};

__device__ __forceinline__ void issue192(float* acc, Ctx& c, int s, bool first = false) {
  c.wait_full(s);
  const uint32_t db = c.dB + c.hb(s) * (STAGE_BYTES >> 4);
  wgmma_ss<192>(acc, c.dA, (s >> 1) * 1024 + (s & 1) * 4, db, Ctx::m3(s) * (STAGE_BYTES >> 4), DESC_HI, first ? 0 : 1);
  wgmma_ss<192>(acc, c.dA, (s >> 1) * 1024 + (s & 1) * 4 + 2, db, Ctx::m3(s) * (STAGE_BYTES >> 4) + 128, DESC_HI, 1);
  wg_commit();
}
template <class Pre, class Post>
__device__ __forceinline__ void plain192(float* acc, Ctx& c, int s, int e, Pre pre, Post post) {
  uint32_t st = c.hb(s) + Ctx::m3(s), pst = c.hb(s - 1) + Ctx::m3(s - 1), ph = (Ctx::m6(s) < 3 ? c.p0 : c.p1) ^ ((s >= 6 && s < 12) ? 1u : 0u);
  uint32_t da = c.dA + (s >> 1) * 1024 + (s & 1) * 4;
#pragma unroll 1
  for (; s < e; s++) {
    pre(s);
    c.wait(c.full + 8 * st, ph);
    wg_fence();
    const uint32_t db = c.dB + st * (STAGE_BYTES >> 4);
    wgmma_ss<192>(acc, da, 0, db, 0, DESC_HI, 1);
    wgmma_ss<192>(acc, da, 2, db, 128, DESC_HI, 1);
    wg_commit();
    const uint32_t rel = c.emb + 8 * pst;
    pst = st;
    st = st == 5 ? 0 : st + 1;
    ph ^= st == 0 ? 1u : 0u;
    da += (s & 1) ? 1020 : 4;
    wg_wait<1>();
    if (c.sig) mbar_arrive_cl(rel);
    post(s);
  }
}
__device__ __forceinline__ void issue96(float* acc, Ctx& c, int k, bool first) {
  c.wait_full(k);
  const uint32_t db = c.dB + c.hb(k) * (STAGE_BYTES >> 4);
  if (first) { wgmma_ss<192>(acc, c.dA, k * 1024, db, Ctx::m3(k) * (STAGE_BYTES >> 4), DESC_HI64, 0); wg_fence(); }
#pragma unroll
  for (int kk = first ? 1 : 0; kk < 4; kk++) wgmma_ss<96>(acc, c.dA, k * 1024 + 2 * kk, db, Ctx::m3(k) * (STAGE_BYTES >> 4) + 64 * kk, DESC_HI64, 1);
  wg_commit();
}
__device__ __forceinline__ void retire(Ctx& c, int prev) {
  wg_wait<1>();
  c.release(prev);
}

constexpr float GK = 0.32920349f;
__device__ __forceinline__ uint32_t gelu_pair(uint32_t y) {
  uint32_t u, th;
  asm("mul.rn.bf16x2 %0, %1, %2;" : "=r"(u) : "r"(hfma2(y, y, 0x401b401bu)), "r"(y));
  asm("tanh.approx.bf16x2 %0, %1;" : "=r"(th) : "r"(u));
  return hfma2(y, th, y);
}
__device__ __forceinline__ uint4 gelu_group(const uint32_t* a) { return make_uint4(gelu_pair(a[0]), gelu_pair(a[1]), gelu_pair(a[2]), gelu_pair(a[3])); }
__device__ __forceinline__ void lds_bias(float2* b, uint32_t addr) {
#pragma unroll
  for (int j = 0; j < 2; j++) asm volatile("ld.shared.v2.f32 {%0,%1}, [%2];" : "=f"(b[j].x), "=f"(b[j].y) : "r"(addr + 32 * j));
}
__device__ __forceinline__ int opaque(int v) { asm volatile("" : "+r"(v)); return v; }
__device__ __forceinline__ void stsm4(uint32_t addr, uint4 r) {
  asm volatile("stmatrix.sync.aligned.m8n8.x4.shared.b16 [%0], {%1,%2,%3,%4};" ::"r"(addr), "r"(r.x), "r"(r.y), "r"(r.z), "r"(r.w) : "memory");
}
__device__ __forceinline__ float ex2f(float x) { float r; asm("ex2.approx.ftz.f32 %0, %1;" : "=f"(r) : "f"(x)); return r; }
__device__ __forceinline__ uint32_t phi_pack(uint32_t tp, float a0, float a1, uint32_t c1, uint32_t c2) {
  uint32_t x, y;
  asm("max.bf16x2 %0, %1, %2;" : "=r"(x) : "r"(tp), "r"(c1));
  asm("min.bf16x2 %0, %1, %2;" : "=r"(y) : "r"(pack_bf16(ex2f(a0), ex2f(a1))), "r"(c2));
  return hadd2(x, y);
}
template <int q0, int q1>
__device__ __forceinline__ void part_groups(const float* a, uint4* p, uint32_t par) {
#pragma unroll
  for (int q = q0; q < q1; q++)
    st_ll(p + q * 32, pack_bf16(a[8 * q], a[8 * q + 1]), pack_bf16(a[8 * q + 2], a[8 * q + 3]), pack_bf16(a[8 * q + 4], a[8 * q + 5]), pack_bf16(a[8 * q + 6], a[8 * q + 7]), par);
}
__device__ __forceinline__ float rcpf(float x) { float r; asm("rcp.approx.ftz.f32 %0, %1;" : "=f"(r) : "f"(x)); return r; }
__device__ __forceinline__ float silu_h(float h) { float r; asm("tanh.approx.f32 %0, %1;" : "=f"(r) : "f"(h)); return fmaf(h, r, h); }
__device__ __forceinline__ int pairoff(int p, int g) { return (p >> 2) * 32 + g * 4 + (p & 3); }
template <bool STRONG, int J0, int J1> __device__ __forceinline__ void d1_load(uint32_t* W, int rb0, int head, int ln) {
  const uint2* qf = g_qkv + rb0 * 216 * 32 + pairoff(288 + head * 9 + (ln & 3), ln >> 2);
#pragma unroll
  for (int b = 0; b < 3; b++) {
#pragma unroll
    for (int j = J0; j < J1; j++) {
      const uint2* p = qf + j * 216 * 32 + 32 * b;
      const uint2 kk = STRONG ? ld_ll64(p) : ld_ca64(p), vv = STRONG ? ld_ll64(p + 72 * 32) : ld_ca64(p + 72 * 32);
      W[6 * j + 2 * b] = kk.x; W[6 * j + 2 * b + 1] = kk.y; W[24 + 6 * j + 2 * b] = vv.x; W[24 + 6 * j + 2 * b + 1] = vv.y;
    }
  }
}
__device__ __forceinline__ bool d1_bad(const uint32_t* W, int t, uint32_t par) {
  uint32_t bad = 0, bad2 = 0;
#pragma unroll
  for (int q = 0; q < 12; q++) ll_chk((q % 3) != 2 ? bad : bad2, W[2 * q], W[24 + 2 * q], par);
  return __any_sync(0xffffffffu, (bad | (t == 0 ? bad2 : 0u)) & 1);
}
__device__ __forceinline__ void d1_mov(uint32_t* W, int j, int t) {
  if (t != 0) { W[6 * j + 4] = W[6 * j + 5] = 0u; W[24 + 6 * j + 4] = W[24 + 6 * j + 5] = (t == 1 ? 0x00003f80u : 0u); }
#pragma unroll
  for (int q = 0; q < 6; q++) { W[6 * j + q] = movmat(W[6 * j + q]); W[24 + 6 * j + q] = movmat(W[24 + 6 * j + q]); }
}
__device__ __forceinline__ void d1_mma(const uint32_t* W, float* R, float zero) {
  float c1[3][4];
#pragma unroll
  for (int j = 0; j < 12; j++) { R[j] = (j & 3) ? 0.f : zero; c1[j >> 2][j & 3] = (j & 3) ? 0.f : zero; }
#pragma unroll
  for (int ks = 0; ks < 4; ks++)
#pragma unroll
    for (int j = 0; j < 3; j++) {
      mma16816(R + 4 * j, W[24 + 6 * ks], W[24 + 6 * ks + 2], W[24 + 6 * ks + 1], W[24 + 6 * ks + 3], W[6 * ks + 2 * j], W[6 * ks + 2 * j + 1]);
      mma16816(c1[j], W[24 + 6 * ks + 4], 0u, W[24 + 6 * ks + 5], 0u, W[6 * ks + 2 * j], W[6 * ks + 2 * j + 1]);
    }
#pragma unroll
  for (int j = 0; j < 3; j++) { R[12 + 2 * j] = c1[j][0]; R[13 + 2 * j] = c1[j][1]; }
}
__device__ __forceinline__ bool kv_valid(int w, int ln) { return (w < 3 || ln < 12) && ((w != 2 && w != 4) || (ln & 3) == 0); }

struct Params {
  CUtensorMap tm_wqkv, tm_w1, tm_w2, tm_m, tm_wqkv64, tm_m64, tm_a, tm_ast;
  const __nv_bfloat16 *x, *b1, *b2, *wqkv, *w1, *w2, *wo;
  __nv_bfloat16* out;
};

__global__ void __cluster_dims__(2, 1, 1) __launch_bounds__(NTHREADS, 1) fused_kernel(const __grid_constant__ Params P) {
  extern __shared__ __align__(1024) uint8_t smem[];
  const uint32_t sbase = smem_u32(smem);
  const int tid = threadIdx.x, lane = tid & 31;
  const int warp = __shfl_sync(0xffffffffu, tid >> 5, 0);
  const int g = lane >> 2, t = lane & 3;
  const uint32_t ep = __shfl_sync(0xffffffffu, g_epoch[blockIdx.x], 0) + 1;
  const uint32_t par = ep & 1;
  STAMPW(0, 0);

  if (blockIdx.x >= 128) {
    const int a = blockIdx.x - 128;
    constexpr int WP = 1168, SM_T = 152 * WP, SM_HB = SM_T + 8 * 32 * 80;
    if (tid == 0) {
      mbar_init(sbase + SM_HB, 1);
      asm volatile("fence.mbarrier_init.release.cluster;" ::: "memory");
      mbar_expect(sbase + SM_HB, 144 * 1152);
    }
    for (int i = tid; i < (8 * WP + 8 * 32 * 80) / 4; i += NTHREADS) reinterpret_cast<uint32_t*>(smem + 144 * WP)[i] = 0u;
    __syncthreads();
    __nanosleep(1500);
    if (tid < 144)
      asm volatile("cp.async.bulk.shared::cluster.global.mbarrier::complete_tx::bytes [%0], [%1], %2, [%3];" ::"r"(sbase + tid * WP), "l"(P.wo + (a * 144 + tid) * D_), "r"(1152), "r"(sbase + SM_HB) : "memory");
    if (warp >= 8 && lane == 0) {
      const int id = a * 4 + (warp - 8);
      constexpr uint32_t CH = 9216 * 2;
#pragma unroll 1
      for (int i = id; i < 576; i += 16) {
        const char* p = i < 288 ? (const char*)P.w1 + (size_t)i * CH : (const char*)P.w2 + (size_t)(i - 288) * CH;
        asm volatile("cp.async.bulk.prefetch.L2.global [%0], %1;" ::"l"(p), "r"(CH) : "memory");
      }
    }
    __syncwarp();
    if (lane < 8) hint_wait(&g_f_kvp[a * 8 + lane], 16 * ep, 50);
    __syncwarp();
    STAMPW(0, 1);
#pragma unroll 1
    for (int u = warp; u < 40; u += 12) {
      const int hh = u & 7, w = 4 - (u >> 3), head = a * 8 + hh;
      uint4 v[16];
      int tries = 0;
      uint32_t bad;
      const bool val = kv_valid(w, lane);
#pragma unroll 1
      do {
        bad = 0;
#pragma unroll
        for (int j = 0; j < 16; j++) v[j] = val ? ld_ll(&g_kvp[((head * 5 + w) * 16 + j) * 32 + lane]) : make_uint4(par, 0u, par, 0u);
#pragma unroll
        for (int j = 0; j < 16; j++) ll_chk(bad, v[j].x, v[j].z, par);
      } while (__any_sync(0xffffffffu, bad & 1) && ++tries < (1 << 20));
      float s0 = 0.f, s1 = 0.f, s2 = 0.f, s3 = 0.f;
#pragma unroll
      for (int j = 0; j < 16; j++) { s0 += __uint_as_float(v[j].x); s1 += __uint_as_float(v[j].y); s2 += __uint_as_float(v[j].z); s3 += __uint_as_float(v[j].w); }
      if (w >= 3) {
        if (g == 2) st_ll(&g_z[(head * 2 + w - 3) * 4 + t], __float_as_uint(s0), __float_as_uint(s1), __float_as_uint(s2), __float_as_uint(s3), par);
        __syncwarp();
        hint_signal(&g_f_z[head]);
      }
      const int e0 = w < 3 ? g : 16 + g, e1 = w < 3 ? g + 8 : 16 + g, d0 = (w < 3 ? 8 * w : (w == 3 ? 0 : 16)) + 2 * t, d1 = w < 3 ? d0 : d0 + 8;
      __nv_bfloat16* T = reinterpret_cast<__nv_bfloat16*>(smem + SM_T) + hh * 32 * 40;
      if (e0 < 18) {
        T[d0 * 40 + e0] = __float2bfloat16(s0); T[(d0 + 1) * 40 + e0] = __float2bfloat16(s1);
        T[d1 * 40 + e1] = __float2bfloat16(s2); T[(d1 + 1) * 40 + e1] = __float2bfloat16(s3);
      }
    }
    __syncthreads();
    STAMPW(0, 2);
    mbar_wait(sbase + SM_HB, 0);
#pragma unroll 1
    for (int u = warp; u < 24; u += 12) {
      const int hh = u / 3, c0 = (u % 3) * 192;
      const uint32_t* T = reinterpret_cast<const uint32_t*>(smem + SM_T) + hh * 32 * 20 + g * 20 + t;
      const uint32_t a00 = T[0], a01 = T[160], a02 = T[4], a03 = T[164], a10 = T[8], a11 = T[168], b00 = T[320], b02 = T[324], b10 = T[328];
      const uint32_t rowa = sbase + (hh * 18 + (lane & 15)) * WP + (c0 + (lane >> 4) * 8) * 2, rowb = sbase + (hh * 18 + 16 + (lane & 7)) * WP + (c0 + ((lane >> 3) & 1) * 8) * 2;
#pragma unroll 3
      for (int j = 0; j < 12; j++) {
        uint32_t w0, w1, w2, w3, w4, w5;
        asm volatile("ldmatrix.sync.aligned.m8n8.x4.trans.shared.b16 {%0,%1,%2,%3}, [%4];" : "=r"(w0), "=r"(w1), "=r"(w2), "=r"(w3) : "r"(rowa + j * 32));
        asm volatile("ldmatrix.sync.aligned.m8n8.x2.trans.shared.b16 {%0,%1}, [%2];" : "=r"(w4), "=r"(w5) : "r"(rowb + j * 32));
        float p[4][4];
#pragma unroll
        for (int q = 0; q < 4; q++) p[q][0] = p[q][1] = p[q][2] = p[q][3] = 0.f;
        mma16816(p[0], a00, a01, a02, a03, w0, w1); mma16816(p[1], a00, a01, a02, a03, w2, w3);
        mma16816(p[2], b00, 0u, b02, 0u, w0, w1); mma16816(p[3], b00, 0u, b02, 0u, w2, w3);
        mma16816(p[0], a10, a11, 0u, 0u, w4, 0u); mma16816(p[1], a10, a11, 0u, 0u, w5, 0u);
        mma16816(p[2], b10, 0u, 0u, 0u, w4, 0u); mma16816(p[3], b10, 0u, 0u, 0u, w5, 0u);
        stsm4(rowa + j * 32, make_uint4(pack_bf16(p[0][0], p[0][1]), pack_bf16(p[0][2], p[0][3]), pack_bf16(p[1][0], p[1][1]), pack_bf16(p[1][2], p[1][3])));
        if (g < 2) {
          uint32_t* r = reinterpret_cast<uint32_t*>(smem + (hh * 18 + 16 + g) * WP + (c0 + j * 16 + 2 * t) * 2);
          r[0] = pack_bf16(p[2][0], p[2][1]); r[4] = pack_bf16(p[3][0], p[3][1]);
        }
      }
      asm volatile("fence.proxy.async.shared::cta;" ::: "memory");
      __syncwarp();
      if (lane < 18) {
        asm volatile("cp.async.bulk.global.shared::cta.bulk_group [%0], [%1], %2;" ::"l"(g_m + (a * 144 + hh * 18 + lane) * D_ + c0), "r"(sbase + (hh * 18 + lane) * WP + c0 * 2), "r"(384) : "memory");
        asm volatile("cp.async.bulk.commit_group;" ::: "memory");
      }
    }
    asm volatile("cp.async.bulk.wait_group 0;" ::: "memory");
    asm volatile("fence.proxy.async.global;" ::: "memory");
    __syncwarp();
    if (lane == 0) asm volatile("red.release.gpu.global.add.u32 [%0], 1;" ::"l"(g_f_m) : "memory");
    STAMPW(0, 3);
    __syncthreads();
    if (tid == 0) g_epoch[blockIdx.x] = ep;
    return;
  }

  const int cl = blockIdx.x >> 1, rank = blockIdx.x & 1;
  const int f = cl & 7, m = (cl >> 3) * 2 + rank;
  const int srole = f >= 6 ? 1 : 0;
  const uint32_t bar_full = sbase + SM_BAR, bar_empty = bar_full + 8 * NSTAGE, bar_xfree = bar_empty + 8 * NSTAGE, bar_ofull = bar_xfree + 72,
                 bar_d = bar_ofull + 72;

  if (tid == 0) {
#pragma unroll 1
    for (int i = 0; i < NSTAGE; i++) { mbar_init(bar_full + 8 * i, 1); mbar_init(bar_empty + 8 * i, 4); }
#pragma unroll 1
    for (int i = 0; i < 9; i++) { mbar_init(bar_xfree + 8 * i, 2); mbar_init(bar_ofull + 8 * i, 1); }
    mbar_init(bar_d, 1);
    asm volatile("fence.mbarrier_init.release.cluster;" ::: "memory");
  }
  __syncwarp();
  cluster_arrive_relaxed();

  if (warp >= 8) {
    const int srow = m * 128 + f * 16 + (warp - 8) * 4 + (lane >> 3);
    uint4 xs[9];
#pragma unroll
    for (int kb = 0; kb < 9; kb++) xs[kb] = __ldg(reinterpret_cast<const uint4*>(P.x + srow * D_) + (lane & 7) + kb * 8);
    auto stats = [&]() {
      const uint32_t* w = reinterpret_cast<const uint32_t*>(xs);
      float s0 = 0.f, s1 = 0.f;
#pragma unroll
      for (int i = 0; i < 36; i++) { s0 += bf_lo(w[i]); s1 += bf_hi(w[i]); }
      float sum = s0 + s1;
      sum += __shfl_xor_sync(0xffffffffu, sum, 1); sum += __shfl_xor_sync(0xffffffffu, sum, 2); sum += __shfl_xor_sync(0xffffffffu, sum, 4);
      const float mean = sum * (1.f / 576.f);
      s0 = 0.f; s1 = 0.f;
#pragma unroll
      for (int i = 0; i < 36; i++) { const float a = bf_lo(w[i]) - mean, b = bf_hi(w[i]) - mean; s0 = fmaf(a, a, s0); s1 = fmaf(b, b, s1); }
      float sq = s0 + s1;
      sq += __shfl_xor_sync(0xffffffffu, sq, 1); sq += __shfl_xor_sync(0xffffffffu, sq, 2); sq += __shfl_xor_sync(0xffffffffu, sq, 4);
      const float rstd = rsqrtf(sq * (1.f / 576.f) + 1e-5f);
      if ((lane & 7) == 0)
        st_ll64(&g_stat[srow], __float_as_uint(rstd), pack_bf16(-mean, -mean), par);
    };
    stats();
    asm volatile("setmaxnreg.dec.sync.aligned.u32 40;");
    cluster_wait();
    if (warp == 8) {
      if (lane == 0) {
        uint32_t stage = 0, phase = 1;
        const uint32_t sb = sbase + SM_B;
#pragma unroll 1
        for (int tl = 2 * srole; tl < 8 + 2 * srole; tl++) {
          const CUtensorMap* map = tl == 0 ? &P.tm_wqkv : (tl == 1 ? &P.tm_wqkv64 : (tl < 5 ? &P.tm_w1 : (tl < 8 ? &P.tm_w2 : (tl == 8 ? &P.tm_m : &P.tm_m64))));
          const int col = tl < 2 ? 288 * f + 192 * tl : (tl < 5 ? 576 * f + 192 * (tl - 2) : (tl < 8 ? 192 * ((tl - 5 + f) % 3) : (tl == 8 ? 192 * (f - 5) : 96 * (f - 6))));
          const bool perm = tl >= 5 && tl < 8;
          const bool z = (tl & 7) == 1;
          if (tl == 8) { flag_wait(g_f_m, 48 * ep); asm volatile("fence.proxy.async.global;" ::: "memory"); }
          const int cs = z ? 32 : 64, rs = z ? 64 : 32, nst = z ? 9 : 18;
#pragma unroll 1
          for (int st = 0; st < nst; st++) {
            int row = st * rs;
            if (perm) row += 576 * f + ((st < 6) ? 192 : (st < 12 ? -192 : 0));
            mbar_wait(bar_empty + 8 * stage, phase);
            mbar_expect(bar_full + 8 * stage, 12288);
            const uint32_t dst = sb + stage * STAGE_BYTES;
            if (((st ^ rank) & 1) == 0) {
              tma2d_mc(dst, map, col, row, bar_full + 8 * stage);
              tma2d_mc(dst + 8192, map, col + 2 * cs, row, bar_full + 8 * stage);
            } else {
              tma2d_mc(dst + 4096, map, col + cs, row, bar_full + 8 * stage);
            }
            if (++stage == NSTAGE) { stage = 0; phase ^= 1; }
          }
        }
      }
      __syncwarp();
    } else {
      const int aw = warp - 9;
      const int hi = f >> 2;
      if (aw == 0) {
        if (lane < 2) hint_wait(&g_f_qkv[m * 8 + 2 + 2 * lane + hi], 16 * ep, 200);
        __syncwarp();
        if (lane == 0) mbar_arrive(bar_d);
        STAMP(20);
      }
      if (lane < 5) hint_wait(lane < 4 ? &g_f_z[4 * f + lane] : &g_f_qkv[m * 8 + hi], lane < 4 ? 2 * ep : 16 * ep);
      __syncwarp();
      STAMPW(9, 22);
      uint32_t* stg = reinterpret_cast<uint32_t*>(smem + SM_SCR + aw * 2304);
#pragma unroll 1
      for (int u = aw * 2; u < 16; u += (u & 1) ? 5 : 1) {
        const int rbl = u >> 1, hp = (u & 1) * 2;
        const uint2* qf = g_qkv + (m * 8 + rbl) * 216 * 32;
        const uint2* zp = reinterpret_cast<const uint2*>(&g_z[(4 * f + hp) * 8 + t]);
        uint2 q[2][3];
        float d[4];
        int tries = 0;
        uint32_t bad;
#pragma unroll 1
        do {
          bad = tries ? ld_acquire(g_f_m) & 0u : 0u;
#pragma unroll
          for (int j = 0; j < 2; j++)
#pragma unroll
            for (int b = 0; b < 3; b++) q[j][b] = ld_ca64(qf + pairoff((4 * f + hp + j) * 9 + t, g) + 32 * b);
#pragma unroll
          for (int j = 0; j < 2; j++) {
            const uint2 z0 = ld_ca64(zp + 16 * j), z1 = ld_ca64(zp + 16 * j + 1), z2 = ld_ca64(zp + 16 * j + 8);
            if (t != 0) q[j][2] = make_uint2(par, 0u);
            ll_chk(bad, z0.x, z1.x, par); ll_chk(bad, z2.x, q[j][2].x, par); ll_chk(bad, q[j][0].x, q[j][1].x, par);
            d[2 * j] = bf_lo(q[j][0].x) * __uint_as_float(z0.x) + bf_hi(q[j][0].x) * __uint_as_float(z0.y) + bf_lo(q[j][1].x) * __uint_as_float(z1.x) + bf_hi(q[j][1].x) * __uint_as_float(z1.y) +
                       bf_lo(q[j][2].x) * __uint_as_float(z2.x) + bf_hi(q[j][2].x) * __uint_as_float(z2.y);
            d[2 * j + 1] = bf_lo(q[j][0].y) * __uint_as_float(z0.x) + bf_hi(q[j][0].y) * __uint_as_float(z0.y) + bf_lo(q[j][1].y) * __uint_as_float(z1.x) + bf_hi(q[j][1].y) * __uint_as_float(z1.y) +
                           bf_lo(q[j][2].y) * __uint_as_float(z2.x) + bf_hi(q[j][2].y) * __uint_as_float(z2.y);
          }
        } while (__any_sync(0xffffffffu, bad & 1) && ++tries < (1 << 20));
#pragma unroll
        for (int j = 0; j < 4; j++) d[j] += __shfl_xor_sync(0xffffffffu, d[j], 1);
#pragma unroll
        for (int j = 0; j < 4; j++) d[j] = rcpf(d[j] + __shfl_xor_sync(0xffffffffu, d[j], 2) + 1e-6f);
        if (hp == 0) { asm volatile("cp.async.bulk.wait_group.read 0;" ::: "memory"); __syncwarp(); }
#pragma unroll
        for (int j = 0; j < 2; j++) {
          const uint32_t r0 = pack_bf16(d[2 * j], d[2 * j]), r1 = pack_bf16(d[2 * j + 1], d[2 * j + 1]);
#pragma unroll
          for (int b = 0; b < 3; b++)
            if (b < 2 || t == 0) {
              stg[g * 36 + (hp + j) * 9 + 4 * b + t] = hfma2(q[j][b].x, r0, 0x80008000u);
              stg[(g + 8) * 36 + (hp + j) * 9 + 4 * b + t] = hfma2(q[j][b].y, r1, 0x80008000u);
            }
        }
        if (hp != 0) {
          asm volatile("fence.proxy.async.shared::cta;" ::: "memory");
          __syncwarp();
          if (lane == 0) {
            asm volatile("cp.async.bulk.tensor.2d.global.shared::cta.bulk_group [%0, {%2, %3}], [%1];" ::"l"(&P.tm_ast), "r"(smem_u32(stg)), "r"(72 * f), "r"(m * 128 + rbl * 16) : "memory");
            asm volatile("cp.async.bulk.commit_group;" ::: "memory");
          }
        }
      }
      asm volatile("cp.async.bulk.wait_group 0;" ::: "memory");
      asm volatile("fence.proxy.async.global;" ::: "memory");
      STAMPW(9, 26);
      asm volatile("bar.sync 5, 96;" ::: "memory");
      if (tid == 288) asm volatile("red.release.gpu.global.add.u32 [%0], 1;" ::"l"(&g_f_a[m]) : "memory");
      __syncwarp();
      STAMPW(9, 23);
      if (srole && aw == 2) {
        if (lane == 0) {
          flag_wait(&g_f_a[m], 8 * ep);
          asm volatile("fence.proxy.async.global;" ::: "memory");
#pragma unroll 1
          for (int kb = 0; kb < 9; kb++) {
            mbar_wait(bar_xfree + 8 * kb, 0);
            mbar_expect(bar_ofull + 8 * kb, 16384);
            tma2d(sbase + SM_A + kb * 16384, &P.tm_a, kb * 64, m * 128, bar_ofull + 8 * kb);
          }
        }
        __syncwarp();
      }
    }
    cluster_arrive_relaxed();
    cluster_wait();
  } else {
    const int wg = warp >> 2;
    {
      const int rs = lane >> 3, j = lane & 7;
      uint4 xv[4][9];
#pragma unroll
      for (int it = 0; it < 4; it++)
#pragma unroll
        for (int kb = 0; kb < 9; kb++) xv[it][kb] = __ldg(reinterpret_cast<const uint4*>(P.x + (m * 128 + warp * 16 + it * 4 + rs) * D_) + j + kb * 8);
      uint32_t bw0 = __ldg(reinterpret_cast<const uint32_t*>(P.b1 + 576 * f) + tid), bw1 = tid < 32 ? __ldg(reinterpret_cast<const uint32_t*>(P.b1 + 576 * f) + 256 + tid) : 0u;
      uint2 st[4];
      int tries = 0;
      uint32_t bad;
#pragma unroll 1
      do {
        bad = 0;
#pragma unroll
        for (int it = 0; it < 4; it++) st[it] = ld_ll64(&g_stat[m * 128 + warp * 16 + it * 4 + rs]);
        ll_chk(bad, st[0].x, st[1].x, par); ll_chk(bad, st[2].x, st[3].x, par);
      } while (__any_sync(0xffffffffu, bad & 1) && ++tries < (1 << 22));
      STAMPW(0, 19);
#pragma unroll
      for (int it = 0; it < 4; it++) {
        const uint32_t nm = st[it].y;
        uint8_t* dst = smem + SM_A + (warp * 16 + it * 4 + rs) * 128 + ((j ^ ((it * 4 + rs) & 7)) << 4);
#pragma unroll
        for (int kb = 0; kb < 9; kb++) {
          const uint4 w = xv[it][kb];
          *reinterpret_cast<uint4*>(dst + kb * 16384) = make_uint4(hadd2(w.x, nm), hadd2(w.y, nm), hadd2(w.z, nm), hadd2(w.w, nm));
        }
        if (j == 0) reinterpret_cast<uint32_t*>(smem + SM_RSTD)[warp * 16 + it * 4 + rs] = st[it].x;
      }
      reinterpret_cast<float2*>(smem + SM_BIAS)[tid] = make_float2(bf_lo(bw0) * GK, bf_hi(bw0) * GK);
      if (tid < 48) reinterpret_cast<float2*>(smem + SM_BIAS)[256 + tid] = make_float2(bf_lo(bw1) * GK, bf_hi(bw1) * GK);
      asm volatile("fence.proxy.async.shared::cta;" ::: "memory");
    }
    asm volatile("setmaxnreg.inc.sync.aligned.u32 232;");
    cluster_wait();
    asm volatile("bar.sync 1, 256;" ::: "memory");
    STAMPW(0, 1);
    Ctx c;
    c.full = bar_full; c.budget = 1 << 22;
    c.emb = __shfl_sync(0xffffffffu, mapa(bar_empty, (warp & 3) == 0 ? rank : (rank ^ 1)), 0);
    c.sig = lane == 0 && (warp & 3) < 2;
    c.dB = (((sbase + SM_B) & 0x3FFFF) >> 4) | ((4096u >> 4) << 16);
    c.dA = (((sbase + SM_A + wg * 8192) & 0x3FFFF) >> 4) | (1u << 16);
    const bool leader = (lane == 0) && ((warp & 3) == 0);

    const int rb = m * 8 + warp;
    const uint32_t bias_t = sbase + SM_BIAS + 8 * t;
    const uint32_t hst = sbase + SM_A + (warp * 16 + (lane & 7) + ((lane >> 3) & 1) * 8) * 128 + (((lane >> 4) ^ (lane & 7)) << 4);
    auto wg_sync = [&]() {
      asm volatile("fence.proxy.async.shared::cta;" ::: "memory");
      if (wg == 0) asm volatile("bar.sync 2, 128;" ::: "memory"); else asm volatile("bar.sync 3, 128;" ::: "memory");
    };
    float A[96], B[96];
#pragma unroll
    for (int i = 0; i < 96; i++) B[i] = 0.f;
#define EXB(ACC, U) uint32_t E[4]; _Pragma("unroll") for (int q = 0; q < 4; q++) E[q] = pack_bf16(fmaf(ACC[8 * (U) + 2 * q], (q & 1) ? r1 : r0, bs[q >> 1].x), fmaf(ACC[8 * (U) + 2 * q + 1], (q & 1) ? r1 : r0, bs[q >> 1].y));
#define ST_QKV(ACC, U, DST) { uint32_t E[4]; _Pragma("unroll") for (int q = 0; q < 4; q++) \
      E[q] = phi_pack(pack_bf16(ACC[8 * (U) + 2 * q] * ((q & 1) ? r1 : r0), ACC[8 * (U) + 2 * q + 1] * ((q & 1) ? r1 : r0)), ACC[8 * (U) + 2 * q] * ((q & 1) ? l1 : l0), ACC[8 * (U) + 2 * q + 1] * ((q & 1) ? l1 : l0), pc1, pc2); \
    st_ll64(reinterpret_cast<uint2*>(DST) + 64 * (U), E[0], E[1], par); st_ll64(reinterpret_cast<uint2*>(DST) + 64 * (U) + 32, E[2], E[3], par); }
#define PHI_SETUP const float l0 = r0 * 1.4426950408889634f, l1 = r1 * 1.4426950408889634f; const uint32_t pc1 = f < 4 ? 0x35863586u : 0xff80ff80u, pc2 = f < 4 ? 0x3f803f80u : 0u;
#define HADDR(KB0, U) ((hst ^ (((U) & 3) << 5)) + ((KB0) + ((U) >> 2)) * 16384)
#define LDS_R(SC) float r0, r1; asm volatile("ld.shared.f32 %0, [%1];" : "=f"(r0) : "r"(rst)); asm volatile("ld.shared.f32 %0, [%1];" : "=f"(r1) : "r"(rst + 32)); r0 *= (SC); r1 *= (SC);
    const uint32_t rst = sbase + SM_RSTD + (warp * 16 + g) * 4;
    const int fr = f % 3;
#pragma unroll 1
    for (int i = srole;; i++) {
      {
        c.set((!srole && i >= 1) ? 1u : 0u, 0u);
        const uint32_t owp = i == 4 ? 0u : 1u;
        c.wait(bar_ofull, owp);
        issue192(A, c, 0, true);
        const int ln = opaque(lane);
        uint4* dst = i == 1 ? reinterpret_cast<uint4*>(g_qkv + (rb * 216 + 36 * f + 24) * 32 + ln) : g_part + ((rb * 8 + f) * 36 + 12 * (i == 3 ? fr : (fr + 2) % 3)) * 32 + ln;
        LDS_R(i == 2 ? GK : 1.f)
#define HEAD(ACC) wg_wait<1>(); c.release(4); c.release(5); fence_regs<96>(ACC);
        int s = 1;
        if (i == 2) {
          HEAD(B)
#pragma unroll
          for (int k = 1; k < 9; k++) {
            float2 b0[2], b1[2];
            if (k >= 3) { lds_bias(b0, bias_t + (192 + 32 * (k - 3)) * 4); lds_bias(b1, bias_t + (208 + 32 * (k - 3)) * 4); }
            issue192(A, c, k);
            if (k >= 3) {
              const int u = k >= 3 ? 2 * (k - 3) : 0;
              { const float2* bs = b0; EXB(B, u) stsm4(HADDR(0, u), gelu_group(E)); }
              { const float2* bs = b1; EXB(B, u + 1) stsm4(HADDR(0, u + 1), gelu_group(E)); }
            }
            retire(c, k - 1);
          }
          s = 9;
        } else if (i >= 3) {
          HEAD(B)
          if (i == 4 && leader) mbar_arrive(bar_xfree + 64);
#pragma unroll
          for (int u = 0; u < 12; u++) {
            if (u & 1) c.wait(bar_ofull + 4 * (u + 1), owp);
            issue192(A, c, u + 1);
            part_groups<0, 1>(&B[8 * u], dst + u * 32, par);
            retire(c, u);
          }
          s = 13;
        } else if (i > srole) {
          PHI_SETUP
          HEAD(B)
#pragma unroll
          for (int u = 0; u < 6; u++) {
            issue192(A, c, u + 1);
            ST_QKV(B, u, dst)
            retire(c, u);
          }
          hint_signal(&g_f_qkv[m * 8 + f]);
          s = 7;
        } else wg_wait<1>();
        const bool d1 = i == 1 + srole;
        const int send = d1 ? 10 : 15;
        plain192(A, c, s, send, [&](int k) { if (k == 14) c.wait(bar_ofull + 56, owp); }, [](int) {});
        uint32_t W[48];
        if (d1) {
          const int head = 4 * f + (warp >> 1), rb0 = m * 8 + (warp & 1) * 4;
          issue192(A, c, 10);
          c.wait(bar_d, 0);
          d1_load<false, 0, 2>(W, rb0, head, opaque(lane));
          retire(c, 9);
          issue192(A, c, 11);
          d1_load<false, 2, 4>(W, rb0, head, opaque(lane));
          retire(c, 10);
          issue192(A, c, 12);
          retire(c, 11);
          issue192(A, c, 13);
          int tries = 0;
#pragma unroll 1
          while (d1_bad(W, t, par) && ++tries < (1 << 20)) d1_load<true, 0, 4>(W, rb0, head, opaque(lane));
          d1_mov(W, 0, t); d1_mov(W, 1, t);
          retire(c, 12);
          issue192(A, c, 14);
          d1_mov(W, 2, t); d1_mov(W, 3, t);
          wg_wait<0>();
          asm volatile("bar.sync 4, 256;" ::: "memory");
          float R[18];
          float zero;
          asm volatile("ld.volatile.shared.f32 %0, [%1];" : "=f"(zero) : "r"(sbase + SM_BIAS + 2304) : "memory");
          d1_mma(W, R, zero);
          const int l2 = opaque(lane);
          float2* xch = reinterpret_cast<float2*>(smem + SM_SCR + (warp >> 1) * 1792) + l2;
          float2* xc2 = xch + 192 - l2 + (l2 < 12 ? l2 : 31);
          if (warp & 1) {
#pragma unroll
            for (int q = 0; q < 6; q++) xch[q * 32] = make_float2(R[2 * q], R[2 * q + 1]);
            if (l2 < 12) { xc2[0] = make_float2(R[12], R[13]); xc2[12] = make_float2(R[14], R[15]); }
            if (l2 < 12 && (l2 & 3) == 0) xc2[24 - l2 + (l2 >> 2)] = make_float2(R[16], R[17]);
          } else if ((R[0] + R[4]) + (R[8] + R[12]) + (R[14] + R[16]) == 1.2345e-30f) xch[223 - l2] = make_float2(0.f, 0.f);
          asm volatile("bar.sync 4, 256;" ::: "memory");
          c.release(13);
          issue192(A, c, 15);
          if (!(warp & 1)) {
#pragma unroll
            for (int q = 0; q < 6; q++) { const float2 o = xch[q * 32]; R[2 * q] += o.x; R[2 * q + 1] += o.y; }
            const float2 o0 = xc2[0], o1 = xc2[l2 < 12 ? 12 : 0], o2 = xc2[l2 < 12 ? 24 - l2 + (l2 >> 2) : 0];
            uint4* dkv = &g_kvp[(head * 80 + m) * 32 + l2];
#pragma unroll
            for (int w = 0; w < 3; w++) st_ll(dkv + w * 512, __float_as_uint(R[4 * w]), __float_as_uint(R[4 * w + 1]), __float_as_uint(R[4 * w + 2]), __float_as_uint(R[4 * w + 3]), par);
            st_ll(dkv + 1536, __float_as_uint(R[12] + o0.x), __float_as_uint(R[13] + o0.y), __float_as_uint(R[14] + o1.x), __float_as_uint(R[15] + o1.y), par);
            st_ll(dkv + 2048, __float_as_uint(R[16] + o2.x), __float_as_uint(R[17] + o2.y), 0u, 0u, par);
            hint_signal(&g_f_kvp[head]);
          }
          STAMPW(0, 21);
        } else issue192(A, c, 15);
        if (i == 2) {
          const uint4* hsp = g_hsp + (blockIdx.x * 8 + warp) * 12 * 32 + opaque(lane);
#pragma unroll
          for (int q = 0; q < 12; q++) { const uint4 v = ldcg128(hsp + q * 32); W[4 * q] = v.x; W[4 * q + 1] = v.y; W[4 * q + 2] = v.z; W[4 * q + 3] = v.w; }
          retire(c, 14);
          issue192(A, c, 16);
          wg_sync();
          retire(c, 15);
          issue192(A, c, 17);
#pragma unroll
          for (int q = 0; q < 12; q++) stsm4(HADDR(3, q), make_uint4(W[4 * q], W[4 * q + 1], W[4 * q + 2], W[4 * q + 3]));
        } else {
          retire(c, 14);
          c.wait(bar_ofull + 64, owp);
          issue192(A, c, 16);
          retire(c, 15);
          issue192(A, c, 17);
        }
      }
      STAMPW(0, 2 + 2 * i);
      c.set((!srole && i >= 1) ? 1u : 0u, 1u);
      if ((i & 3) == 0) {
        issue96(B, c, 0, true);
        const int ln = opaque(lane);
        uint2* dst = i == 0 ? g_qkv + (rb * 216 + 36 * f) * 32 + ln : g_s + (rb * 72 + 24 * (f - 5)) * 32 + ln;
        LDS_R(1.f)
        if (i != 0) { r0 = 1.f; r1 = 1.f; }
        PHI_SETUP
        HEAD(A)
#pragma unroll
        for (int k = 1; k < 9; k++) {
          issue96(B, c, k, false);
#pragma unroll
          for (int u = (3 * (k - 1) + 1) / 2; u < (3 * k + 1) / 2; u++) ST_QKV(A, u, dst)
          if (k < 8) retire(c, k - 1);
        }
        if (i == 4) {
          STAMPW(0, 11);
          wg_wait<0>();
          c.release(7); c.release(8);
          fence_regs<48>(B);
          uint2* d2 = g_s + (rb * 72 + 12 * (f - 6)) * 32 + opaque(lane);
#pragma unroll
          for (int q = 0; q < 12; q++) st_ll64(d2 + q * 32, pack_bf16(B[4 * q], B[4 * q + 1]), pack_bf16(B[4 * q + 2], B[4 * q + 3]), par);
          break;
        }
        hint_signal(&g_f_qkv[m * 8 + f]);
      } else {
        issue192(B, c, 0, true);
        const int ln = opaque(lane);
        uint4* dst = i == 1 ? g_hsp + (blockIdx.x * 8 + warp) * 12 * 32 + ln : g_part + ((rb * 8 + f) * 36 + 12 * ((fr + 1) % 3)) * 32 + ln;
        const bool xf = i == 3 && srole && leader;
        const uint32_t bsa = bias_t + (i == 1 ? 0 : 384) * 4;
        LDS_R(GK)
        int s;
        if (i != 3) {
          HEAD(A)
#pragma unroll
          for (int u = 0; u < 12; u++) {
            float2 bs[2];
            lds_bias(bs, bsa + 16 * u * 4);
            issue192(B, c, u + 1);
            EXB(A, u)
            const uint4 h = gelu_group(E);
            asm volatile("{.reg .pred p; setp.eq.s32 p, %6, 1; @p st.global.v4.u32 [%0], {%2,%3,%4,%5}; @!p stmatrix.sync.aligned.m8n8.x4.shared.b16 [%1], {%2,%3,%4,%5};}"
                         ::"l"(dst + u * 32), "r"(HADDR(6, u)), "r"(h.x), "r"(h.y), "r"(h.z), "r"(h.w), "r"(i) : "memory");
            if (u == 3 || u == 9) wg_sync();
            retire(c, u);
          }
          s = 13;
        } else {
          HEAD(A)
#pragma unroll
          for (int u = 0; u < 6; u++) {
            issue192(B, c, u + 1);
            part_groups<0, 2>(&A[16 * u], dst + 2 * u * 32, par);
            retire(c, u);
            if ((u & 1) && xf) mbar_arrive(bar_xfree + 4 * u - 4);
          }
          s = 7;
        }
        if (i == 3 && !srole) {
          const int c2 = (fr + 2) % 3, v0 = 12 * c2 + (f < 3 ? 0 : 6), fo = f < 3 ? f + 3 : f - 3;
          const int l2 = opaque(lane);
          const uint4* pb = g_part + (rb * 8 * 36 + v0) * 32 + l2;
          uint4 p[12];
          uint32_t S[24];
#pragma unroll
          for (int q = 0; q < 24; q++) S[q] = 0u;
          auto ldp = [&](const uint4* a0, const uint4* a1) {
#pragma unroll
            for (int q = 0; q < 6; q++) { p[q] = ld_ll(a0 + q * 32); p[6 + q] = ld_ll(a1 + q * 32); }
          };
          auto badp = [&]() {
            uint32_t bad = 0;
#pragma unroll
            for (int q = 0; q < 12; q++) ll_chk(bad, p[q].x, p[q].z, par);
            return __any_sync(0xffffffffu, bad & 1);
          };
#pragma unroll 1
          for (int w = 0; w < 3; w++) {
            const uint4* a0 = pb + (w == 0 ? c2 : (w == 1 ? 6 : (fr + 1) % 3)) * 36 * 32;
            const uint4* a1 = a0 + (w == 1 ? 1 : 3) * 36 * 32;
            issue192(B, c, 7 + 3 * w);
            ldp(a0, a1);
            retire(c, 6 + 3 * w);
            issue192(B, c, 8 + 3 * w);
            retire(c, 7 + 3 * w);
            issue192(B, c, 9 + 3 * w);
            int tries = 0;
#pragma unroll 1
            while (badp() && ++tries < (1 << 20)) ldp(a0, a1);
#pragma unroll
            for (int q = 0; q < 24; q++) S[q] = hadd2(S[q], hadd2(reinterpret_cast<const uint32_t*>(p)[q], reinterpret_cast<const uint32_t*>(p)[24 + q]));
            retire(c, 8 + 3 * w);
          }
          uint4 xx[6];
          uint32_t bb[12];
          int ro[6];
          issue192(B, c, 16);
#pragma unroll
          for (int j = 0; j < 6; j++) {
            const int k = l2 + 32 * j, r = (k * 171) >> 11;
            ro[j] = (rb * 16 + r) * D_ + 16 * v0 + (k - 12 * r) * 8;
            xx[j] = __ldg(reinterpret_cast<const uint4*>(P.x + ro[j]));
          }
#pragma unroll
          for (int j = 0; j < 12; j++) bb[j] = __ldg(reinterpret_cast<const uint32_t*>(P.b2 + 16 * v0 + 8 * j + 2 * (l2 & 3)));
          retire(c, 15);
          issue192(B, c, 17);
          retire(c, 16);
          STAMPW(0, 9);
          wg_wait<0>();
          c.release(17);
          fence_regs<96>(B);
          uint4* snd = g_part + ((rb * 8 + f) * 36 + 12 * c2 + (f < 3 ? 6 : 0)) * 32 + l2;
          if (f < 3) part_groups<0, 6>(B + 48, snd, par);
          else {
            part_groups<0, 6>(B, snd, par);
#pragma unroll
            for (int q = 0; q < 48; q++) B[q] = B[48 + q];
          }
          asm volatile("bar.sync 4, 256;" ::: "memory");
          STAMPW(0, 12);
#pragma unroll
          for (int q = 0; q < 24; q++) {
            B[2 * q] = fmaf(B[2 * q] + bf_lo(S[q]), 0.25f / GK, 0.5f * bf_lo(bb[q >> 1])); B[2 * q + 1] = fmaf(B[2 * q + 1] + bf_hi(S[q]), 0.25f / GK, 0.5f * bf_hi(bb[q >> 1]));
          }
          const uint2* sp = g_s + (rb * 72 + 2 * v0) * 32 + l2;
          int tries = 0;
#pragma unroll 1
          while (++tries < (1 << 20)) {
            const uint2 u0 = ld_ll64(pb + (fo * 36 + 5) * 32), u1 = ld_ll64(sp + 11 * 32);
            if (!__any_sync(0xffffffffu, ((u0.x ^ par) | (u1.x ^ par)) & 1)) break;
            __nanosleep(40);
          }
          tries = 0;
#pragma unroll 1
          do {
#pragma unroll
            for (int q = 0; q < 6; q++) {
              p[q] = ld_ll(pb + (fo * 36 + q) * 32);
              const uint2 s0 = ld_ll64(sp + 2 * q * 32), s1 = ld_ll64(sp + (2 * q + 1) * 32);
              p[6 + q] = make_uint4(s0.x, s0.y, s1.x, s1.y);
            }
          } while (badp() && ++tries < (1 << 20));
          STAMPW(0, 14);
          const uint32_t tb = sbase + SM_A + warp * 3328;
#pragma unroll
          for (int v = 0; v < 6; v++) {
            uint32_t o[4];
#pragma unroll
            for (int k = 0; k < 4; k++) {
              const int q = 4 * v + k;
              const uint32_t w = reinterpret_cast<const uint32_t*>(p)[q];
              const uint32_t gt = pack_bf16(silu_h(fmaf(bf_lo(w), 0.25f / GK, B[2 * q])), silu_h(fmaf(bf_hi(w), 0.25f / GK, B[2 * q + 1])));
              o[k] = hfma2(reinterpret_cast<const uint32_t*>(p)[24 + q], gt, 0x80008000u);
            }
            stsm4(tb + (l2 & 15) * 208 + (l2 >> 4) * 16 + v * 32, make_uint4(o[0], o[1], o[2], o[3]));
          }
          __syncwarp();
#pragma unroll
          for (int j = 0; j < 6; j++) {
            const int k = l2 + 32 * j, r = (k * 171) >> 11;
            uint4 o;
            asm volatile("ld.shared.v4.u32 {%0,%1,%2,%3}, [%4];" : "=r"(o.x), "=r"(o.y), "=r"(o.z), "=r"(o.w) : "r"(tb + r * 208 + (k - 12 * r) * 16) : "memory");
            *reinterpret_cast<uint4*>(P.out + ro[j]) = make_uint4(hadd2(o.x, xx[j].x), hadd2(o.y, xx[j].y), hadd2(o.z, xx[j].z), hadd2(o.w, xx[j].w));
          }
          break;
        }
        plain192(B, c, s, 17, [&](int k) { if (k == 15) wg_sync(); }, [&](int k) { if (!(k & 1) && xf) mbar_arrive(bar_xfree + 4 * k - 8); });
        issue192(B, c, 17);
      }
      STAMPW(0, 3 + 2 * i);
    }
    STAMPW(0, 15);
    cluster_arrive_relaxed();
    cluster_wait();
    STAMPW(0, 16);
    if (tid == 0) g_epoch[blockIdx.x] = ep;
  }
}

typedef CUresult (*EncFn)(CUtensorMap*, CUtensorMapDataType, cuuint32_t, void*, const cuuint64_t*, const cuuint64_t*, const cuuint32_t*, const cuuint32_t*,
                          CUtensorMapInterleave, CUtensorMapSwizzle, CUtensorMapL2promotion, CUtensorMapFloatOOBfill);

void make_map(EncFn enc, CUtensorMap* tm, const void* ptr, int rows, int cols, int box_rows, int mode = 0) {
  cuuint64_t gd[2] = {(cuuint64_t)cols, (cuuint64_t)rows};
  cuuint64_t gs[1] = {(cuuint64_t)cols * 2};
  cuuint32_t bx[2] = {mode == 1 ? 32u : (mode == 2 ? 72u : 64u), (cuuint32_t)box_rows};
  cuuint32_t es[2] = {1, 1};
  enc(tm, CU_TENSOR_MAP_DATA_TYPE_BFLOAT16, 2, const_cast<void*>(ptr), gd, gs, bx, es, CU_TENSOR_MAP_INTERLEAVE_NONE, mode == 1 ? CU_TENSOR_MAP_SWIZZLE_64B : (mode == 2 ? CU_TENSOR_MAP_SWIZZLE_NONE : CU_TENSOR_MAP_SWIZZLE_128B),
      CU_TENSOR_MAP_L2_PROMOTION_L2_256B, CU_TENSOR_MAP_FLOAT_OOB_FILL_NONE);
}

}

extern "C" void kernel_launch(void* const* d_in, const int* in_sizes, int n_in, void* d_out, int out_size) {
  (void)in_sizes; (void)n_in; (void)out_size;
  static EncFn enc = nullptr;
  static void *a_ptr = nullptr, *m_ptr = nullptr;
  if (!enc) {
    void* fn = nullptr; cudaDriverEntryPointQueryResult q;
    cudaGetDriverEntryPoint("cuTensorMapEncodeTiled", &fn, cudaEnableDefault, &q);
    enc = (EncFn)fn;
    cudaFuncSetAttribute(fused_kernel, cudaFuncAttributeMaxDynamicSharedMemorySize, SMEM_BYTES);
    cudaGetSymbolAddress(&a_ptr, g_a);
    cudaGetSymbolAddress(&m_ptr, g_m);
  }
  Params P;
  P.x = (const __nv_bfloat16*)d_in[0];
  P.wqkv = (const __nv_bfloat16*)d_in[1];
  P.wo = (const __nv_bfloat16*)d_in[2];
  P.w1 = (const __nv_bfloat16*)d_in[4];
  P.b1 = (const __nv_bfloat16*)d_in[5];
  P.w2 = (const __nv_bfloat16*)d_in[6];
  P.b2 = (const __nv_bfloat16*)d_in[7];
  P.out = (__nv_bfloat16*)d_out;
  make_map(enc, &P.tm_wqkv, P.wqkv, D_, Q3_, 32);
  make_map(enc, &P.tm_w1, P.w1, D_, F_, 32);
  make_map(enc, &P.tm_w2, P.w2, F_, D_, 32);
  make_map(enc, &P.tm_m, m_ptr, D_, D_, 32);
  make_map(enc, &P.tm_wqkv64, P.wqkv, D_, Q3_, 64, 1);
  make_map(enc, &P.tm_m64, m_ptr, D_, D_, 64, 1);
  make_map(enc, &P.tm_a, a_ptr, S_, D_, 128);
  make_map(enc, &P.tm_ast, a_ptr, S_, D_, 16, 2);
  fused_kernel<<<NCTAS, NTHREADS, SMEM_BYTES, cudaStreamPerThread>>>(P);
}
```

```cpp
#include <cuda_runtime.h>
#include <cuda.h>
#include <cuda_bf16.h>
#include <stdint.h>

namespace {

constexpr int S_ = 2048, D_ = 576, F_ = 4608, Q3_ = 1728;
constexpr int NSTAGE = 6, STAGE_BYTES = 12288;
constexpr int SM_A = 0, SM_B = 147456, SM_BIAS = SM_B + NSTAGE * STAGE_BYTES, SM_RSTD = SM_BIAS + 2304 + 128, SM_SCR = SM_RSTD + 512, SM_BAR = SM_SCR + 7168;
constexpr int SMEM_BYTES = SM_BAR + 320;
constexpr int NTHREADS = 384;
constexpr int NCTAS = 132;

__device__ uint2 g_qkv[(128 * 216 + 2) * 32];
__device__ __align__(1024) __nv_bfloat16 g_a[S_ * D_];
__device__ __align__(1024) __nv_bfloat16 g_m[D_ * D_];
__device__ uint4 g_kvp[32 * 5 * 16 * 32];
__device__ uint4 g_z[32 * 2 * 4];
__device__ uint4 g_part[128 * 8 * 36 * 32];
__device__ uint2 g_s[128 * 72 * 32];
__device__ uint4 g_hsp[128 * 12 * 256];
__device__ uint32_t g_f_qkv[16 * 8];
__device__ uint32_t g_f_kvp[32];
__device__ uint32_t g_f_z[32];
__device__ uint32_t g_f_a[16];
__device__ uint32_t g_f_m[1];
__device__ uint2 g_stat[S_];
__device__ uint32_t g_epoch[NCTAS];

#define STAMP(i)
#define STAMPW(w, i)
#define WSTAMP(i)
__device__ __forceinline__ uint32_t smem_u32(const void* p) { return (uint32_t)__cvta_generic_to_shared(p); }
__device__ __forceinline__ void mbar_init(uint32_t a, int c) { asm volatile("mbarrier.init.shared::cta.b64 [%0], %1;" ::"r"(a), "r"(c)); }
__device__ __forceinline__ void mbar_expect(uint32_t a, uint32_t b) { asm volatile("mbarrier.arrive.expect_tx.shared::cta.b64 _, [%0], %1;" ::"r"(a), "r"(b) : "memory"); }
__device__ __forceinline__ void mbar_arrive(uint32_t a) { asm volatile("mbarrier.arrive.shared::cta.b64 _, [%0];" ::"r"(a) : "memory"); }
__device__ __forceinline__ void mbar_arrive_cl(uint32_t a) { asm volatile("mbarrier.arrive.shared::cluster.b64 _, [%0];" ::"r"(a) : "memory"); }
__device__ __forceinline__ uint32_t mapa(uint32_t a, uint32_t cta) { uint32_t r; asm volatile("mapa.shared::cluster.u32 %0, %1, %2;" : "=r"(r) : "r"(a), "r"(cta)); return r; }
__device__ __forceinline__ void mbar_wait(uint32_t a, uint32_t ph) {
  uint32_t ok; int it = 0;
#pragma unroll 1
  do {
    asm volatile("{.reg .pred p; mbarrier.try_wait.parity.shared::cta.b64 p, [%1], %2; selp.u32 %0,1,0,p;}" : "=r"(ok) : "r"(a), "r"(ph) : "memory");
  } while (!ok && ++it < (1 << 18));
}
__device__ __forceinline__ void tma2d(uint32_t dst, const CUtensorMap* m, int c0, int c1, uint32_t bar) {
  asm volatile("cp.async.bulk.tensor.2d.shared::cluster.global.mbarrier::complete_tx::bytes [%0], [%1, {%3,%4}], [%2];" ::"r"(dst), "l"(m), "r"(bar), "r"(c0), "r"(c1) : "memory");
}
__device__ __forceinline__ void tma3d_mc_elect(uint32_t dst, const CUtensorMap* m, int c0, int c1, uint32_t bar) {
  asm volatile("{.reg .pred p; elect.sync _|p, 0xffffffff; @p mbarrier.arrive.expect_tx.shared::cta.b64 _, [%2], 12288; "
               "@p cp.async.bulk.tensor.3d.shared::cluster.global.mbarrier::complete_tx::bytes.multicast::cluster [%0], [%1, {%3,%4,%6}], [%2], %5;}"
               ::"r"(dst), "l"(m), "r"(bar), "r"(c0), "r"(c1), "h"((uint16_t)3), "r"(0) : "memory");
}
__device__ __forceinline__ void cluster_arrive_relaxed() { asm volatile("barrier.cluster.arrive.relaxed.aligned;" ::: "memory"); }
__device__ __forceinline__ void cluster_wait() { asm volatile("barrier.cluster.wait.acquire.aligned;" ::: "memory"); }
__device__ __forceinline__ void wg_fence() { asm volatile("wgmma.fence.sync.aligned;" ::: "memory"); }
__device__ __forceinline__ void wg_commit() { asm volatile("wgmma.commit_group.sync.aligned;" ::: "memory"); }
template <int n> __device__ __forceinline__ void wg_wait() { asm volatile("wgmma.wait_group.sync.aligned %0;" ::"n"(n) : "memory"); }
__device__ __forceinline__ uint32_t ld_acquire(const uint32_t* p) { uint32_t v; asm volatile("ld.acquire.gpu.global.u32 %0, [%1];" : "=r"(v) : "l"(p) : "memory"); return v; }
__device__ __forceinline__ void flag_wait(const uint32_t* p, uint32_t target) {
  int it = 0;
#pragma unroll 1
  while ((int)(ld_acquire(p) - target) < 0 && ++it < (1 << 20)) __nanosleep(300);
}
__device__ __forceinline__ void hint_signal(uint32_t* p) {
  if ((threadIdx.x & 31) == 0) asm volatile("red.relaxed.gpu.global.add.u32 [%0], 1;" ::"l"(p) : "memory");
}
__device__ __forceinline__ void hint_wait(const uint32_t* p, uint32_t target, uint32_t ns = 400) {
  int it = 0; uint32_t v;
#pragma unroll 1
  do { asm volatile("ld.relaxed.gpu.global.u32 %0, [%1];" : "=r"(v) : "l"(p) : "memory"); if ((int)(v - target) >= 0) break; __nanosleep(ns); } while (++it < (1 << 20));
}
__device__ __forceinline__ uint32_t tag(uint32_t x, uint32_t par) { uint32_t r; asm("lop3.b32 %0, %1, 0xfffffffe, %2, 0xea;" : "=r"(r) : "r"(x), "r"(par)); return r; }
__device__ __forceinline__ void st_ll(uint4* p, uint32_t x, uint32_t y, uint32_t z, uint32_t w, uint32_t par) {
  asm volatile("{.reg .b64 a, b; mov.b64 a, {%1,%2}; mov.b64 b, {%3,%4}; st.relaxed.gpu.global.v2.b64 [%0], {a, b};}"
               ::"l"(p), "r"(tag(x, par)), "r"(y), "r"(tag(z, par)), "r"(w) : "memory");
}
__device__ __forceinline__ uint4 ld_ll(const uint4* p) {
  uint4 v;
  asm volatile("{.reg .b64 a, b; ld.relaxed.gpu.global.v2.b64 {a, b}, [%4]; mov.b64 {%0,%1}, a; mov.b64 {%2,%3}, b;}"
               : "=r"(v.x), "=r"(v.y), "=r"(v.z), "=r"(v.w) : "l"(p) : "memory");
  return v;
}
__device__ __forceinline__ void st_ll64(uint2* p, uint32_t x, uint32_t y, uint32_t par) {
  asm volatile("{.reg .b64 a; mov.b64 a, {%1,%2}; st.relaxed.gpu.global.b64 [%0], a;}" ::"l"(p), "r"(tag(x, par)), "r"(y) : "memory");
}
__device__ __forceinline__ uint2 ld_ca64(const void* p) {
  uint2 v;
  asm volatile("{.reg .b64 a; ld.global.ca.b64 a, [%2]; mov.b64 {%0,%1}, a;}" : "=r"(v.x), "=r"(v.y) : "l"(p) : "memory");
  return v;
}
__device__ __forceinline__ uint2 ld_ll64(const void* p) {
  uint2 v;
  asm volatile("{.reg .b64 a; ld.relaxed.gpu.global.b64 a, [%2]; mov.b64 {%0,%1}, a;}" : "=r"(v.x), "=r"(v.y) : "l"(p) : "memory");
  return v;
}
__device__ __forceinline__ void ll_chk(uint32_t& bad, uint32_t a, uint32_t b, uint32_t par) {
  uint32_t u; asm("lop3.b32 %0, %1, %2, %3, 0x7e;" : "=r"(u) : "r"(a), "r"(b), "r"(par));
  asm("or.b32 %0, %0, %1;" : "+r"(bad) : "r"(u));
}
__device__ __forceinline__ uint32_t hadd2(uint32_t a, uint32_t b) { uint32_t d; asm("add.rn.bf16x2 %0, %1, %2;" : "=r"(d) : "r"(a), "r"(b)); return d; }
__device__ __forceinline__ uint32_t hfma2(uint32_t a, uint32_t b, uint32_t c) { uint32_t d; asm("fma.rn.bf16x2 %0, %1, %2, %3;" : "=r"(d) : "r"(a), "r"(b), "r"(c)); return d; }
__device__ __forceinline__ uint32_t pack_bf16(float lo, float hi) { uint32_t r; asm("cvt.rn.bf16x2.f32 %0, %1, %2;" : "=r"(r) : "f"(hi), "f"(lo)); return r; }
__device__ __forceinline__ float bf_lo(uint32_t v) { return __uint_as_float(v << 16); }
__device__ __forceinline__ float bf_hi(uint32_t v) { return __uint_as_float(v & 0xffff0000u); }
__device__ __forceinline__ uint32_t movmat(uint32_t a) { uint32_t d; asm volatile("movmatrix.sync.aligned.m8n8.trans.b16 %0, %1;" : "=r"(d) : "r"(a)); return d; }
__device__ __forceinline__ void mma16816(float* c, uint32_t a0, uint32_t a1, uint32_t a2, uint32_t a3, uint32_t b0, uint32_t b1) {
  asm volatile("mma.sync.aligned.m16n8k16.row.col.f32.bf16.bf16.f32 {%0,%1,%2,%3}, {%4,%5,%6,%7}, {%8,%9}, {%0,%1,%2,%3};"
               : "+f"(c[0]), "+f"(c[1]), "+f"(c[2]), "+f"(c[3]) : "r"(a0), "r"(a1), "r"(a2), "r"(a3), "r"(b0), "r"(b1));
}
__device__ __forceinline__ uint4 ldcg128(const void* p) { uint4 v; asm volatile("ld.global.cg.v4.u32 {%0,%1,%2,%3}, [%4];" : "=r"(v.x), "=r"(v.y), "=r"(v.z), "=r"(v.w) : "l"(p) : "memory"); return v; }

template <int N> __device__ __forceinline__ void wgmma_ss(float* d, uint32_t alo, int aimm, uint32_t blo, int bimm, uint32_t bhi, int sc);
template <> __device__ __forceinline__ void wgmma_ss<96>(float* d, uint32_t alo, int aimm, uint32_t blo, int bimm, uint32_t bhi, int sc) {
  asm volatile("{.reg .pred p; .reg .b32 x, y; .reg .b64 da, db; setp.ne.b32 p, %53, 0; add.u32 x, %48, %49; add.u32 y, %50, %51; mov.b64 da, {x, 0x40000040}; mov.b64 db, {y, %52}; "
               "wgmma.mma_async.sync.aligned.m64n96k16.f32.bf16.bf16 {%0, %1, %2, %3, %4, %5, %6, %7, %8, %9, %10, %11, %12, %13, %14, %15, %16, %17, %18, %19, %20, %21, %22, %23, %24, %25, %26, %27, %28, %29, %30, %31, %32, %33, %34, %35, %36, %37, %38, %39, %40, %41, %42, %43, %44, %45, %46, %47}, da, db, p, 1, 1, 0, 1;}"
   : "+f"(d[0]), "+f"(d[1]), "+f"(d[2]), "+f"(d[3]), "+f"(d[4]), "+f"(d[5]), "+f"(d[6]), "+f"(d[7]), "+f"(d[8]), "+f"(d[9]), "+f"(d[10]), "+f"(d[11]), "+f"(d[12]), "+f"(d[13]), "+f"(d[14]), "+f"(d[15]), "+f"(d[16]), "+f"(d[17]), "+f"(d[18]), "+f"(d[19]), "+f"(d[20]), "+f"(d[21]), "+f"(d[22]), "+f"(d[23]), "+f"(d[24]), "+f"(d[25]), "+f"(d[26]), "+f"(d[27]), "+f"(d[28]), "+f"(d[29]), "+f"(d[30]), "+f"(d[31]), "+f"(d[32]), "+f"(d[33]), "+f"(d[34]), "+f"(d[35]), "+f"(d[36]), "+f"(d[37]), "+f"(d[38]), "+f"(d[39]), "+f"(d[40]), "+f"(d[41]), "+f"(d[42]), "+f"(d[43]), "+f"(d[44]), "+f"(d[45]), "+f"(d[46]), "+f"(d[47]) : "r"(alo), "r"(aimm), "r"(blo), "r"(bimm), "r"(bhi), "r"(sc));
}
template <> __device__ __forceinline__ void wgmma_ss<192>(float* d, uint32_t alo, int aimm, uint32_t blo, int bimm, uint32_t bhi, int sc) {
  asm volatile("{.reg .pred p; .reg .b32 x, y; .reg .b64 da, db; setp.ne.b32 p, %101, 0; add.u32 x, %96, %97; add.u32 y, %98, %99; mov.b64 da, {x, 0x40000040}; mov.b64 db, {y, %100}; "
               "wgmma.mma_async.sync.aligned.m64n192k16.f32.bf16.bf16 {%0, %1, %2, %3, %4, %5, %6, %7, %8, %9, %10, %11, %12, %13, %14, %15, %16, %17, %18, %19, %20, %21, %22, %23, %24, %25, %26, %27, %28, %29, %30, %31, %32, %33, %34, %35, %36, %37, %38, %39, %40, %41, %42, %43, %44, %45, %46, %47, %48, %49, %50, %51, %52, %53, %54, %55, %56, %57, %58, %59, %60, %61, %62, %63, %64, %65, %66, %67, %68, %69, %70, %71, %72, %73, %74, %75, %76, %77, %78, %79, %80, %81, %82, %83, %84, %85, %86, %87, %88, %89, %90, %91, %92, %93, %94, %95}, da, db, p, 1, 1, 0, 1;}"
   : "+f"(d[0]), "+f"(d[1]), "+f"(d[2]), "+f"(d[3]), "+f"(d[4]), "+f"(d[5]), "+f"(d[6]), "+f"(d[7]), "+f"(d[8]), "+f"(d[9]), "+f"(d[10]), "+f"(d[11]), "+f"(d[12]), "+f"(d[13]), "+f"(d[14]), "+f"(d[15]), "+f"(d[16]), "+f"(d[17]), "+f"(d[18]), "+f"(d[19]), "+f"(d[20]), "+f"(d[21]), "+f"(d[22]), "+f"(d[23]), "+f"(d[24]), "+f"(d[25]), "+f"(d[26]), "+f"(d[27]), "+f"(d[28]), "+f"(d[29]), "+f"(d[30]), "+f"(d[31]), "+f"(d[32]), "+f"(d[33]), "+f"(d[34]), "+f"(d[35]), "+f"(d[36]), "+f"(d[37]), "+f"(d[38]), "+f"(d[39]), "+f"(d[40]), "+f"(d[41]), "+f"(d[42]), "+f"(d[43]), "+f"(d[44]), "+f"(d[45]), "+f"(d[46]), "+f"(d[47]), "+f"(d[48]), "+f"(d[49]), "+f"(d[50]), "+f"(d[51]), "+f"(d[52]), "+f"(d[53]), "+f"(d[54]), "+f"(d[55]), "+f"(d[56]), "+f"(d[57]), "+f"(d[58]), "+f"(d[59]), "+f"(d[60]), "+f"(d[61]), "+f"(d[62]), "+f"(d[63]), "+f"(d[64]), "+f"(d[65]), "+f"(d[66]), "+f"(d[67]), "+f"(d[68]), "+f"(d[69]), "+f"(d[70]), "+f"(d[71]), "+f"(d[72]), "+f"(d[73]), "+f"(d[74]), "+f"(d[75]), "+f"(d[76]), "+f"(d[77]), "+f"(d[78]), "+f"(d[79]), "+f"(d[80]), "+f"(d[81]), "+f"(d[82]), "+f"(d[83]), "+f"(d[84]), "+f"(d[85]), "+f"(d[86]), "+f"(d[87]), "+f"(d[88]), "+f"(d[89]), "+f"(d[90]), "+f"(d[91]), "+f"(d[92]), "+f"(d[93]), "+f"(d[94]), "+f"(d[95]) : "r"(alo), "r"(aimm), "r"(blo), "r"(bimm), "r"(bhi), "r"(sc));
}

constexpr uint32_t DESC_HI = (1024u >> 4) | (1u << 30);
constexpr uint32_t DESC_HI64 = (512u >> 4) | (2u << 30);
template <int n> __device__ __forceinline__ void fence_regs(float* a) {
#pragma unroll
  for (int i = 0; i < n; i++) asm volatile("" : "+f"(a[i])::"memory");
}

struct Ctx {
  uint32_t full, emb;
  bool sig;
  uint32_t o0, o1;
  uint32_t p0, p1;
  uint32_t dB, dA;
  int budget;
  __device__ __forceinline__ static int m6(int s) { return s >= 12 ? s - 12 : (s >= 6 ? s - 6 : s); }
  __device__ __forceinline__ uint32_t hb(int s) const { return m6(s) < 3 ? o0 : o1; }
  __device__ __forceinline__ static int m3(int s) { return m6(s) < 3 ? m6(s) : m6(s) - 3; }
  __device__ __forceinline__ void release(int s) { if (sig) mbar_arrive_cl(emb + 8 * hb(s) + 8 * m3(s)); }
  __device__ __forceinline__ void wait(uint32_t a, uint32_t ph) {
    uint32_t ok;
#pragma unroll 1
    do {
      asm volatile("{.reg .pred p; mbarrier.try_wait.parity.shared::cta.b64 p, [%1], %2; selp.u32 %0,1,0,p;}" : "=r"(ok) : "r"(a), "r"(ph) : "memory");
      budget--;
    } while ((ok == 0) & (budget > 0));
  }
  __device__ __forceinline__ void wait_full(int s) {
    const uint32_t a = full + 8 * hb(s) + 8 * m3(s), ph = (m6(s) < 3 ? p0 : p1) ^ ((s >= 6 && s < 12) ? 1u : 0u);
    wait(a, ph);
    wg_fence();
  }
  __device__ __forceinline__ void set(uint32_t sw, uint32_t second) { o0 = sw ? 3 : 0; o1 = 3 - o0; p0 = second; p1 = second ^ sw; }
};

__device__ __forceinline__ void issue192(float* acc, Ctx& c, int s, bool first = false) {
  c.wait_full(s);
  const uint32_t db = c.dB + c.hb(s) * (STAGE_BYTES >> 4);
  wgmma_ss<192>(acc, c.dA, (s >> 1) * 1024 + (s & 1) * 4, db, Ctx::m3(s) * (STAGE_BYTES >> 4), DESC_HI, first ? 0 : 1);
  wgmma_ss<192>(acc, c.dA, (s >> 1) * 1024 + (s & 1) * 4 + 2, db, Ctx::m3(s) * (STAGE_BYTES >> 4) + 384, DESC_HI, 1);
  wg_commit();
}
template <class Pre, class Post>
__device__ __forceinline__ void plain192(float* acc, Ctx& c, int s, int e, Pre pre, Post post) {
  uint32_t st = c.hb(s) + Ctx::m3(s), pst = c.hb(s - 1) + Ctx::m3(s - 1), ph = (Ctx::m6(s) < 3 ? c.p0 : c.p1) ^ ((s >= 6 && s < 12) ? 1u : 0u);
  uint32_t da = c.dA + (s >> 1) * 1024 + (s & 1) * 4;
#pragma unroll 1
  for (; s < e; s++) {
    pre(s);
    c.wait(c.full + 8 * st, ph);
    wg_fence();
    const uint32_t db = c.dB + st * (STAGE_BYTES >> 4);
    wgmma_ss<192>(acc, da, 0, db, 0, DESC_HI, 1);
    wgmma_ss<192>(acc, da, 2, db, 384, DESC_HI, 1);
    wg_commit();
    const uint32_t rel = c.emb + 8 * pst;
    pst = st;
    st = st == 5 ? 0 : st + 1;
    ph ^= st == 0 ? 1u : 0u;
    da += (s & 1) ? 1020 : 4;
    wg_wait<1>();
    if (c.sig) mbar_arrive_cl(rel);
    post(s);
  }
}
__device__ __forceinline__ void issue96(float* acc, Ctx& c, int k, bool first) {
  c.wait_full(k);
  const uint32_t db = c.dB + c.hb(k) * (STAGE_BYTES >> 4);
  if (first) { wgmma_ss<192>(acc, c.dA, k * 1024, db, Ctx::m3(k) * (STAGE_BYTES >> 4), DESC_HI64, 0); wg_fence(); }
#pragma unroll
  for (int kk = first ? 1 : 0; kk < 4; kk++) wgmma_ss<96>(acc, c.dA, k * 1024 + 2 * kk, db, Ctx::m3(k) * (STAGE_BYTES >> 4) + 384 * (kk >> 1) + 64 * (kk & 1), DESC_HI64, 1);
  wg_commit();
}
__device__ __forceinline__ void retire(Ctx& c, int prev) {
  wg_wait<1>();
  c.release(prev);
}

constexpr float GK = 0.32920349f;
__device__ __forceinline__ uint32_t gelu_pair(uint32_t y) {
  uint32_t u, th;
  asm("mul.rn.bf16x2 %0, %1, %2;" : "=r"(u) : "r"(hfma2(y, y, 0x401b401bu)), "r"(y));
  asm("tanh.approx.bf16x2 %0, %1;" : "=r"(th) : "r"(u));
  return hfma2(y, th, y);
}
__device__ __forceinline__ uint4 gelu_group(const uint32_t* a) { return make_uint4(gelu_pair(a[0]), gelu_pair(a[1]), gelu_pair(a[2]), gelu_pair(a[3])); }
__device__ __forceinline__ void lds_bias(float2* b, uint32_t addr) {
#pragma unroll
  for (int j = 0; j < 2; j++) asm volatile("ld.shared.v2.f32 {%0,%1}, [%2];" : "=f"(b[j].x), "=f"(b[j].y) : "r"(addr + 32 * j));
}
__device__ __forceinline__ int opaque(int v) { asm volatile("" : "+r"(v)); return v; }
__device__ __forceinline__ void stsm4(uint32_t addr, uint4 r) {
  asm volatile("stmatrix.sync.aligned.m8n8.x4.shared.b16 [%0], {%1,%2,%3,%4};" ::"r"(addr), "r"(r.x), "r"(r.y), "r"(r.z), "r"(r.w) : "memory");
}
__device__ __forceinline__ float ex2f(float x) { float r; asm("ex2.approx.ftz.f32 %0, %1;" : "=f"(r) : "f"(x)); return r; }
__device__ __forceinline__ uint32_t phi_pack(uint32_t tp, float a0, float a1, uint32_t c1, uint32_t c2) {
  uint32_t x, y;
  asm("max.bf16x2 %0, %1, %2;" : "=r"(x) : "r"(tp), "r"(c1));
  asm("min.bf16x2 %0, %1, %2;" : "=r"(y) : "r"(pack_bf16(ex2f(a0), ex2f(a1))), "r"(c2));
  return hadd2(x, y);
}
template <int q0, int q1>
__device__ __forceinline__ void part_groups(const float* a, uint4* p, uint32_t par) {
#pragma unroll
  for (int q = q0; q < q1; q++)
    st_ll(p + q * 32, pack_bf16(a[8 * q], a[8 * q + 1]), pack_bf16(a[8 * q + 2], a[8 * q + 3]), pack_bf16(a[8 * q + 4], a[8 * q + 5]), pack_bf16(a[8 * q + 6], a[8 * q + 7]), par);
}
__device__ __forceinline__ float rcpf(float x) { float r; asm("rcp.approx.ftz.f32 %0, %1;" : "=f"(r) : "f"(x)); return r; }
__device__ __forceinline__ float silu_h(float h) { float r; asm("tanh.approx.f32 %0, %1;" : "=f"(r) : "f"(h)); return fmaf(h, r, h); }
__device__ __forceinline__ int pairoff(int p, int g) { return (p >> 2) * 32 + g * 4 + (p & 3); }
template <bool STRONG, int J0, int J1> __device__ __forceinline__ void d1_load(uint32_t* W, int rb0, int head, int ln) {
  const uint2* qf = g_qkv + rb0 * 216 * 32 + pairoff(288 + head * 9 + (ln & 3), ln >> 2);
#pragma unroll
  for (int b = 0; b < 3; b++) {
#pragma unroll
    for (int j = J0; j < J1; j++) {
      const uint2* p = qf + j * 216 * 32 + 32 * b;
      const uint2 kk = STRONG ? ld_ll64(p) : ld_ca64(p), vv = STRONG ? ld_ll64(p + 72 * 32) : ld_ca64(p + 72 * 32);
      W[6 * j + 2 * b] = kk.x; W[6 * j + 2 * b + 1] = kk.y; W[24 + 6 * j + 2 * b] = vv.x; W[24 + 6 * j + 2 * b + 1] = vv.y;
    }
  }
}
__device__ __forceinline__ bool d1_bad(const uint32_t* W, int t, uint32_t par) {
  uint32_t bad = 0, bad2 = 0;
#pragma unroll
  for (int q = 0; q < 12; q++) ll_chk((q % 3) != 2 ? bad : bad2, W[2 * q], W[24 + 2 * q], par);
  return __any_sync(0xffffffffu, (bad | (t == 0 ? bad2 : 0u)) & 1);
}
__device__ __forceinline__ void d1_mov(uint32_t* W, int j, int t) {
  if (t != 0) { W[6 * j + 4] = W[6 * j + 5] = 0u; W[24 + 6 * j + 4] = W[24 + 6 * j + 5] = (t == 1 ? 0x00003f80u : 0u); }
#pragma unroll
  for (int q = 0; q < 6; q++) { W[6 * j + q] = movmat(W[6 * j + q]); W[24 + 6 * j + q] = movmat(W[24 + 6 * j + q]); }
}
__device__ __forceinline__ void d1_mma(const uint32_t* W, float* R, float zero) {
  float c1[3][4];
#pragma unroll
  for (int j = 0; j < 12; j++) { R[j] = (j & 3) ? 0.f : zero; c1[j >> 2][j & 3] = (j & 3) ? 0.f : zero; }
#pragma unroll
  for (int ks = 0; ks < 4; ks++)
#pragma unroll
    for (int j = 0; j < 3; j++) {
      mma16816(R + 4 * j, W[24 + 6 * ks], W[24 + 6 * ks + 2], W[24 + 6 * ks + 1], W[24 + 6 * ks + 3], W[6 * ks + 2 * j], W[6 * ks + 2 * j + 1]);
      mma16816(c1[j], W[24 + 6 * ks + 4], 0u, W[24 + 6 * ks + 5], 0u, W[6 * ks + 2 * j], W[6 * ks + 2 * j + 1]);
    }
#pragma unroll
  for (int j = 0; j < 3; j++) { R[12 + 2 * j] = c1[j][0]; R[13 + 2 * j] = c1[j][1]; }
}
__device__ __forceinline__ bool kv_valid(int w, int ln) { return (w < 3 || ln < 12) && ((w != 2 && w != 4) || (ln & 3) == 0); }

struct Params {
  CUtensorMap tm_wqkv, tm_w1, tm_w2, tm_m, tm_wqkv64, tm_m64, tm_a, tm_ast;
  const __nv_bfloat16 *x, *b1, *b2, *wqkv, *w1, *w2, *wo;
  __nv_bfloat16* out;
};

__global__ void __cluster_dims__(2, 1, 1) __launch_bounds__(NTHREADS, 1) fused_kernel(const __grid_constant__ Params P) {
  extern __shared__ __align__(1024) uint8_t smem[];
  const uint32_t sbase = smem_u32(smem);
  const int tid = threadIdx.x, lane = tid & 31;
  const int warp = __shfl_sync(0xffffffffu, tid >> 5, 0);
  const int g = lane >> 2, t = lane & 3;
  const uint32_t ep = __shfl_sync(0xffffffffu, g_epoch[blockIdx.x], 0) + 1;
  const uint32_t par = ep & 1;
  STAMPW(0, 0);

  if (blockIdx.x >= 128) {
    const int a = blockIdx.x - 128;
    constexpr int WP = 1168, SM_T = 152 * WP, SM_HB = SM_T + 8 * 32 * 80;
    if (tid == 0) {
      mbar_init(sbase + SM_HB, 1);
      asm volatile("fence.mbarrier_init.release.cluster;" ::: "memory");
      mbar_expect(sbase + SM_HB, 144 * 1152);
    }
    for (int i = tid; i < (8 * WP + 8 * 32 * 80) / 4; i += NTHREADS) reinterpret_cast<uint32_t*>(smem + 144 * WP)[i] = 0u;
    __syncthreads();
    __nanosleep(1500);
    if (tid < 144)
      asm volatile("cp.async.bulk.shared::cluster.global.mbarrier::complete_tx::bytes [%0], [%1], %2, [%3];" ::"r"(sbase + tid * WP), "l"(P.wo + (a * 144 + tid) * D_), "r"(1152), "r"(sbase + SM_HB) : "memory");
    if (warp >= 8 && lane == 0) {
      const int id = a * 4 + (warp - 8);
      constexpr uint32_t CH = 9216 * 2;
#pragma unroll 1
      for (int i = id; i < 576; i += 16) {
        const char* p = i < 288 ? (const char*)P.w1 + (size_t)i * CH : (const char*)P.w2 + (size_t)(i - 288) * CH;
        asm volatile("cp.async.bulk.prefetch.L2.global [%0], %1;" ::"l"(p), "r"(CH) : "memory");
      }
    }
    __syncwarp();
    if (lane < 8) hint_wait(&g_f_kvp[a * 8 + lane], 16 * ep, 50);
    __syncwarp();
    STAMPW(0, 1);
#pragma unroll 1
    for (int u = warp; u < 40; u += 12) {
      const int hh = u & 7, w = 4 - (u >> 3), head = a * 8 + hh;
      uint4 v[16];
      int tries = 0;
      uint32_t bad;
      const bool val = kv_valid(w, lane);
#pragma unroll 1
      do {
        bad = 0;
#pragma unroll
        for (int j = 0; j < 16; j++) v[j] = val ? ld_ll(&g_kvp[((head * 5 + w) * 16 + j) * 32 + lane]) : make_uint4(par, 0u, par, 0u);
#pragma unroll
        for (int j = 0; j < 16; j++) ll_chk(bad, v[j].x, v[j].z, par);
      } while (__any_sync(0xffffffffu, bad & 1) && ++tries < (1 << 20));
      float s0 = 0.f, s1 = 0.f, s2 = 0.f, s3 = 0.f;
#pragma unroll
      for (int j = 0; j < 16; j++) { s0 += __uint_as_float(v[j].x); s1 += __uint_as_float(v[j].y); s2 += __uint_as_float(v[j].z); s3 += __uint_as_float(v[j].w); }
      if (w >= 3) {
        if (g == 2) st_ll(&g_z[(head * 2 + w - 3) * 4 + t], __float_as_uint(s0), __float_as_uint(s1), __float_as_uint(s2), __float_as_uint(s3), par);
        __syncwarp();
        hint_signal(&g_f_z[head]);
      }
      const int e0 = w < 3 ? g : 16 + g, e1 = w < 3 ? g + 8 : 16 + g, d0 = (w < 3 ? 8 * w : (w == 3 ? 0 : 16)) + 2 * t, d1 = w < 3 ? d0 : d0 + 8;
      __nv_bfloat16* T = reinterpret_cast<__nv_bfloat16*>(smem + SM_T) + hh * 32 * 40;
      if (e0 < 18) {
        T[d0 * 40 + e0] = __float2bfloat16(s0); T[(d0 + 1) * 40 + e0] = __float2bfloat16(s1);
        T[d1 * 40 + e1] = __float2bfloat16(s2); T[(d1 + 1) * 40 + e1] = __float2bfloat16(s3);
      }
    }
    __syncthreads();
    STAMPW(0, 2);
    mbar_wait(sbase + SM_HB, 0);
#pragma unroll 1
    for (int u = warp; u < 24; u += 12) {
      const int hh = u / 3, c0 = (u % 3) * 192;
      const uint32_t* T = reinterpret_cast<const uint32_t*>(smem + SM_T) + hh * 32 * 20 + g * 20 + t;
      const uint32_t a00 = T[0], a01 = T[160], a02 = T[4], a03 = T[164], a10 = T[8], a11 = T[168], b00 = T[320], b02 = T[324], b10 = T[328];
      const uint32_t rowa = sbase + (hh * 18 + (lane & 15)) * WP + (c0 + (lane >> 4) * 8) * 2, rowb = sbase + (hh * 18 + 16 + (lane & 7)) * WP + (c0 + ((lane >> 3) & 1) * 8) * 2;
#pragma unroll 3
      for (int j = 0; j < 12; j++) {
        uint32_t w0, w1, w2, w3, w4, w5;
        asm volatile("ldmatrix.sync.aligned.m8n8.x4.trans.shared.b16 {%0,%1,%2,%3}, [%4];" : "=r"(w0), "=r"(w1), "=r"(w2), "=r"(w3) : "r"(rowa + j * 32));
        asm volatile("ldmatrix.sync.aligned.m8n8.x2.trans.shared.b16 {%0,%1}, [%2];" : "=r"(w4), "=r"(w5) : "r"(rowb + j * 32));
        float p[4][4];
#pragma unroll
        for (int q = 0; q < 4; q++) p[q][0] = p[q][1] = p[q][2] = p[q][3] = 0.f;
        mma16816(p[0], a00, a01, a02, a03, w0, w1); mma16816(p[1], a00, a01, a02, a03, w2, w3);
        mma16816(p[2], b00, 0u, b02, 0u, w0, w1); mma16816(p[3], b00, 0u, b02, 0u, w2, w3);
        mma16816(p[0], a10, a11, 0u, 0u, w4, 0u); mma16816(p[1], a10, a11, 0u, 0u, w5, 0u);
        mma16816(p[2], b10, 0u, 0u, 0u, w4, 0u); mma16816(p[3], b10, 0u, 0u, 0u, w5, 0u);
        stsm4(rowa + j * 32, make_uint4(pack_bf16(p[0][0], p[0][1]), pack_bf16(p[0][2], p[0][3]), pack_bf16(p[1][0], p[1][1]), pack_bf16(p[1][2], p[1][3])));
        if (g < 2) {
          uint32_t* r = reinterpret_cast<uint32_t*>(smem + (hh * 18 + 16 + g) * WP + (c0 + j * 16 + 2 * t) * 2);
          r[0] = pack_bf16(p[2][0], p[2][1]); r[4] = pack_bf16(p[3][0], p[3][1]);
        }
      }
      asm volatile("fence.proxy.async.shared::cta;" ::: "memory");
      __syncwarp();
      if (lane < 18) {
        asm volatile("cp.async.bulk.global.shared::cta.bulk_group [%0], [%1], %2;" ::"l"(g_m + (a * 144 + hh * 18 + lane) * D_ + c0), "r"(sbase + (hh * 18 + lane) * WP + c0 * 2), "r"(384) : "memory");
        asm volatile("cp.async.bulk.commit_group;" ::: "memory");
      }
    }
    asm volatile("cp.async.bulk.wait_group 0;" ::: "memory");
    asm volatile("fence.proxy.async.global;" ::: "memory");
    __syncwarp();
    if (lane == 0) asm volatile("red.release.gpu.global.add.u32 [%0], 1;" ::"l"(g_f_m) : "memory");
    STAMPW(0, 3);
    __syncthreads();
    if (tid == 0) g_epoch[blockIdx.x] = ep;
    return;
  }

  const int cl = blockIdx.x >> 1, rank = blockIdx.x & 1;
  const int f = cl & 7, m = (cl >> 3) * 2 + rank;
  const int srole = f >= 6 ? 1 : 0;
  const uint32_t bar_full = sbase + SM_BAR, bar_empty = bar_full + 8 * NSTAGE, bar_xfree = bar_empty + 8 * NSTAGE, bar_ofull = bar_xfree + 72,
                 bar_d = bar_ofull + 72;

  if (tid == 0) {
#pragma unroll 1
    for (int i = 0; i < NSTAGE; i++) { mbar_init(bar_full + 8 * i, 1); mbar_init(bar_empty + 8 * i, 4); }
#pragma unroll 1
    for (int i = 0; i < 9; i++) { mbar_init(bar_xfree + 8 * i, 2); mbar_init(bar_ofull + 8 * i, 1); }
    mbar_init(bar_d, 1);
    asm volatile("fence.mbarrier_init.release.cluster;" ::: "memory");
  }
  __syncwarp();
  cluster_arrive_relaxed();

  if (warp >= 8) {
    const int srow = m * 128 + f * 16 + (warp - 8) * 4 + (lane >> 3);
    uint4 xs[9];
#pragma unroll
    for (int kb = 0; kb < 9; kb++) xs[kb] = __ldg(reinterpret_cast<const uint4*>(P.x + srow * D_) + (lane & 7) + kb * 8);
    auto stats = [&]() {
      const uint32_t* w = reinterpret_cast<const uint32_t*>(xs);
      float s0 = 0.f, s1 = 0.f;
#pragma unroll
      for (int i = 0; i < 36; i++) { s0 += bf_lo(w[i]); s1 += bf_hi(w[i]); }
      float sum = s0 + s1;
      sum += __shfl_xor_sync(0xffffffffu, sum, 1); sum += __shfl_xor_sync(0xffffffffu, sum, 2); sum += __shfl_xor_sync(0xffffffffu, sum, 4);
      const float mean = sum * (1.f / 576.f);
      s0 = 0.f; s1 = 0.f;
#pragma unroll
      for (int i = 0; i < 36; i++) { const float a = bf_lo(w[i]) - mean, b = bf_hi(w[i]) - mean; s0 = fmaf(a, a, s0); s1 = fmaf(b, b, s1); }
      float sq = s0 + s1;
      sq += __shfl_xor_sync(0xffffffffu, sq, 1); sq += __shfl_xor_sync(0xffffffffu, sq, 2); sq += __shfl_xor_sync(0xffffffffu, sq, 4);
      const float rstd = rsqrtf(sq * (1.f / 576.f) + 1e-5f);
      if ((lane & 7) == 0)
        st_ll64(&g_stat[srow], __float_as_uint(rstd), pack_bf16(-mean, -mean), par);
    };
    stats();
    asm volatile("setmaxnreg.dec.sync.aligned.u32 40;");
    cluster_wait();
    if (warp == 8) {
      uint32_t stage = 0, phase = 1;
      const uint32_t sb = sbase + SM_B + rank * 6144;
#pragma unroll 1
      for (int tl = 2 * srole; tl < 8 + 2 * srole; tl++) {
        const CUtensorMap* map = tl == 0 ? &P.tm_wqkv : (tl == 1 ? &P.tm_wqkv64 : (tl < 5 ? &P.tm_w1 : (tl < 8 ? &P.tm_w2 : (tl == 8 ? &P.tm_m : &P.tm_m64))));
        const int col = tl < 2 ? 288 * f + 192 * tl : (tl < 5 ? 576 * f + 192 * (tl - 2) : (tl < 8 ? 192 * ((tl - 5 + f) % 3) : (tl == 8 ? 192 * (f - 5) : 96 * (f - 6))));
        const bool perm = tl >= 5 && tl < 8;
        const bool z = (tl & 7) == 1;
        if (tl == 8) { flag_wait(g_f_m, 48 * ep); asm volatile("fence.proxy.async.global;" ::: "memory"); }
        const int rs = z ? 64 : 32, n3 = z ? 3 : 6;
#pragma unroll 1
        for (int blk = 0; blk < 3; blk++) {
          int row = (perm ? 576 * f + (blk == 2 ? 384 : 192 - 192 * blk) : 192 * blk) + rank * (rs >> 1);
#pragma unroll 1
          for (int st = 0; st < n3; st++) {
            mbar_wait(bar_empty + 8 * stage, phase);
            tma3d_mc_elect(sb + stage * STAGE_BYTES, map, col, row, bar_full + 8 * stage);
            row += rs;
            if (++stage == NSTAGE) { stage = 0; phase ^= 1; }
          }
        }
      }
    } else {
      const int aw = warp - 9;
      const int hi = f >> 2;
      if (aw == 0) {
        if (lane < 2) hint_wait(&g_f_qkv[m * 8 + 2 + 2 * lane + hi], 16 * ep, 200);
        __syncwarp();
        if (lane == 0) mbar_arrive(bar_d);
        STAMP(20);
      }
      if (lane < 5) hint_wait(lane < 4 ? &g_f_z[4 * f + lane] : &g_f_qkv[m * 8 + hi], lane < 4 ? 2 * ep : 16 * ep);
      __syncwarp();
      STAMPW(9, 22);
      uint32_t* stg = reinterpret_cast<uint32_t*>(smem + SM_SCR + aw * 2304);
#pragma unroll 1
      for (int u = aw * 2; u < 16; u += (u & 1) ? 5 : 1) {
        const int rbl = u >> 1, hp = (u & 1) * 2;
        const uint2* qf = g_qkv + (m * 8 + rbl) * 216 * 32;
        const uint2* zp = reinterpret_cast<const uint2*>(&g_z[(4 * f + hp) * 8 + t]);
        uint2 q[2][3];
        float d[4];
        int tries = 0;
        uint32_t bad;
#pragma unroll 1
        do {
          bad = tries ? ld_acquire(g_f_m) & 0u : 0u;
#pragma unroll
          for (int j = 0; j < 2; j++)
#pragma unroll
            for (int b = 0; b < 3; b++) q[j][b] = ld_ca64(qf + pairoff((4 * f + hp + j) * 9 + t, g) + 32 * b);
#pragma unroll
          for (int j = 0; j < 2; j++) {
            const uint2 z0 = ld_ca64(zp + 16 * j), z1 = ld_ca64(zp + 16 * j + 1), z2 = ld_ca64(zp + 16 * j + 8);
            if (t != 0) q[j][2] = make_uint2(par, 0u);
            ll_chk(bad, z0.x, z1.x, par); ll_chk(bad, z2.x, q[j][2].x, par); ll_chk(bad, q[j][0].x, q[j][1].x, par);
            d[2 * j] = bf_lo(q[j][0].x) * __uint_as_float(z0.x) + bf_hi(q[j][0].x) * __uint_as_float(z0.y) + bf_lo(q[j][1].x) * __uint_as_float(z1.x) + bf_hi(q[j][1].x) * __uint_as_float(z1.y) +
                       bf_lo(q[j][2].x) * __uint_as_float(z2.x) + bf_hi(q[j][2].x) * __uint_as_float(z2.y);
            d[2 * j + 1] = bf_lo(q[j][0].y) * __uint_as_float(z0.x) + bf_hi(q[j][0].y) * __uint_as_float(z0.y) + bf_lo(q[j][1].y) * __uint_as_float(z1.x) + bf_hi(q[j][1].y) * __uint_as_float(z1.y) +
                           bf_lo(q[j][2].y) * __uint_as_float(z2.x) + bf_hi(q[j][2].y) * __uint_as_float(z2.y);
          }
        } while (__any_sync(0xffffffffu, bad & 1) && ++tries < (1 << 20));
#pragma unroll
        for (int j = 0; j < 4; j++) d[j] += __shfl_xor_sync(0xffffffffu, d[j], 1);
#pragma unroll
        for (int j = 0; j < 4; j++) d[j] = rcpf(d[j] + __shfl_xor_sync(0xffffffffu, d[j], 2) + 1e-6f);
        if (hp == 0) { asm volatile("cp.async.bulk.wait_group.read 0;" ::: "memory"); __syncwarp(); }
#pragma unroll
        for (int j = 0; j < 2; j++) {
          const uint32_t r0 = pack_bf16(d[2 * j], d[2 * j]), r1 = pack_bf16(d[2 * j + 1], d[2 * j + 1]);
#pragma unroll
          for (int b = 0; b < 3; b++)
            if (b < 2 || t == 0) {
              stg[g * 36 + (hp + j) * 9 + 4 * b + t] = hfma2(q[j][b].x, r0, 0x80008000u);
              stg[(g + 8) * 36 + (hp + j) * 9 + 4 * b + t] = hfma2(q[j][b].y, r1, 0x80008000u);
            }
        }
        if (hp != 0) {
          asm volatile("fence.proxy.async.shared::cta;" ::: "memory");
          __syncwarp();
          if (lane == 0) {
            asm volatile("cp.async.bulk.tensor.2d.global.shared::cta.bulk_group [%0, {%2, %3}], [%1];" ::"l"(&P.tm_ast), "r"(smem_u32(stg)), "r"(72 * f), "r"(m * 128 + rbl * 16) : "memory");
            asm volatile("cp.async.bulk.commit_group;" ::: "memory");
          }
        }
      }
      asm volatile("cp.async.bulk.wait_group 0;" ::: "memory");
      asm volatile("fence.proxy.async.global;" ::: "memory");
      STAMPW(9, 26);
      asm volatile("bar.sync 5, 96;" ::: "memory");
      if (tid == 288) asm volatile("red.release.gpu.global.add.u32 [%0], 1;" ::"l"(&g_f_a[m]) : "memory");
      __syncwarp();
      STAMPW(9, 23);
      if (srole && aw == 2) {
        if (lane == 0) {
          flag_wait(&g_f_a[m], 8 * ep);
          asm volatile("fence.proxy.async.global;" ::: "memory");
#pragma unroll 1
          for (int kb = 0; kb < 9; kb++) {
            mbar_wait(bar_xfree + 8 * kb, 0);
            mbar_expect(bar_ofull + 8 * kb, 16384);
            tma2d(sbase + SM_A + kb * 16384, &P.tm_a, kb * 64, m * 128, bar_ofull + 8 * kb);
          }
        }
        __syncwarp();
      }
    }
    cluster_arrive_relaxed();
    cluster_wait();
  } else {
    const int wg = warp >> 2;
    {
      const int rs = lane >> 3, j = lane & 7;
      uint4 xv[4][9];
#pragma unroll
      for (int it = 0; it < 4; it++)
#pragma unroll
        for (int kb = 0; kb < 9; kb++) xv[it][kb] = __ldg(reinterpret_cast<const uint4*>(P.x + (m * 128 + warp * 16 + it * 4 + rs) * D_) + j + kb * 8);
      uint32_t bw0 = __ldg(reinterpret_cast<const uint32_t*>(P.b1 + 576 * f) + tid), bw1 = tid < 32 ? __ldg(reinterpret_cast<const uint32_t*>(P.b1 + 576 * f) + 256 + tid) : 0u;
      uint2 st[4];
      int tries = 0;
      uint32_t bad;
#pragma unroll 1
      do {
        bad = 0;
#pragma unroll
        for (int it = 0; it < 4; it++) st[it] = ld_ll64(&g_stat[m * 128 + warp * 16 + it * 4 + rs]);
        ll_chk(bad, st[0].x, st[1].x, par); ll_chk(bad, st[2].x, st[3].x, par);
      } while (__any_sync(0xffffffffu, bad & 1) && ++tries < (1 << 22));
      STAMPW(0, 19);
#pragma unroll
      for (int it = 0; it < 4; it++) {
        const uint32_t nm = st[it].y;
        uint8_t* dst = smem + SM_A + (warp * 16 + it * 4 + rs) * 128 + ((j ^ ((it * 4 + rs) & 7)) << 4);
#pragma unroll
        for (int kb = 0; kb < 9; kb++) {
          const uint4 w = xv[it][kb];
          *reinterpret_cast<uint4*>(dst + kb * 16384) = make_uint4(hadd2(w.x, nm), hadd2(w.y, nm), hadd2(w.z, nm), hadd2(w.w, nm));
        }
        if (j == 0) reinterpret_cast<uint32_t*>(smem + SM_RSTD)[warp * 16 + it * 4 + rs] = st[it].x;
      }
      reinterpret_cast<float2*>(smem + SM_BIAS)[tid] = make_float2(bf_lo(bw0) * GK, bf_hi(bw0) * GK);
      if (tid < 48) reinterpret_cast<float2*>(smem + SM_BIAS)[256 + tid] = make_float2(bf_lo(bw1) * GK, bf_hi(bw1) * GK);
      asm volatile("fence.proxy.async.shared::cta;" ::: "memory");
    }
    asm volatile("setmaxnreg.inc.sync.aligned.u32 232;");
    cluster_wait();
    asm volatile("bar.sync 1, 256;" ::: "memory");
    STAMPW(0, 1);
    Ctx c;
    c.full = bar_full; c.budget = 1 << 22;
    c.emb = __shfl_sync(0xffffffffu, mapa(bar_empty, (warp & 3) == 0 ? rank : (rank ^ 1)), 0);
    c.sig = lane == 0 && (warp & 3) < 2;
    c.dB = (((sbase + SM_B) & 0x3FFFF) >> 4) | ((2048u >> 4) << 16);
    c.dA = (((sbase + SM_A + wg * 8192) & 0x3FFFF) >> 4) | (1u << 16);
    const bool leader = (lane == 0) && ((warp & 3) == 0);

    const int rb = m * 8 + warp;
    const uint32_t bias_t = sbase + SM_BIAS + 8 * t;
    const uint32_t hst = sbase + SM_A + (warp * 16 + (lane & 7) + ((lane >> 3) & 1) * 8) * 128 + (((lane >> 4) ^ (lane & 7)) << 4);
    auto wg_sync = [&]() {
      asm volatile("fence.proxy.async.shared::cta;" ::: "memory");
      if (wg == 0) asm volatile("bar.sync 2, 128;" ::: "memory"); else asm volatile("bar.sync 3, 128;" ::: "memory");
    };
    float A[96], B[96];
#pragma unroll
    for (int i = 0; i < 96; i++) B[i] = 0.f;
#define EXB(ACC, U) uint32_t E[4]; _Pragma("unroll") for (int q = 0; q < 4; q++) E[q] = pack_bf16(fmaf(ACC[8 * (U) + 2 * q], (q & 1) ? r1 : r0, bs[q >> 1].x), fmaf(ACC[8 * (U) + 2 * q + 1], (q & 1) ? r1 : r0, bs[q >> 1].y));
#define ST_QKV(ACC, U, DST) { uint32_t E[4]; _Pragma("unroll") for (int q = 0; q < 4; q++) \
      E[q] = phi_pack(pack_bf16(ACC[8 * (U) + 2 * q] * ((q & 1) ? r1 : r0), ACC[8 * (U) + 2 * q + 1] * ((q & 1) ? r1 : r0)), ACC[8 * (U) + 2 * q] * ((q & 1) ? l1 : l0), ACC[8 * (U) + 2 * q + 1] * ((q & 1) ? l1 : l0), pc1, pc2); \
    st_ll64(reinterpret_cast<uint2*>(DST) + 64 * (U), E[0], E[1], par); st_ll64(reinterpret_cast<uint2*>(DST) + 64 * (U) + 32, E[2], E[3], par); }
#define PHI_SETUP const float l0 = r0 * 1.4426950408889634f, l1 = r1 * 1.4426950408889634f; const uint32_t pc1 = f < 4 ? 0x35863586u : 0xff80ff80u, pc2 = f < 4 ? 0x3f803f80u : 0u;
#define HADDR(KB0, U) ((hst ^ (((U) & 3) << 5)) + ((KB0) + ((U) >> 2)) * 16384)
#define LDS_R(SC) float r0, r1; asm volatile("ld.shared.f32 %0, [%1];" : "=f"(r0) : "r"(rst)); asm volatile("ld.shared.f32 %0, [%1];" : "=f"(r1) : "r"(rst + 32)); r0 *= (SC); r1 *= (SC);
    const uint32_t rst = sbase + SM_RSTD + (warp * 16 + g) * 4;
    const int fr = f % 3;
#pragma unroll 1
    for (int i = srole;; i++) {
      {
        c.set((!srole && i >= 1) ? 1u : 0u, 0u);
        const uint32_t owp = i == 4 ? 0u : 1u;
        c.wait(bar_ofull, owp);
        issue192(A, c, 0, true);
        const int ln = opaque(lane);
        uint4* dst = i == 1 ? reinterpret_cast<uint4*>(g_qkv + (rb * 216 + 36 * f + 24) * 32 + ln) : g_part + ((rb * 8 + f) * 36 + 12 * (i == 3 ? fr : (fr + 2) % 3)) * 32 + ln;
        LDS_R(i == 2 ? GK : 1.f)
#define HEAD(ACC) wg_wait<1>(); c.release(4); c.release(5); fence_regs<96>(ACC);
        int s = 1;
        if (i == 2) {
          HEAD(B)
#pragma unroll
          for (int k = 1; k < 9; k++) {
            float2 b0[2], b1[2];
            if (k >= 3) { lds_bias(b0, bias_t + (192 + 32 * (k - 3)) * 4); lds_bias(b1, bias_t + (208 + 32 * (k - 3)) * 4); }
            issue192(A, c, k);
            if (k >= 3) {
              const int u = k >= 3 ? 2 * (k - 3) : 0;
              { const float2* bs = b0; EXB(B, u) stsm4(HADDR(0, u), gelu_group(E)); }
              { const float2* bs = b1; EXB(B, u + 1) stsm4(HADDR(0, u + 1), gelu_group(E)); }
            }
            retire(c, k - 1);
          }
          s = 9;
        } else if (i >= 3) {
          HEAD(B)
          if (i == 4 && leader) mbar_arrive(bar_xfree + 64);
#pragma unroll
          for (int u = 0; u < 12; u++) {
            if (u & 1) c.wait(bar_ofull + 4 * (u + 1), owp);
            issue192(A, c, u + 1);
            part_groups<0, 1>(&B[8 * u], dst + u * 32, par);
            retire(c, u);
          }
          s = 13;
        } else if (i > srole) {
          PHI_SETUP
          HEAD(B)
#pragma unroll
          for (int u = 0; u < 6; u++) {
            issue192(A, c, u + 1);
            ST_QKV(B, u, dst)
            retire(c, u);
          }
          hint_signal(&g_f_qkv[m * 8 + f]);
          s = 7;
        } else wg_wait<1>();
        const bool d1 = i == 1 + srole;
        const int send = d1 ? 10 : 15;
        plain192(A, c, s, send, [&](int k) { if (k == 14) c.wait(bar_ofull + 56, owp); }, [](int) {});
        uint32_t W[48];
        if (d1) {
          const int head = 4 * f + (warp >> 1), rb0 = m * 8 + (warp & 1) * 4;
          issue192(A, c, 10);
          c.wait(bar_d, 0);
          d1_load<false, 0, 2>(W, rb0, head, opaque(lane));
          retire(c, 9);
          issue192(A, c, 11);
          d1_load<false, 2, 4>(W, rb0, head, opaque(lane));
          retire(c, 10);
          issue192(A, c, 12);
          retire(c, 11);
          issue192(A, c, 13);
          int tries = 0;
#pragma unroll 1
          while (d1_bad(W, t, par) && ++tries < (1 << 20)) d1_load<true, 0, 4>(W, rb0, head, opaque(lane));
          d1_mov(W, 0, t); d1_mov(W, 1, t);
          retire(c, 12);
          issue192(A, c, 14);
          d1_mov(W, 2, t); d1_mov(W, 3, t);
          wg_wait<0>();
          asm volatile("bar.sync 4, 256;" ::: "memory");
          float R[18];
          float zero;
          asm volatile("ld.volatile.shared.f32 %0, [%1];" : "=f"(zero) : "r"(sbase + SM_BIAS + 2304) : "memory");
          d1_mma(W, R, zero);
          const int l2 = opaque(lane);
          float2* xch = reinterpret_cast<float2*>(smem + SM_SCR + (warp >> 1) * 1792) + l2;
          float2* xc2 = xch + 192 - l2 + (l2 < 12 ? l2 : 31);
          if (warp & 1) {
#pragma unroll
            for (int q = 0; q < 6; q++) xch[q * 32] = make_float2(R[2 * q], R[2 * q + 1]);
            if (l2 < 12) { xc2[0] = make_float2(R[12], R[13]); xc2[12] = make_float2(R[14], R[15]); }
            if (l2 < 12 && (l2 & 3) == 0) xc2[24 - l2 + (l2 >> 2)] = make_float2(R[16], R[17]);
          } else if ((R[0] + R[4]) + (R[8] + R[12]) + (R[14] + R[16]) == 1.2345e-30f) xch[223 - l2] = make_float2(0.f, 0.f);
          asm volatile("bar.sync 4, 256;" ::: "memory");
          c.release(13);
          issue192(A, c, 15);
          if (!(warp & 1)) {
#pragma unroll
            for (int q = 0; q < 6; q++) { const float2 o = xch[q * 32]; R[2 * q] += o.x; R[2 * q + 1] += o.y; }
            const float2 o0 = xc2[0], o1 = xc2[l2 < 12 ? 12 : 0], o2 = xc2[l2 < 12 ? 24 - l2 + (l2 >> 2) : 0];
            uint4* dkv = &g_kvp[(head * 80 + m) * 32 + l2];
#pragma unroll
            for (int w = 0; w < 3; w++) st_ll(dkv + w * 512, __float_as_uint(R[4 * w]), __float_as_uint(R[4 * w + 1]), __float_as_uint(R[4 * w + 2]), __float_as_uint(R[4 * w + 3]), par);
            st_ll(dkv + 1536, __float_as_uint(R[12] + o0.x), __float_as_uint(R[13] + o0.y), __float_as_uint(R[14] + o1.x), __float_as_uint(R[15] + o1.y), par);
            st_ll(dkv + 2048, __float_as_uint(R[16] + o2.x), __float_as_uint(R[17] + o2.y), 0u, 0u, par);
            hint_signal(&g_f_kvp[head]);
          }
          STAMPW(0, 21);
        } else issue192(A, c, 15);
        if (i == 2) {
          const uint4* hsp = g_hsp + (blockIdx.x * 8 + warp) * 12 * 32 + opaque(lane);
#pragma unroll
          for (int q = 0; q < 12; q++) { const uint4 v = ldcg128(hsp + q * 32); W[4 * q] = v.x; W[4 * q + 1] = v.y; W[4 * q + 2] = v.z; W[4 * q + 3] = v.w; }
          retire(c, 14);
          issue192(A, c, 16);
          wg_sync();
          retire(c, 15);
          issue192(A, c, 17);
#pragma unroll
          for (int q = 0; q < 12; q++) stsm4(HADDR(3, q), make_uint4(W[4 * q], W[4 * q + 1], W[4 * q + 2], W[4 * q + 3]));
        } else {
          retire(c, 14);
          c.wait(bar_ofull + 64, owp);
          issue192(A, c, 16);
          retire(c, 15);
          issue192(A, c, 17);
        }
      }
      STAMPW(0, 2 + 2 * i);
      c.set((!srole && i >= 1) ? 1u : 0u, 1u);
      if ((i & 3) == 0) {
        issue96(B, c, 0, true);
        const int ln = opaque(lane);
        uint2* dst = i == 0 ? g_qkv + (rb * 216 + 36 * f) * 32 + ln : g_s + (rb * 72 + 24 * (f - 5)) * 32 + ln;
        LDS_R(1.f)
        if (i != 0) { r0 = 1.f; r1 = 1.f; }
        PHI_SETUP
        HEAD(A)
#pragma unroll
        for (int k = 1; k < 9; k++) {
          issue96(B, c, k, false);
#pragma unroll
          for (int u = (3 * (k - 1) + 1) / 2; u < (3 * k + 1) / 2; u++) ST_QKV(A, u, dst)
          if (k < 8) retire(c, k - 1);
        }
        if (i == 4) {
          STAMPW(0, 11);
          wg_wait<0>();
          c.release(7); c.release(8);
          fence_regs<48>(B);
          uint2* d2 = g_s + (rb * 72 + 12 * (f - 6)) * 32 + opaque(lane);
#pragma unroll
          for (int q = 0; q < 12; q++) st_ll64(d2 + q * 32, pack_bf16(B[4 * q], B[4 * q + 1]), pack_bf16(B[4 * q + 2], B[4 * q + 3]), par);
          break;
        }
        hint_signal(&g_f_qkv[m * 8 + f]);
      } else {
        issue192(B, c, 0, true);
        const int ln = opaque(lane);
        uint4* dst = i == 1 ? g_hsp + (blockIdx.x * 8 + warp) * 12 * 32 + ln : g_part + ((rb * 8 + f) * 36 + 12 * ((fr + 1) % 3)) * 32 + ln;
        const bool xf = i == 3 && srole && leader;
        const uint32_t bsa = bias_t + (i == 1 ? 0 : 384) * 4;
        LDS_R(GK)
        int s;
        if (i != 3) {
          HEAD(A)
#pragma unroll
          for (int u = 0; u < 12; u++) {
            float2 bs[2];
            lds_bias(bs, bsa + 16 * u * 4);
            issue192(B, c, u + 1);
            EXB(A, u)
            const uint4 h = gelu_group(E);
            asm volatile("{.reg .pred p; setp.eq.s32 p, %6, 1; @p st.global.v4.u32 [%0], {%2,%3,%4,%5}; @!p stmatrix.sync.aligned.m8n8.x4.shared.b16 [%1], {%2,%3,%4,%5};}"
                         ::"l"(dst + u * 32), "r"(HADDR(6, u)), "r"(h.x), "r"(h.y), "r"(h.z), "r"(h.w), "r"(i) : "memory");
            if (u == 3 || u == 9) wg_sync();
            retire(c, u);
          }
          s = 13;
        } else {
          HEAD(A)
#pragma unroll
          for (int u = 0; u < 6; u++) {
            issue192(B, c, u + 1);
            part_groups<0, 2>(&A[16 * u], dst + 2 * u * 32, par);
            retire(c, u);
            if ((u & 1) && xf) mbar_arrive(bar_xfree + 4 * u - 4);
          }
          s = 7;
        }
        if (i == 3 && !srole) {
          const int c2 = (fr + 2) % 3, v0 = 12 * c2 + (f < 3 ? 0 : 6), fo = f < 3 ? f + 3 : f - 3;
          const int l2 = opaque(lane);
          const uint4* pb = g_part + (rb * 8 * 36 + v0) * 32 + l2;
          uint4 p[12];
          uint32_t S[24];
#pragma unroll
          for (int q = 0; q < 24; q++) S[q] = 0u;
          auto ldp = [&](const uint4* a0, const uint4* a1) {
#pragma unroll
            for (int q = 0; q < 6; q++) { p[q] = ld_ll(a0 + q * 32); p[6 + q] = ld_ll(a1 + q * 32); }
          };
          auto badp = [&]() {
            uint32_t bad = 0;
#pragma unroll
            for (int q = 0; q < 12; q++) ll_chk(bad, p[q].x, p[q].z, par);
            return __any_sync(0xffffffffu, bad & 1);
          };
#pragma unroll 1
          for (int w = 0; w < 3; w++) {
            const uint4* a0 = pb + (w == 0 ? c2 : (w == 1 ? 6 : (fr + 1) % 3)) * 36 * 32;
            const uint4* a1 = a0 + (w == 1 ? 1 : 3) * 36 * 32;
            issue192(B, c, 7 + 3 * w);
            ldp(a0, a1);
            retire(c, 6 + 3 * w);
            issue192(B, c, 8 + 3 * w);
            retire(c, 7 + 3 * w);
            issue192(B, c, 9 + 3 * w);
            int tries = 0;
#pragma unroll 1
            while (badp() && ++tries < (1 << 20)) ldp(a0, a1);
#pragma unroll
            for (int q = 0; q < 24; q++) S[q] = hadd2(S[q], hadd2(reinterpret_cast<const uint32_t*>(p)[q], reinterpret_cast<const uint32_t*>(p)[24 + q]));
            retire(c, 8 + 3 * w);
          }
          uint4 xx[6];
          uint32_t bb[12];
          int ro[6];
          issue192(B, c, 16);
#pragma unroll
          for (int j = 0; j < 6; j++) {
            const int k = l2 + 32 * j, r = (k * 171) >> 11;
            ro[j] = (rb * 16 + r) * D_ + 16 * v0 + (k - 12 * r) * 8;
            xx[j] = __ldg(reinterpret_cast<const uint4*>(P.x + ro[j]));
          }
#pragma unroll
          for (int j = 0; j < 12; j++) bb[j] = __ldg(reinterpret_cast<const uint32_t*>(P.b2 + 16 * v0 + 8 * j + 2 * (l2 & 3)));
          retire(c, 15);
          issue192(B, c, 17);
          retire(c, 16);
          STAMPW(0, 9);
          wg_wait<0>();
          c.release(17);
          fence_regs<96>(B);
          uint4* snd = g_part + ((rb * 8 + f) * 36 + 12 * c2 + (f < 3 ? 6 : 0)) * 32 + l2;
          if (f < 3) part_groups<0, 6>(B + 48, snd, par);
          else {
            part_groups<0, 6>(B, snd, par);
#pragma unroll
            for (int q = 0; q < 48; q++) B[q] = B[48 + q];
          }
          asm volatile("bar.sync 4, 256;" ::: "memory");
          STAMPW(0, 12);
#pragma unroll
          for (int q = 0; q < 24; q++) {
            B[2 * q] = fmaf(B[2 * q] + bf_lo(S[q]), 0.25f / GK, 0.5f * bf_lo(bb[q >> 1])); B[2 * q + 1] = fmaf(B[2 * q + 1] + bf_hi(S[q]), 0.25f / GK, 0.5f * bf_hi(bb[q >> 1]));
          }
          const uint2* sp = g_s + (rb * 72 + 2 * v0) * 32 + l2;
          int tries = 0;
#pragma unroll 1
          while (++tries < (1 << 20)) {
            const uint2 u0 = ld_ll64(pb + (fo * 36 + 5) * 32), u1 = ld_ll64(sp + 11 * 32);
            if (!__any_sync(0xffffffffu, ((u0.x ^ par) | (u1.x ^ par)) & 1)) break;
            __nanosleep(40);
          }
          tries = 0;
#pragma unroll 1
          do {
#pragma unroll
            for (int q = 0; q < 6; q++) {
              p[q] = ld_ll(pb + (fo * 36 + q) * 32);
              const uint2 s0 = ld_ll64(sp + 2 * q * 32), s1 = ld_ll64(sp + (2 * q + 1) * 32);
              p[6 + q] = make_uint4(s0.x, s0.y, s1.x, s1.y);
            }
          } while (badp() && ++tries < (1 << 20));
          STAMPW(0, 14);
          const uint32_t tb = sbase + SM_A + warp * 3328;
#pragma unroll
          for (int v = 0; v < 6; v++) {
            uint32_t o[4];
#pragma unroll
            for (int k = 0; k < 4; k++) {
              const int q = 4 * v + k;
              const uint32_t w = reinterpret_cast<const uint32_t*>(p)[q];
              const uint32_t gt = pack_bf16(silu_h(fmaf(bf_lo(w), 0.25f / GK, B[2 * q])), silu_h(fmaf(bf_hi(w), 0.25f / GK, B[2 * q + 1])));
              o[k] = hfma2(reinterpret_cast<const uint32_t*>(p)[24 + q], gt, 0x80008000u);
            }
            stsm4(tb + (l2 & 15) * 208 + (l2 >> 4) * 16 + v * 32, make_uint4(o[0], o[1], o[2], o[3]));
          }
          __syncwarp();
#pragma unroll
          for (int j = 0; j < 6; j++) {
            const int k = l2 + 32 * j, r = (k * 171) >> 11;
            uint4 o;
            asm volatile("ld.shared.v4.u32 {%0,%1,%2,%3}, [%4];" : "=r"(o.x), "=r"(o.y), "=r"(o.z), "=r"(o.w) : "r"(tb + r * 208 + (k - 12 * r) * 16) : "memory");
            *reinterpret_cast<uint4*>(P.out + ro[j]) = make_uint4(hadd2(o.x, xx[j].x), hadd2(o.y, xx[j].y), hadd2(o.z, xx[j].z), hadd2(o.w, xx[j].w));
          }
          break;
        }
        plain192(B, c, s, 17, [&](int k) { if (k == 15) wg_sync(); }, [&](int k) { if (!(k & 1) && xf) mbar_arrive(bar_xfree + 4 * k - 8); });
        issue192(B, c, 17);
      }
      STAMPW(0, 3 + 2 * i);
    }
    STAMPW(0, 15);
    cluster_arrive_relaxed();
    cluster_wait();
    STAMPW(0, 16);
    if (tid == 0) g_epoch[blockIdx.x] = ep;
  }
}

typedef CUresult (*EncFn)(CUtensorMap*, CUtensorMapDataType, cuuint32_t, void*, const cuuint64_t*, const cuuint64_t*, const cuuint32_t*, const cuuint32_t*,
                          CUtensorMapInterleave, CUtensorMapSwizzle, CUtensorMapL2promotion, CUtensorMapFloatOOBfill);

void make_map(EncFn enc, CUtensorMap* tm, const void* ptr, int rows, int cols, int box_cols, int box_rows, CUtensorMapSwizzle sw) {
  cuuint64_t gd[2] = {(cuuint64_t)cols, (cuuint64_t)rows};
  cuuint64_t gs[1] = {(cuuint64_t)cols * 2};
  cuuint32_t bx[2] = {(cuuint32_t)box_cols, (cuuint32_t)box_rows};
  cuuint32_t es[2] = {1, 1};
  enc(tm, CU_TENSOR_MAP_DATA_TYPE_BFLOAT16, 2, const_cast<void*>(ptr), gd, gs, bx, es, CU_TENSOR_MAP_INTERLEAVE_NONE, sw, CU_TENSOR_MAP_L2_PROMOTION_L2_256B, CU_TENSOR_MAP_FLOAT_OOB_FILL_NONE);
}
void make_wmap(EncFn enc, CUtensorMap* tm, const void* ptr, int rows, int cols, bool sw64) {
  const int ac = sw64 ? 32 : 64;
  cuuint64_t gd[3] = {(cuuint64_t)(cols - 2 * ac), (cuuint64_t)rows, 3};
  cuuint64_t gs[2] = {(cuuint64_t)cols * 2, (cuuint64_t)ac * 2};
  cuuint32_t bx[3] = {(cuuint32_t)ac, sw64 ? 32u : 16u, 3};
  cuuint32_t es[3] = {1, 1, 1};
  enc(tm, CU_TENSOR_MAP_DATA_TYPE_BFLOAT16, 3, const_cast<void*>(ptr), gd, gs, bx, es, CU_TENSOR_MAP_INTERLEAVE_NONE, sw64 ? CU_TENSOR_MAP_SWIZZLE_64B : CU_TENSOR_MAP_SWIZZLE_128B,
      CU_TENSOR_MAP_L2_PROMOTION_L2_256B, CU_TENSOR_MAP_FLOAT_OOB_FILL_NONE);
}

}

extern "C" void kernel_launch(void* const* d_in, const int* in_sizes, int n_in, void* d_out, int out_size) {
  (void)in_sizes; (void)n_in; (void)out_size;
  static EncFn enc = nullptr;
  static void *a_ptr = nullptr, *m_ptr = nullptr;
  if (!enc) {
    void* fn = nullptr; cudaDriverEntryPointQueryResult q;
    cudaGetDriverEntryPoint("cuTensorMapEncodeTiled", &fn, cudaEnableDefault, &q);
    enc = (EncFn)fn;
    cudaFuncSetAttribute(fused_kernel, cudaFuncAttributeMaxDynamicSharedMemorySize, SMEM_BYTES);
    cudaGetSymbolAddress(&a_ptr, g_a);
    cudaGetSymbolAddress(&m_ptr, g_m);
  }
  Params P;
  P.x = (const __nv_bfloat16*)d_in[0];
  P.wqkv = (const __nv_bfloat16*)d_in[1];
  P.wo = (const __nv_bfloat16*)d_in[2];
  P.w1 = (const __nv_bfloat16*)d_in[4];
  P.b1 = (const __nv_bfloat16*)d_in[5];
  P.w2 = (const __nv_bfloat16*)d_in[6];
  P.b2 = (const __nv_bfloat16*)d_in[7];
  P.out = (__nv_bfloat16*)d_out;
  make_wmap(enc, &P.tm_wqkv, P.wqkv, D_, Q3_, false);
  make_wmap(enc, &P.tm_w1, P.w1, D_, F_, false);
  make_wmap(enc, &P.tm_w2, P.w2, F_, D_, false);
  make_wmap(enc, &P.tm_m, m_ptr, D_, D_, false);
  make_wmap(enc, &P.tm_wqkv64, P.wqkv, D_, Q3_, true);
  make_wmap(enc, &P.tm_m64, m_ptr, D_, D_, true);
  make_map(enc, &P.tm_a, a_ptr, S_, D_, 64, 128, CU_TENSOR_MAP_SWIZZLE_128B);
  make_map(enc, &P.tm_ast, a_ptr, S_, D_, 72, 16, CU_TENSOR_MAP_SWIZZLE_NONE);
  fused_kernel<<<NCTAS, NTHREADS, SMEM_BYTES, cudaStreamPerThread>>>(P);
}
```

```cpp
#include <cuda_runtime.h>
#include <cuda.h>
#include <cuda_bf16.h>
#include <stdint.h>

namespace {

constexpr int S_ = 2048, D_ = 576, F_ = 4608, Q3_ = 1728;
constexpr int NSTAGE = 6, STAGE_BYTES = 12288;
constexpr int SM_A = 0, SM_B = 147456, SM_BIAS = SM_B + NSTAGE * STAGE_BYTES, SM_RSTD = SM_BIAS + 2304 + 128, SM_SCR = SM_RSTD + 512, SM_Z = SM_SCR + 7168, SM_B2 = SM_Z + 384, SM_BAR = SM_B2 + 384;
constexpr int SMEM_BYTES = SM_BAR + 320;
constexpr int NTHREADS = 384;
constexpr int NCTAS = 132;

__device__ __align__(128) uint2 g_qkv[(128 * 216 + 2) * 32];
__device__ __align__(1024) __nv_bfloat16 g_a[S_ * D_];
__device__ __align__(1024) __nv_bfloat16 g_m[D_ * D_];
__device__ __align__(128) uint4 g_kvp[32 * 5 * 16 * 32];
__device__ uint4 g_z[32 * 2 * 4];
__device__ __align__(128) uint4 g_part[128 * 8 * 36 * 32];
__device__ __align__(128) uint2 g_s[128 * 72 * 32];
__device__ __align__(128) uint4 g_hsp[128 * 12 * 256];
__device__ __align__(128) uint32_t g_f_qkv[16 * 32];
__device__ __align__(128) uint32_t g_f_kvp[32 * 32];
__device__ __align__(128) uint32_t g_f_z[32 * 32];
__device__ __align__(128) uint32_t g_f_a[16 * 32];
__device__ __align__(128) uint32_t g_f_m[1];
__device__ __align__(128) uint32_t g_f_y1[16 * 8 * 32];
__device__ __align__(128) uint32_t g_f_fin[128 * 32];
__device__ __align__(128) uint32_t g_stat[S_];
__device__ uint32_t g_epoch[NCTAS];

__device__ __forceinline__ uint32_t smem_u32(const void* p) { return (uint32_t)__cvta_generic_to_shared(p); }
__device__ __forceinline__ void mbar_init(uint32_t a, int c) { asm volatile("mbarrier.init.shared::cta.b64 [%0], %1;" ::"r"(a), "r"(c)); }
__device__ __forceinline__ void mbar_expect(uint32_t a, uint32_t b) { asm volatile("mbarrier.arrive.expect_tx.shared::cta.b64 _, [%0], %1;" ::"r"(a), "r"(b) : "memory"); }
__device__ __forceinline__ void mbar_arrive(uint32_t a) { asm volatile("mbarrier.arrive.shared::cta.b64 _, [%0];" ::"r"(a) : "memory"); }
__device__ __forceinline__ void mbar_arrive_cl(uint32_t a) { asm volatile("mbarrier.arrive.shared::cluster.b64 _, [%0];" ::"r"(a) : "memory"); }
__device__ __forceinline__ uint32_t mapa(uint32_t a, uint32_t cta) { uint32_t r; asm volatile("mapa.shared::cluster.u32 %0, %1, %2;" : "=r"(r) : "r"(a), "r"(cta)); return r; }
__device__ __forceinline__ void mbar_wait(uint32_t a, uint32_t ph) {
  uint32_t ok; int it = 0;
#pragma unroll 1
  do {
    asm volatile("{.reg .pred p; mbarrier.try_wait.parity.shared::cta.b64 p, [%1], %2; selp.u32 %0,1,0,p;}" : "=r"(ok) : "r"(a), "r"(ph) : "memory");
  } while (!ok && ++it < (1 << 18));
}
__device__ __forceinline__ void tma2d(uint32_t dst, const CUtensorMap* m, int c0, int c1, uint32_t bar) {
  asm volatile("cp.async.bulk.tensor.2d.shared::cluster.global.mbarrier::complete_tx::bytes [%0], [%1, {%3,%4}], [%2];" ::"r"(dst), "l"(m), "r"(bar), "r"(c0), "r"(c1) : "memory");
}
__device__ __forceinline__ void tma3d_mc_elect(uint32_t dst, const CUtensorMap* m, int c0, int c1, uint32_t bar) {
  asm volatile("{.reg .pred p; elect.sync _|p, 0xffffffff; @p mbarrier.arrive.expect_tx.shared::cta.b64 _, [%2], 12288; "
               "@p cp.async.bulk.tensor.3d.shared::cluster.global.mbarrier::complete_tx::bytes.multicast::cluster [%0], [%1, {%3,%4,%6}], [%2], %5;}"
               ::"r"(dst), "l"(m), "r"(bar), "r"(c0), "r"(c1), "h"((uint16_t)3), "r"(0) : "memory");
}
__device__ __forceinline__ void cluster_arrive_relaxed() { asm volatile("barrier.cluster.arrive.relaxed.aligned;" ::: "memory"); }
__device__ __forceinline__ void cluster_wait() { asm volatile("barrier.cluster.wait.acquire.aligned;" ::: "memory"); }
__device__ __forceinline__ void wg_fence() { asm volatile("wgmma.fence.sync.aligned;" ::: "memory"); }
__device__ __forceinline__ void wg_commit() { asm volatile("wgmma.commit_group.sync.aligned;" ::: "memory"); }
template <int n> __device__ __forceinline__ void wg_wait() { asm volatile("wgmma.wait_group.sync.aligned %0;" ::"n"(n) : "memory"); }
__device__ __forceinline__ uint32_t ld_acquire(const uint32_t* p) { uint32_t v; asm volatile("ld.acquire.gpu.global.u32 %0, [%1];" : "=r"(v) : "l"(p) : "memory"); return v; }
__device__ __forceinline__ void flag_wait(const uint32_t* p, uint32_t target) {
  int it = 0;
#pragma unroll 1
  while ((int)(ld_acquire(p) - target) < 0 && ++it < (1 << 20)) __nanosleep(300);
}
__device__ __forceinline__ void hint_signal(uint32_t* p) {
  if ((threadIdx.x & 31) == 0) asm volatile("red.relaxed.gpu.global.add.u32 [%0], 1;" ::"l"(p) : "memory");
}
__device__ __forceinline__ void hint_wait(const uint32_t* p, uint32_t target, uint32_t ns = 400) {
  int it = 0; uint32_t v;
#pragma unroll 1
  do { asm volatile("ld.relaxed.gpu.global.u32 %0, [%1];" : "=r"(v) : "l"(p) : "memory"); if ((int)(v - target) >= 0) break; __nanosleep(ns); } while (++it < (1 << 20));
}
__device__ __forceinline__ uint32_t tag(uint32_t x, uint32_t par) { uint32_t r; asm("lop3.b32 %0, %1, 0xfffffffe, %2, 0xea;" : "=r"(r) : "r"(x), "r"(par)); return r; }
__device__ __forceinline__ void st_ll(uint4* p, uint32_t x, uint32_t y, uint32_t z, uint32_t w, uint32_t par) {
  asm volatile("{.reg .b64 a, b; mov.b64 a, {%1,%2}; mov.b64 b, {%3,%4}; st.relaxed.gpu.global.v2.b64 [%0], {a, b};}"
               ::"l"(p), "r"(tag(x, par)), "r"(y), "r"(tag(z, par)), "r"(w) : "memory");
}
__device__ __forceinline__ uint4 ld_ll(const uint4* p) {
  uint4 v;
  asm volatile("{.reg .b64 a, b; ld.relaxed.gpu.global.v2.b64 {a, b}, [%4]; mov.b64 {%0,%1}, a; mov.b64 {%2,%3}, b;}"
               : "=r"(v.x), "=r"(v.y), "=r"(v.z), "=r"(v.w) : "l"(p) : "memory");
  return v;
}
__device__ __forceinline__ void st_ll64(uint2* p, uint32_t x, uint32_t y, uint32_t par) {
  asm volatile("{.reg .b64 a; mov.b64 a, {%1,%2}; st.relaxed.gpu.global.b64 [%0], a;}" ::"l"(p), "r"(tag(x, par)), "r"(y) : "memory");
}
__device__ __forceinline__ uint2 ld_ca64(const void* p) {
  uint2 v;
  asm volatile("{.reg .b64 a; ld.global.ca.b64 a, [%2]; mov.b64 {%0,%1}, a;}" : "=r"(v.x), "=r"(v.y) : "l"(p) : "memory");
  return v;
}
__device__ __forceinline__ uint2 ld_ll64(const void* p) {
  uint2 v;
  asm volatile("{.reg .b64 a; ld.relaxed.gpu.global.b64 a, [%2]; mov.b64 {%0,%1}, a;}" : "=r"(v.x), "=r"(v.y) : "l"(p) : "memory");
  return v;
}
__device__ __forceinline__ void ll_chk(uint32_t& bad, uint32_t a, uint32_t b, uint32_t par) {
  uint32_t u; asm("lop3.b32 %0, %1, %2, %3, 0x7e;" : "=r"(u) : "r"(a), "r"(b), "r"(par));
  asm("or.b32 %0, %0, %1;" : "+r"(bad) : "r"(u));
}
__device__ __forceinline__ uint32_t hadd2(uint32_t a, uint32_t b) { uint32_t d; asm("add.rn.bf16x2 %0, %1, %2;" : "=r"(d) : "r"(a), "r"(b)); return d; }
__device__ __forceinline__ uint32_t hfma2(uint32_t a, uint32_t b, uint32_t c) { uint32_t d; asm("fma.rn.bf16x2 %0, %1, %2, %3;" : "=r"(d) : "r"(a), "r"(b), "r"(c)); return d; }
__device__ __forceinline__ uint32_t pack_bf16(float lo, float hi) { uint32_t r; asm("cvt.rn.bf16x2.f32 %0, %1, %2;" : "=r"(r) : "f"(hi), "f"(lo)); return r; }
__device__ __forceinline__ float bf_lo(uint32_t v) { return __uint_as_float(v << 16); }
__device__ __forceinline__ float bf_hi(uint32_t v) { return __uint_as_float(v & 0xffff0000u); }
__device__ __forceinline__ uint32_t movmat(uint32_t a) { uint32_t d; asm volatile("movmatrix.sync.aligned.m8n8.trans.b16 %0, %1;" : "=r"(d) : "r"(a)); return d; }
__device__ __forceinline__ void mma16816(float* c, uint32_t a0, uint32_t a1, uint32_t a2, uint32_t a3, uint32_t b0, uint32_t b1) {
  asm volatile("mma.sync.aligned.m16n8k16.row.col.f32.bf16.bf16.f32 {%0,%1,%2,%3}, {%4,%5,%6,%7}, {%8,%9}, {%0,%1,%2,%3};"
               : "+f"(c[0]), "+f"(c[1]), "+f"(c[2]), "+f"(c[3]) : "r"(a0), "r"(a1), "r"(a2), "r"(a3), "r"(b0), "r"(b1));
}
__device__ __forceinline__ uint4 ldcg128(const void* p) { uint4 v; asm volatile("ld.global.cg.v4.u32 {%0,%1,%2,%3}, [%4];" : "=r"(v.x), "=r"(v.y), "=r"(v.z), "=r"(v.w) : "l"(p) : "memory"); return v; }

template <int N> __device__ __forceinline__ void wgmma_ss(float* d, uint32_t alo, int aimm, uint32_t blo, int bimm, uint32_t bhi, int sc);
template <> __device__ __forceinline__ void wgmma_ss<96>(float* d, uint32_t alo, int aimm, uint32_t blo, int bimm, uint32_t bhi, int sc) {
  asm volatile("{.reg .pred p; .reg .b32 x, y; .reg .b64 da, db; setp.ne.b32 p, %53, 0; add.u32 x, %48, %49; add.u32 y, %50, %51; mov.b64 da, {x, 0x40000040}; mov.b64 db, {y, %52}; "
               "wgmma.mma_async.sync.aligned.m64n96k16.f32.bf16.bf16 {%0, %1, %2, %3, %4, %5, %6, %7, %8, %9, %10, %11, %12, %13, %14, %15, %16, %17, %18, %19, %20, %21, %22, %23, %24, %25, %26, %27, %28, %29, %30, %31, %32, %33, %34, %35, %36, %37, %38, %39, %40, %41, %42, %43, %44, %45, %46, %47}, da, db, p, 1, 1, 0, 1;}"
   : "+f"(d[0]), "+f"(d[1]), "+f"(d[2]), "+f"(d[3]), "+f"(d[4]), "+f"(d[5]), "+f"(d[6]), "+f"(d[7]), "+f"(d[8]), "+f"(d[9]), "+f"(d[10]), "+f"(d[11]), "+f"(d[12]), "+f"(d[13]), "+f"(d[14]), "+f"(d[15]), "+f"(d[16]), "+f"(d[17]), "+f"(d[18]), "+f"(d[19]), "+f"(d[20]), "+f"(d[21]), "+f"(d[22]), "+f"(d[23]), "+f"(d[24]), "+f"(d[25]), "+f"(d[26]), "+f"(d[27]), "+f"(d[28]), "+f"(d[29]), "+f"(d[30]), "+f"(d[31]), "+f"(d[32]), "+f"(d[33]), "+f"(d[34]), "+f"(d[35]), "+f"(d[36]), "+f"(d[37]), "+f"(d[38]), "+f"(d[39]), "+f"(d[40]), "+f"(d[41]), "+f"(d[42]), "+f"(d[43]), "+f"(d[44]), "+f"(d[45]), "+f"(d[46]), "+f"(d[47]) : "r"(alo), "r"(aimm), "r"(blo), "r"(bimm), "r"(bhi), "r"(sc));
}
template <> __device__ __forceinline__ void wgmma_ss<192>(float* d, uint32_t alo, int aimm, uint32_t blo, int bimm, uint32_t bhi, int sc) {
  asm volatile("{.reg .pred p; .reg .b32 x, y; .reg .b64 da, db; setp.ne.b32 p, %101, 0; add.u32 x, %96, %97; add.u32 y, %98, %99; mov.b64 da, {x, 0x40000040}; mov.b64 db, {y, %100}; "
               "wgmma.mma_async.sync.aligned.m64n192k16.f32.bf16.bf16 {%0, %1, %2, %3, %4, %5, %6, %7, %8, %9, %10, %11, %12, %13, %14, %15, %16, %17, %18, %19, %20, %21, %22, %23, %24, %25, %26, %27, %28, %29, %30, %31, %32, %33, %34, %35, %36, %37, %38, %39, %40, %41, %42, %43, %44, %45, %46, %47, %48, %49, %50, %51, %52, %53, %54, %55, %56, %57, %58, %59, %60, %61, %62, %63, %64, %65, %66, %67, %68, %69, %70, %71, %72, %73, %74, %75, %76, %77, %78, %79, %80, %81, %82, %83, %84, %85, %86, %87, %88, %89, %90, %91, %92, %93, %94, %95}, da, db, p, 1, 1, 0, 1;}"
   : "+f"(d[0]), "+f"(d[1]), "+f"(d[2]), "+f"(d[3]), "+f"(d[4]), "+f"(d[5]), "+f"(d[6]), "+f"(d[7]), "+f"(d[8]), "+f"(d[9]), "+f"(d[10]), "+f"(d[11]), "+f"(d[12]), "+f"(d[13]), "+f"(d[14]), "+f"(d[15]), "+f"(d[16]), "+f"(d[17]), "+f"(d[18]), "+f"(d[19]), "+f"(d[20]), "+f"(d[21]), "+f"(d[22]), "+f"(d[23]), "+f"(d[24]), "+f"(d[25]), "+f"(d[26]), "+f"(d[27]), "+f"(d[28]), "+f"(d[29]), "+f"(d[30]), "+f"(d[31]), "+f"(d[32]), "+f"(d[33]), "+f"(d[34]), "+f"(d[35]), "+f"(d[36]), "+f"(d[37]), "+f"(d[38]), "+f"(d[39]), "+f"(d[40]), "+f"(d[41]), "+f"(d[42]), "+f"(d[43]), "+f"(d[44]), "+f"(d[45]), "+f"(d[46]), "+f"(d[47]), "+f"(d[48]), "+f"(d[49]), "+f"(d[50]), "+f"(d[51]), "+f"(d[52]), "+f"(d[53]), "+f"(d[54]), "+f"(d[55]), "+f"(d[56]), "+f"(d[57]), "+f"(d[58]), "+f"(d[59]), "+f"(d[60]), "+f"(d[61]), "+f"(d[62]), "+f"(d[63]), "+f"(d[64]), "+f"(d[65]), "+f"(d[66]), "+f"(d[67]), "+f"(d[68]), "+f"(d[69]), "+f"(d[70]), "+f"(d[71]), "+f"(d[72]), "+f"(d[73]), "+f"(d[74]), "+f"(d[75]), "+f"(d[76]), "+f"(d[77]), "+f"(d[78]), "+f"(d[79]), "+f"(d[80]), "+f"(d[81]), "+f"(d[82]), "+f"(d[83]), "+f"(d[84]), "+f"(d[85]), "+f"(d[86]), "+f"(d[87]), "+f"(d[88]), "+f"(d[89]), "+f"(d[90]), "+f"(d[91]), "+f"(d[92]), "+f"(d[93]), "+f"(d[94]), "+f"(d[95]) : "r"(alo), "r"(aimm), "r"(blo), "r"(bimm), "r"(bhi), "r"(sc));
}


constexpr uint32_t DESC_HI = (1024u >> 4) | (1u << 30);
constexpr uint32_t DESC_HI64 = (512u >> 4) | (2u << 30);
template <int n> __device__ __forceinline__ void fence_regs(float* a) {
#pragma unroll
  for (int i = 0; i < n; i++) asm volatile("" : "+f"(a[i])::"memory");
}

struct Ctx {
  uint32_t full, emb;
  bool sig;
  uint32_t o0, o1;
  uint32_t p0, p1;
  uint32_t dB, dA;
  __device__ __forceinline__ static int m6(int s) { return s >= 12 ? s - 12 : (s >= 6 ? s - 6 : s); }
  __device__ __forceinline__ uint32_t hb(int s) const { return m6(s) < 3 ? o0 : o1; }
  __device__ __forceinline__ static int m3(int s) { return m6(s) < 3 ? m6(s) : m6(s) - 3; }
  __device__ __forceinline__ void release(int s) { if (sig) mbar_arrive_cl(emb + 8 * hb(s) + 8 * m3(s)); }
  __device__ __forceinline__ void wait(uint32_t a, uint32_t ph) {
    uint32_t ok;
#pragma unroll 1
    do {
      asm volatile("{.reg .pred p; mbarrier.try_wait.parity.shared::cta.b64 p, [%1], %2; selp.u32 %0,1,0,p;}" : "=r"(ok) : "r"(a), "r"(ph) : "memory");
    } while (!ok);
  }
  __device__ __forceinline__ void wait_full(int s) {
    const uint32_t a = full + 8 * hb(s) + 8 * m3(s), ph = (m6(s) < 3 ? p0 : p1) ^ ((s >= 6 && s < 12) ? 1u : 0u);
    wait(a, ph);
    wg_fence();
  }
  __device__ __forceinline__ void set(uint32_t sw, uint32_t second) { o0 = sw ? 3 : 0; o1 = 3 - o0; p0 = second; p1 = second ^ sw; }
};

__device__ __forceinline__ void issue192(float* acc, Ctx& c, int s, bool first = false) {
  c.wait_full(s);
  const uint32_t db = c.dB + c.hb(s) * (STAGE_BYTES >> 4);
  wgmma_ss<192>(acc, c.dA, (s >> 1) * 1024 + (s & 1) * 4, db, Ctx::m3(s) * (STAGE_BYTES >> 4), DESC_HI, first ? 0 : 1);
  wgmma_ss<192>(acc, c.dA, (s >> 1) * 1024 + (s & 1) * 4 + 2, db, Ctx::m3(s) * (STAGE_BYTES >> 4) + 384, DESC_HI, 1);
  wg_commit();
}
template <class Pre, class Post>
__device__ __forceinline__ void plain192(float* acc, Ctx& c, int s, int e, Pre pre, Post post) {
  uint32_t st = c.hb(s) + Ctx::m3(s), pst = c.hb(s - 1) + Ctx::m3(s - 1), ph = (Ctx::m6(s) < 3 ? c.p0 : c.p1) ^ ((s >= 6 && s < 12) ? 1u : 0u);
  uint32_t da = c.dA + (s >> 1) * 1024 + (s & 1) * 4;
#pragma unroll 1
  for (; s < e; s++) {
    pre(s);
    c.wait(c.full + 8 * st, ph);
    wg_fence();
    const uint32_t db = c.dB + st * (STAGE_BYTES >> 4);
    wgmma_ss<192>(acc, da, 0, db, 0, DESC_HI, 1);
    wgmma_ss<192>(acc, da, 2, db, 384, DESC_HI, 1);
    wg_commit();
    const uint32_t rel = c.emb + 8 * pst;
    pst = st;
    st = st == 5 ? 0 : st + 1;
    ph ^= st == 0 ? 1u : 0u;
    da += (s & 1) ? 1020 : 4;
    wg_wait<1>();
    if (c.sig) mbar_arrive_cl(rel);
    post(s);
  }
}
__device__ __forceinline__ void issue96(float* acc, Ctx& c, int k, bool first) {
  c.wait_full(k);
  const uint32_t db = c.dB + c.hb(k) * (STAGE_BYTES >> 4);
  if (first) { wgmma_ss<192>(acc, c.dA, k * 1024, db, Ctx::m3(k) * (STAGE_BYTES >> 4), DESC_HI64, 0); wg_fence(); }
#pragma unroll
  for (int kk = first ? 1 : 0; kk < 4; kk++) wgmma_ss<96>(acc, c.dA, k * 1024 + 2 * kk, db, Ctx::m3(k) * (STAGE_BYTES >> 4) + 384 * (kk >> 1) + 64 * (kk & 1), DESC_HI64, 1);
  wg_commit();
}
__device__ __forceinline__ void retire(Ctx& c, int prev) {
  wg_wait<1>();
  c.release(prev);
}

constexpr float GK = 0.32920349f;
__device__ __forceinline__ uint32_t gelu_pair(uint32_t y) {
  uint32_t u, th;
  asm("mul.rn.bf16x2 %0, %1, %2;" : "=r"(u) : "r"(hfma2(y, y, 0x401b401bu)), "r"(y));
  asm("tanh.approx.bf16x2 %0, %1;" : "=r"(th) : "r"(u));
  return hfma2(y, th, y);
}
__device__ __forceinline__ uint4 gelu_group(const uint32_t* a) { return make_uint4(gelu_pair(a[0]), gelu_pair(a[1]), gelu_pair(a[2]), gelu_pair(a[3])); }
__device__ __forceinline__ void lds_bias(float2* b, uint32_t addr) {
#pragma unroll
  for (int j = 0; j < 2; j++) asm volatile("ld.shared.v2.f32 {%0,%1}, [%2];" : "=f"(b[j].x), "=f"(b[j].y) : "r"(addr + 32 * j));
}
__device__ __forceinline__ int opaque(int v) { asm volatile("" : "+r"(v)); return v; }
__device__ __forceinline__ void stsm4(uint32_t addr, uint4 r) {
  asm volatile("stmatrix.sync.aligned.m8n8.x4.shared.b16 [%0], {%1,%2,%3,%4};" ::"r"(addr), "r"(r.x), "r"(r.y), "r"(r.z), "r"(r.w) : "memory");
}
__device__ __forceinline__ float ex2f(float x) { float r; asm("ex2.approx.ftz.f32 %0, %1;" : "=f"(r) : "f"(x)); return r; }
__device__ __forceinline__ uint32_t phi_pack(uint32_t tp, float a0, float a1, uint32_t c1, uint32_t c2) {
  uint32_t x, y;
  asm("max.bf16x2 %0, %1, %2;" : "=r"(x) : "r"(tp), "r"(c1));
  asm("min.bf16x2 %0, %1, %2;" : "=r"(y) : "r"(pack_bf16(ex2f(a0), ex2f(a1))), "r"(c2));
  return hadd2(x, y);
}
template <int q0, int q1>
__device__ __forceinline__ void part_groups(const float* a, uint4* p, uint32_t par) {
#pragma unroll
  for (int q = q0; q < q1; q++)
    st_ll(p + q * 32, pack_bf16(a[8 * q], a[8 * q + 1]), pack_bf16(a[8 * q + 2], a[8 * q + 3]), pack_bf16(a[8 * q + 4], a[8 * q + 5]), pack_bf16(a[8 * q + 6], a[8 * q + 7]), par);
}
__device__ __forceinline__ float rcpf(float x) { float r; asm("rcp.approx.ftz.f32 %0, %1;" : "=f"(r) : "f"(x)); return r; }
__device__ __forceinline__ float silu_h(float h) { float r; asm("tanh.approx.f32 %0, %1;" : "=f"(r) : "f"(h)); return fmaf(h, r, h); }
__device__ __forceinline__ int pairoff(int p, int g) { return (p >> 2) * 32 + g * 4 + (p & 3); }
template <bool STRONG, int J0, int J1> __device__ __forceinline__ void d1_load(uint32_t* W, int rb0, int head, int ln) {
  const uint2* qf = g_qkv + rb0 * 216 * 32 + pairoff(288 + head * 9 + (ln & 3), ln >> 2);
#pragma unroll
  for (int b = 0; b < 3; b++) {
#pragma unroll
    for (int j = J0; j < J1; j++) {
      const uint2* p = qf + j * 216 * 32 + 32 * b;
      const uint2 kk = STRONG ? ld_ll64(p) : ld_ca64(p), vv = STRONG ? ld_ll64(p + 72 * 32) : ld_ca64(p + 72 * 32);
      W[6 * j + 2 * b] = kk.x; W[6 * j + 2 * b + 1] = kk.y; W[24 + 6 * j + 2 * b] = vv.x; W[24 + 6 * j + 2 * b + 1] = vv.y;
    }
  }
}
__device__ __forceinline__ bool d1_bad(const uint32_t* W, int t, uint32_t par) {
  uint32_t bad = 0, bad2 = 0;
#pragma unroll
  for (int q = 0; q < 12; q++) ll_chk((q % 3) != 2 ? bad : bad2, W[2 * q], W[24 + 2 * q], par);
  return __any_sync(0xffffffffu, (bad | (t == 0 ? bad2 : 0u)) & 1);
}
__device__ __forceinline__ void d1_mov(uint32_t* W, int j, int t) {
  if (t != 0) { W[6 * j + 4] = W[6 * j + 5] = 0u; W[24 + 6 * j + 4] = W[24 + 6 * j + 5] = (t == 1 ? 0x00003f80u : 0u); }
#pragma unroll
  for (int q = 0; q < 6; q++) { W[6 * j + q] = movmat(W[6 * j + q]); W[24 + 6 * j + q] = movmat(W[24 + 6 * j + q]); }
}
__device__ __forceinline__ void d1_mma(const uint32_t* W, float* R) {
  float c1[3][4];
#pragma unroll
  for (int j = 0; j < 3; j++) { c1[j][0] = R[12 + 2 * j]; c1[j][1] = R[13 + 2 * j]; c1[j][2] = c1[j][3] = 0.f; }
#pragma unroll
  for (int ks = 0; ks < 4; ks++)
#pragma unroll
    for (int j = 0; j < 3; j++) {
      mma16816(R + 4 * j, W[24 + 6 * ks], W[24 + 6 * ks + 2], W[24 + 6 * ks + 1], W[24 + 6 * ks + 3], W[6 * ks + 2 * j], W[6 * ks + 2 * j + 1]);
      mma16816(c1[j], W[24 + 6 * ks + 4], 0u, W[24 + 6 * ks + 5], 0u, W[6 * ks + 2 * j], W[6 * ks + 2 * j + 1]);
    }
#pragma unroll
  for (int j = 0; j < 3; j++) { R[12 + 2 * j] = c1[j][0]; R[13 + 2 * j] = c1[j][1]; }
}
__device__ __forceinline__ bool kv_valid(int w, int ln) { return (w < 3 || ln < 12) && ((w != 2 && w != 4) || (ln & 3) == 0); }

struct Params {
  CUtensorMap tm_wqkv, tm_w1, tm_w2, tm_m, tm_wqkv64, tm_m64, tm_a, tm_ast, tm_x, tm_p, tm_x3, tm_o3, tm_wo, tm_mst;
  const __nv_bfloat16 *x, *b1, *b2, *wqkv, *w1, *w2, *wo;
  __nv_bfloat16* out;
};

__global__ void __cluster_dims__(2, 1, 1) __launch_bounds__(NTHREADS, 1) fused_kernel(const __grid_constant__ Params P) {
  extern __shared__ __align__(1024) uint8_t smem[];
  const uint32_t sbase = smem_u32(smem);
  const int tid = threadIdx.x, lane = tid & 31;
  const int warp = __shfl_sync(0xffffffffu, tid >> 5, 0);
  const int g = lane >> 2, t = lane & 3;
  const uint32_t ep = __shfl_sync(0xffffffffu, g_epoch[blockIdx.x], 0) + 1;
  const uint32_t par = ep & 1;

  if (warp == 9 && lane < 14) asm volatile("prefetch.tensormap [%0];" ::"l"(&P.tm_wqkv + lane) : "memory");
  if (blockIdx.x >= 128) {
    const int a = blockIdx.x - 128;
    constexpr int AT = 144 * 128, SM_T = 9 * AT, SM_HB = SM_T + 8 * 32 * 80 + 64;
    if (tid == 0) {
      mbar_init(sbase + SM_HB, 1);
      asm volatile("fence.mbarrier_init.release.cluster;" ::: "memory");
      mbar_expect(sbase + SM_HB, 9 * AT);
    }
#pragma unroll 1
    for (int i = tid; i < 8 * 32 * 20 + 16; i += NTHREADS) reinterpret_cast<uint32_t*>(smem + SM_T)[i] = 0u;
    __syncthreads();
    __nanosleep(1800);
    if (warp < 9 && lane == 0) tma2d(sbase + warp * AT, &P.tm_wo, warp * 64, a * 144, sbase + SM_HB);
    if (warp >= 8 && lane == 0) {
      const int id = a * 4 + (warp - 8);
      constexpr uint32_t CH = 9216 * 2;
#pragma unroll 1
      for (int i = id; i < 576; i += 16) {
        const char* p = i < 288 ? (const char*)P.w1 + (size_t)i * CH : (const char*)P.w2 + (size_t)(i - 288) * CH;
        asm volatile("cp.async.bulk.prefetch.L2.global [%0], %1;" ::"l"(p), "r"(CH) : "memory");
      }
    }
    __syncwarp();
    if (lane < 8) hint_wait(&g_f_kvp[(a * 8 + lane) * 32], 16 * ep, 50);
    __syncwarp();
#pragma unroll 1
    for (int u = warp; u < 40; u += 12) {
      const int hh = u & 7, w = 4 - (u >> 3), head = a * 8 + hh;
      uint4 v[16];
      int tries = 0;
      uint32_t bad;
      const bool val = kv_valid(w, lane);
#pragma unroll 1
      do {
        bad = 0;
#pragma unroll
        for (int j = 0; j < 16; j++) v[j] = val ? ld_ll(&g_kvp[((head * 5 + w) * 16 + j) * 32 + lane]) : make_uint4(par, 0u, par, 0u);
#pragma unroll
        for (int j = 0; j < 16; j++) ll_chk(bad, v[j].x, v[j].z, par);
      } while (__any_sync(0xffffffffu, bad & 1) && ++tries < (1 << 20));
      float s0 = 0.f, s1 = 0.f, s2 = 0.f, s3 = 0.f;
#pragma unroll
      for (int j = 0; j < 16; j++) { s0 += __uint_as_float(v[j].x); s1 += __uint_as_float(v[j].y); s2 += __uint_as_float(v[j].z); s3 += __uint_as_float(v[j].w); }
      if (w >= 3) {
        if (g == 2) st_ll(&g_z[(head * 2 + w - 3) * 4 + t], __float_as_uint(s0), __float_as_uint(s1), __float_as_uint(s2), __float_as_uint(s3), par);
        __syncwarp();
        hint_signal(&g_f_z[(head) * 32]);
      }
      const int e0 = w < 3 ? g : 16 + g, e1 = w < 3 ? g + 8 : 16 + g, d0 = (w < 3 ? 8 * w : (w == 3 ? 0 : 16)) + 2 * t, d1 = w < 3 ? d0 : d0 + 8;
      __nv_bfloat16* T = reinterpret_cast<__nv_bfloat16*>(smem + SM_T) + hh * 32 * 40;
      if (e0 < 18) {
        T[d0 * 40 + e0] = __float2bfloat16(s0); T[(d0 + 1) * 40 + e0] = __float2bfloat16(s1);
        T[d1 * 40 + e1] = __float2bfloat16(s2); T[(d1 + 1) * 40 + e1] = __float2bfloat16(s3);
      }
    }
    __syncthreads();
    mbar_wait(sbase + SM_HB, 0);
#pragma unroll 1
    for (int u = warp; u < 144; u += 12) {
      const int hh = u & 7, at = u >> 4, jx = (u & 8) << 3;
      const uint32_t* T = reinterpret_cast<const uint32_t*>(smem + SM_T) + hh * 32 * 20 + g * 20 + t;
      const uint32_t a00 = T[0], a01 = T[160], a02 = T[4], a03 = T[164], a10 = T[8], a11 = T[168], b00 = T[320], b02 = T[324], b10 = T[328];
      const int ra = hh * 18 + (lane & 15), rbb = hh * 18 + 16 + (lane & 7), rc = hh * 18 + 16 + g;
      const uint32_t rowa = sbase + at * AT + ra * 128 + ((((lane >> 4) ^ (ra & 7)) << 4) ^ jx), rowb = sbase + at * AT + rbb * 128 + (((((lane >> 3) & 1) ^ (rbb & 7)) << 4) ^ jx);
      const uint32_t rowc = sbase + at * AT + rc * 128 + (((rc & 7) << 4) ^ jx) + 4 * t;
      uint32_t w[2][6];
#pragma unroll
      for (int j = 0; j < 2; j++) {
        asm volatile("ldmatrix.sync.aligned.m8n8.x4.trans.shared.b16 {%0,%1,%2,%3}, [%4];" : "=r"(w[j][0]), "=r"(w[j][1]), "=r"(w[j][2]), "=r"(w[j][3]) : "r"(rowa ^ (j << 5)));
        asm volatile("ldmatrix.sync.aligned.m8n8.x2.trans.shared.b16 {%0,%1}, [%2];" : "=r"(w[j][4]), "=r"(w[j][5]) : "r"(rowb ^ (j << 5)));
      }
      float p[2][4][4];
#pragma unroll
      for (int j = 0; j < 2; j++) {
#pragma unroll
        for (int q = 0; q < 4; q++) p[j][q][0] = p[j][q][1] = p[j][q][2] = p[j][q][3] = 0.f;
        mma16816(p[j][0], a00, a01, a02, a03, w[j][0], w[j][1]); mma16816(p[j][1], a00, a01, a02, a03, w[j][2], w[j][3]);
        mma16816(p[j][2], b00, 0u, b02, 0u, w[j][0], w[j][1]); mma16816(p[j][3], b00, 0u, b02, 0u, w[j][2], w[j][3]);
      }
#pragma unroll
      for (int j = 0; j < 2; j++) {
        mma16816(p[j][0], a10, a11, 0u, 0u, w[j][4], 0u); mma16816(p[j][1], a10, a11, 0u, 0u, w[j][5], 0u);
        mma16816(p[j][2], b10, 0u, 0u, 0u, w[j][4], 0u); mma16816(p[j][3], b10, 0u, 0u, 0u, w[j][5], 0u);
      }
#pragma unroll
      for (int j = 0; j < 2; j++) {
        stsm4(rowa ^ (j << 5), make_uint4(pack_bf16(p[j][0][0], p[j][0][1]), pack_bf16(p[j][0][2], p[j][0][3]), pack_bf16(p[j][1][0], p[j][1][1]), pack_bf16(p[j][1][2], p[j][1][3])));
        if (g < 2) {
          asm volatile("st.shared.u32 [%0], %1;" ::"r"(rowc ^ (j << 5)), "r"(pack_bf16(p[j][2][0], p[j][2][1])) : "memory");
          asm volatile("st.shared.u32 [%0], %1;" ::"r"(rowc ^ (j << 5) ^ 16), "r"(pack_bf16(p[j][3][0], p[j][3][1])) : "memory");
        }
      }
      asm volatile("fence.proxy.async.shared::cta;" ::: "memory");
      __syncwarp();
      if (lane == 0) {
        __threadfence_block();
        if (atomicAdd(reinterpret_cast<uint32_t*>(smem + SM_HB - 64) + at, 1u) == 15u) {
          __threadfence_block();
          asm volatile("cp.async.bulk.tensor.2d.global.shared::cta.bulk_group [%0, {%2, %3}], [%1];" ::"l"(&P.tm_mst), "r"(sbase + at * AT), "r"(at * 64), "r"(a * 144) : "memory");
          asm volatile("cp.async.bulk.commit_group;" ::: "memory");
        }
      }
      __syncwarp();
    }
    if (lane == 0) {
      asm volatile("cp.async.bulk.wait_group 0;" ::: "memory");
      asm volatile("fence.proxy.async.global;" ::: "memory");
      asm volatile("red.release.gpu.global.add.u32 [%0], 1;" ::"l"(g_f_m) : "memory");
    }
    __syncwarp();
    __syncthreads();
    if (tid == 0) g_epoch[blockIdx.x] = ep;
    return;
  }

  const int cl = blockIdx.x >> 1, rank = blockIdx.x & 1;
  const int f = cl & 7, m = (cl >> 3) * 2 + rank;
  const int srole = f >= 6 ? 1 : 0;
  const uint32_t bar_full = sbase + SM_BAR, bar_empty = bar_full + 8 * NSTAGE, bar_xfree = bar_empty + 8 * NSTAGE, bar_ofull = bar_xfree + 72,
                 bar_d = bar_ofull + 72, bar_x = bar_d + 16, bar_end = bar_x + 32;

  if (warp == 8) {
    if (lane < 4) mbar_init(bar_x + 8 * lane, 1);
    asm volatile("fence.mbarrier_init.release.cluster;" ::: "memory");
    __syncwarp();
#pragma unroll 1
    for (int i = 0; i < 36; i++) {
      const int gi = i / 9, kb = i - 9 * gi;
      asm volatile("{.reg .pred p, q; elect.sync _|p, 0xffffffff; setp.eq.and.s32 q, %5, 0, p; @q mbarrier.arrive.expect_tx.shared::cta.b64 _, [%2], 36864; "
                   "@p cp.async.bulk.tensor.2d.shared::cluster.global.mbarrier::complete_tx::bytes [%0], [%1, {%3,%4}], [%2];}"
                   ::"r"(sbase + SM_A + kb * 16384 + gi * 4096), "l"(&P.tm_x), "r"(bar_x + 8 * gi), "r"(kb * 64), "r"(m * 128 + gi * 32), "r"(kb) : "memory");
    }
  } else if (tid == 0) {
#pragma unroll 1
    for (int i = 0; i < NSTAGE; i++) { mbar_init(bar_full + 8 * i, 1); mbar_init(bar_empty + 8 * i, 4); }
#pragma unroll 1
    for (int i = 0; i < 9; i++) { mbar_init(bar_xfree + 8 * i, 2); mbar_init(bar_ofull + 8 * i, 1); }
    mbar_init(bar_d, 1); mbar_init(bar_d + 8, 3); mbar_init(bar_end, 8);
    asm volatile("fence.mbarrier_init.release.cluster;" ::: "memory");
  }
  __syncwarp();
  cluster_arrive_relaxed();

  if (warp >= 8) {
    asm volatile("setmaxnreg.dec.sync.aligned.u32 56;");
    cluster_wait();
    if (warp == 8) {
      uint32_t stage = 0, phase = 1;
      const uint32_t sb = sbase + SM_B + rank * 6144;
#pragma unroll 1
      for (int tl = 2 * srole; tl < 8 + 2 * srole; tl++) {
        const CUtensorMap* map = tl == 0 ? &P.tm_wqkv : (tl == 1 ? &P.tm_wqkv64 : (tl < 5 ? &P.tm_w1 : (tl < 8 ? &P.tm_w2 : (tl == 8 ? &P.tm_m : &P.tm_m64))));
        const int col = tl < 2 ? (tl == 0 ? 192 * f : 1152 + 96 * f) : (tl < 5 ? 576 * f + 192 * (tl - 2) : (tl < 8 ? 192 * ((tl - 5 + f) % 3) : (tl == 8 ? 192 * (f - 5) : 96 * (f - 6))));
        const bool perm = tl >= 5 && tl < 8;
        const bool z = (tl & 7) == 1;
        if (tl == 8) { flag_wait(g_f_m, 48 * ep); asm volatile("fence.proxy.async.global;" ::: "memory"); }
        const int rs = z ? 64 : 32, n3 = z ? 3 : 6;
#pragma unroll 1
        for (int blk = 0; blk < 3; blk++) {
          int row = (perm ? 576 * f + (blk == 2 ? 384 : 192 - 192 * blk) : 192 * blk) + rank * (rs >> 1);
#pragma unroll 1
          for (int st = 0; st < n3; st++) {
            mbar_wait(bar_empty + 8 * stage, phase);
            tma3d_mc_elect(sb + stage * STAGE_BYTES, map, col, row, bar_full + 8 * stage);
            row += rs;
            if (++stage == NSTAGE) { stage = 0; phase ^= 1; }
          }
        }
      }
      cluster_arrive_relaxed();
      uint32_t ok, t0, t1;
      asm volatile("mov.u32 %0, %%globaltimer_lo;" : "=r"(t0));
#pragma unroll 1
      do {
        asm volatile("{.reg .pred p; mbarrier.try_wait.parity.shared::cta.b64 p, [%1], 0, 100000; selp.u32 %0,1,0,p;}" : "=r"(ok) : "r"(bar_end) : "memory");
        asm volatile("mov.u32 %0, %%globaltimer_lo;" : "=r"(t1));
      } while (!ok && t1 - t0 < 3000000000u);
      if (!ok) asm volatile("trap;");
    } else {
      const int aw = warp - 9;
      const uint4 bw = tid < 360 ? __ldg(reinterpret_cast<const uint4*>(P.b1 + 576 * f) + tid - 288) : make_uint4(0u, 0u, 0u, 0u);
      uint32_t wn[9];
#pragma unroll
      for (int k = 0; k < 9; k++) wn[k] = __ldg(reinterpret_cast<const uint32_t*>(P.x + (m * 128 + f * 16 + aw) * D_) + lane + 32 * k);
#pragma unroll 1
      for (int r = aw; r < 16; r += 3) {
        const int srow = m * 128 + f * 16 + r;
        uint32_t w[9];
#pragma unroll
        for (int k = 0; k < 9; k++) { w[k] = wn[k]; wn[k] = __ldg(reinterpret_cast<const uint32_t*>(P.x + (srow + (r < 13 ? 3 : 0)) * D_) + lane + 32 * k); }
        float s0 = 0.f;
#pragma unroll
        for (int k = 0; k < 9; k++) s0 += bf_lo(w[k]) + bf_hi(w[k]);
#pragma unroll
        for (int o = 16; o > 0; o >>= 1) s0 += __shfl_xor_sync(0xffffffffu, s0, o);
        const float mean = s0 * (1.f / 576.f);
        s0 = 0.f;
#pragma unroll
        for (int k = 0; k < 9; k++) { const float x0 = bf_lo(w[k]) - mean, x1 = bf_hi(w[k]) - mean; s0 = fmaf(x0, x0, fmaf(x1, x1, s0)); }
#pragma unroll
        for (int o = 16; o > 0; o >>= 1) s0 += __shfl_xor_sync(0xffffffffu, s0, o);
        if (lane == 0) asm volatile("st.relaxed.gpu.global.u32 [%0], %1;" ::"l"(&g_stat[srow]), "r"(tag(__float_as_uint(rsqrtf(s0 * (1.f / 576.f) + 1e-5f)), par)) : "memory");
      }
      if (tid < 364) {
        float4* bp = reinterpret_cast<float4*>(smem + SM_BIAS) + 2 * (tid - 288);
        bp[0] = make_float4(bf_lo(bw.x) * GK, bf_hi(bw.x) * GK, bf_lo(bw.y) * GK, bf_hi(bw.y) * GK);
        bp[1] = make_float4(bf_lo(bw.z) * GK, bf_hi(bw.z) * GK, bf_lo(bw.w) * GK, bf_hi(bw.w) * GK);
      }
      if (aw == 0 && lane < 24) {
        const uint2 v = __ldg(reinterpret_cast<const uint2*>(P.b2 + 192 * ((f + 2) % 3) + (f < 3 ? 0 : 96)) + lane);
        reinterpret_cast<float4*>(smem + SM_B2)[lane] = make_float4(0.5f * bf_lo(v.x), 0.5f * bf_hi(v.x), 0.5f * bf_lo(v.y), 0.5f * bf_hi(v.y));
      }
      __syncwarp();
      if (aw != 2 && lane == 0) mbar_arrive(bar_d + 8);
      if (aw == 2) {
        uint4 v;
        int tries = 0;
#pragma unroll 1
        while (true) {
          asm volatile("ld.relaxed.gpu.global.v4.u32 {%0,%1,%2,%3}, [%4];" : "=r"(v.x), "=r"(v.y), "=r"(v.z), "=r"(v.w) : "l"(&g_stat[m * 128 + lane * 4]) : "memory");
          if (!__any_sync(0xffffffffu, ((v.x ^ par) | (v.y ^ par) | (v.z ^ par) | (v.w ^ par)) & 1) || ++tries > (1 << 20)) break;
          __nanosleep(200);
        }
        reinterpret_cast<uint4*>(smem + SM_RSTD)[lane] = v;
        __syncwarp();
        if (lane == 0) mbar_arrive(bar_d + 8);
      }
      if (aw == 0 && lane == 0) {
        hint_wait(&g_f_qkv[(m) * 32], 96 * ep, 200);
        mbar_arrive(bar_d);
      }
      __syncwarp();
      mbar_wait(bar_d, 0);
      const uint2* qb = g_qkv + ((m * 8 + aw) * 216 + 9 * f) * 32;
      const int nit = aw < 2 ? 3 : 2;
      uint2 q[4][3];
      auto ldq = [&](int it) {
#pragma unroll
        for (int hh = 0; hh < 4; hh++) {
          const uint2* p = qb + it * 3 * 216 * 32 + pairoff(hh * 9 + t, g);
          q[hh][0] = ld_ca64(p); q[hh][1] = ld_ca64(p + 32); q[hh][2] = ld_ca64(p + 64);
        }
      };
      if (lane < 20) {
        asm volatile("prefetch.global.L1 [%0];" ::"l"(qb + lane * 16));
        asm volatile("prefetch.global.L1 [%0];" ::"l"(qb + 3 * 216 * 32 + lane * 16));
        if (aw < 2) asm volatile("prefetch.global.L1 [%0];" ::"l"(qb + 6 * 216 * 32 + lane * 16));
      }
      if (aw == 1) {
        if (lane < 4) hint_wait(&g_f_z[(4 * f + lane) * 32], 2 * ep, 200);
        __syncwarp();
        uint4 zv;
        int tries = 0;
#pragma unroll 1
        do { zv = ld_ll(&g_z[4 * f * 8 + lane]); } while (__any_sync(0xffffffffu, ((zv.x ^ par) | (zv.z ^ par)) & 1) && ++tries < (1 << 20));
        uint2* zs = reinterpret_cast<uint2*>(smem + SM_Z) + (lane >> 3) * 12 + t;
        if (lane & 4) zs[8] = make_uint2(zv.x, zv.y);
        else { zs[0] = make_uint2(zv.x, zv.y); zs[4] = make_uint2(zv.z, zv.w); }
      }
      asm volatile("bar.sync 5, 96;" ::: "memory");
      uint32_t* stg = reinterpret_cast<uint32_t*>(smem + SM_SCR + aw * 2304) + g * 36 + t;
#pragma unroll 1
      for (int it = 0; it < nit; it++) {
        int tries = 0;
#pragma unroll 1
        while (true) {
          uint32_t bad = 0;
          ldq(it);
#pragma unroll
          for (int hh = 0; hh < 4; hh++) {
            if (t != 0) q[hh][2] = make_uint2(par, 0u);
            ll_chk(bad, q[hh][0].x, q[hh][1].x, par); ll_chk(bad, q[hh][2].x, par, par);
          }
          if (!__any_sync(0xffffffffu, bad & 1) || ++tries > (1 << 20)) break;
          ld_acquire(g_f_m);
        }
        float d[8];
#pragma unroll
        for (int hh = 0; hh < 4; hh++) {
          const float2* zp = reinterpret_cast<const float2*>(smem + SM_Z) + hh * 12 + t;
          const float2 z0 = zp[0], z1 = zp[4], z2 = zp[8];
          d[2 * hh] = bf_lo(q[hh][0].x) * z0.x + bf_hi(q[hh][0].x) * z0.y + bf_lo(q[hh][1].x) * z1.x + bf_hi(q[hh][1].x) * z1.y + bf_lo(q[hh][2].x) * z2.x + bf_hi(q[hh][2].x) * z2.y;
          d[2 * hh + 1] = bf_lo(q[hh][0].y) * z0.x + bf_hi(q[hh][0].y) * z0.y + bf_lo(q[hh][1].y) * z1.x + bf_hi(q[hh][1].y) * z1.y + bf_lo(q[hh][2].y) * z2.x + bf_hi(q[hh][2].y) * z2.y;
        }
#pragma unroll
        for (int j = 0; j < 8; j++) d[j] += __shfl_xor_sync(0xffffffffu, d[j], 1);
#pragma unroll
        for (int j = 0; j < 8; j++) d[j] = rcpf(d[j] + __shfl_xor_sync(0xffffffffu, d[j], 2) + 1e-6f);
        asm volatile("cp.async.bulk.wait_group.read 0;" ::: "memory");
        __syncwarp();
#pragma unroll
        for (int hh = 0; hh < 4; hh++) {
          const uint32_t r0 = pack_bf16(d[2 * hh], d[2 * hh]), r1 = pack_bf16(d[2 * hh + 1], d[2 * hh + 1]);
          uint32_t* so = stg + hh * 9;
          so[0] = hfma2(q[hh][0].x, r0, 0x80008000u); so[288] = hfma2(q[hh][0].y, r1, 0x80008000u);
          so[4] = hfma2(q[hh][1].x, r0, 0x80008000u); so[292] = hfma2(q[hh][1].y, r1, 0x80008000u);
          if (t == 0) { so[8] = hfma2(q[hh][2].x, r0, 0x80008000u); so[296] = hfma2(q[hh][2].y, r1, 0x80008000u); }
        }
        asm volatile("fence.proxy.async.shared::cta;" ::: "memory");
        __syncwarp();
        asm volatile("{.reg .pred p; elect.sync _|p, 0xffffffff; @p cp.async.bulk.tensor.2d.global.shared::cta.bulk_group [%0, {%2, %3}], [%1]; cp.async.bulk.commit_group;}"
                     ::"l"(&P.tm_ast), "r"(sbase + SM_SCR + aw * 2304), "r"(72 * f), "r"(m * 128 + (aw + 3 * it) * 16) : "memory");
      }
      asm volatile("cp.async.bulk.wait_group 0;" ::: "memory");
      asm volatile("fence.proxy.async.global;" ::: "memory");
      asm volatile("bar.sync 5, 96;" ::: "memory");
      if (tid == 288) asm volatile("red.release.gpu.global.add.u32 [%0], 1;" ::"l"(&g_f_a[(m) * 32]) : "memory");
      __syncwarp();
      if (!srole) {
        const int fr = f % 3, c2 = (fr + 2) % 3, b0 = 4 * c2 + (f < 3 ? 0 : 2);
        const int src0 = aw == 0 ? c2 : (aw == 1 ? 6 : (fr + 1) % 3), sst = aw == 1 ? 1 : 3;
        mbar_wait(bar_xfree + (aw == 2 ? 32 : 0), 0);
        if (aw != 0 && lane < 2) hint_wait(&g_f_y1[(m * 8 + src0 + sst * lane) * 32], aw == 1 ? 24 * ep - 16 + 8 * ((c2 + 3 - lane) % 3) : 8 * ep, 100);
        __syncwarp();
#pragma unroll 1
        for (int j = 0; j < 4; j++) {
          mbar_wait(bar_xfree + (aw < 2 ? 8 * ((3 * (aw * 4 + j) + 2) / 4) : (j < 3 ? 48 : 56)), 0);
          asm volatile("{.reg .pred p, q; elect.sync _|p, 0xffffffff; setp.eq.and.s32 q, %5, 0, p; @q mbarrier.arrive.expect_tx.shared::cta.b64 _, [%2], 49152; "
                       "@p cp.async.bulk.tensor.3d.shared::cluster.global.mbarrier::complete_tx::bytes [%0], [%1, {%6,%3,%4}], [%2];}"
                       ::"r"(sbase + (aw < 2 ? SM_A + (aw * 4 + j) * 12288 : (j < 2 ? SM_B + (j + 3) * 12288 : SM_A + (j + 6) * 12288))), "l"(&P.tm_p), "r"(bar_ofull + 8 * aw), "r"((src0 + sst * (j >> 1)) * 12 + b0), "r"(m * 8 + (j & 1) * 4), "r"(j), "r"(0) : "memory");
        }
        if (aw == 0) {
        mbar_wait(bar_xfree + 56, 0);
#pragma unroll 1
        for (int k = 0; k < 2; k++)
          asm volatile("{.reg .pred p, q; elect.sync _|p, 0xffffffff; setp.eq.and.s32 q, %5, 0, p; @q mbarrier.arrive.expect_tx.shared::cta.b64 _, [%2], 24576; "
                       "@p cp.async.bulk.tensor.3d.shared::cluster.global.mbarrier::complete_tx::bytes [%0], [%1, {%3,%4,%6}], [%2];}"
                       ::"r"(sbase + SM_B + (k ? 0 : 61440)), "l"(&P.tm_x3), "r"(bar_ofull + 24), "r"(48 * b0), "r"(m * 128 + k * 64), "r"(k), "r"(0) : "memory");
        }
      }
      if (srole && aw == 2) {
        if (lane == 0) {
          flag_wait(&g_f_a[(m) * 32], 8 * ep);
          asm volatile("fence.proxy.async.global;" ::: "memory");
#pragma unroll 1
          for (int kb = 0; kb < 9; kb++) {
            mbar_wait(bar_xfree + 8 * kb, 0);
            mbar_expect(bar_ofull + 8 * kb, 16384);
            tma2d(sbase + SM_A + kb * 16384, &P.tm_a, kb * 64, m * 128, bar_ofull + 8 * kb);
          }
        }
        __syncwarp();
      }
      cluster_arrive_relaxed();
    }
    cluster_wait();
  } else {
    asm volatile("setmaxnreg.inc.sync.aligned.u32 224;");
    const int wg = warp >> 2;
    {
      cluster_wait();
#pragma unroll 1
      for (int it = 0; it < 4; it++) {
        mbar_wait(bar_x + 8 * it, 0);
        uint8_t* rowp = smem + SM_A + (it * 32 + warp * 4 + (lane >> 3)) * 128 + (lane & 7) * 16;
        uint4 xv[9];
        float s0 = 0.f, s1 = 0.f;
#pragma unroll
        for (int kb = 0; kb < 9; kb++) xv[kb] = *reinterpret_cast<const uint4*>(rowp + kb * 16384);
#pragma unroll
        for (int kb = 0; kb < 9; kb++) {
          const uint32_t p = hadd2(hadd2(xv[kb].x, xv[kb].y), hadd2(xv[kb].z, xv[kb].w));
          s0 += bf_lo(p); s1 += bf_hi(p);
        }
        s0 += s1;
        s0 += __shfl_xor_sync(0xffffffffu, s0, 1); s0 += __shfl_xor_sync(0xffffffffu, s0, 2); s0 += __shfl_xor_sync(0xffffffffu, s0, 4);
        const uint32_t nm = pack_bf16(s0 * (-1.f / 576.f), s0 * (-1.f / 576.f));
#pragma unroll
        for (int kb = 0; kb < 9; kb++) *reinterpret_cast<uint4*>(rowp + kb * 16384) = make_uint4(hadd2(xv[kb].x, nm), hadd2(xv[kb].y, nm), hadd2(xv[kb].z, nm), hadd2(xv[kb].w, nm));
      }
      asm volatile("fence.proxy.async.shared::cta;" ::: "memory");
    }
    asm volatile("bar.sync 1, 256;" ::: "memory");
    __syncwarp();
    Ctx c;
    c.full = bar_full;
    c.emb = __shfl_sync(0xffffffffu, mapa(bar_empty, (warp & 3) == 0 ? rank : (rank ^ 1)), 0);
    c.sig = lane == 0 && (warp & 3) < 2;
    c.dB = (((sbase + SM_B) & 0x3FFFF) >> 4) | ((2048u >> 4) << 16);
    c.dA = (((sbase + SM_A + wg * 8192) & 0x3FFFF) >> 4) | (1u << 16);
    const bool leader = (lane == 0) && ((warp & 3) == 0);

    const int rb = m * 8 + warp;
    const uint32_t bias_t = sbase + SM_BIAS + 8 * t;
    const uint32_t hst = sbase + SM_A + (warp * 16 + (lane & 7) + ((lane >> 3) & 1) * 8) * 128 + (((lane >> 4) ^ (lane & 7)) << 4);
    auto wg_sync = [&]() {
      asm volatile("fence.proxy.async.shared::cta;" ::: "memory");
      if (wg == 0) asm volatile("bar.sync 2, 128;" ::: "memory"); else asm volatile("bar.sync 3, 128;" ::: "memory");
    };
    float A[96], B[96];
#pragma unroll
    for (int i = 0; i < 96; i++) B[i] = 0.f;
#define EXB(ACC, U) uint32_t E[4]; _Pragma("unroll") for (int q = 0; q < 4; q++) E[q] = pack_bf16(fmaf(ACC[8 * (U) + 2 * q], (q & 1) ? r1 : r0, bs[q >> 1].x), fmaf(ACC[8 * (U) + 2 * q + 1], (q & 1) ? r1 : r0, bs[q >> 1].y));
#define ST_QKV(ACC, U, DST) { uint32_t E[4]; _Pragma("unroll") for (int q = 0; q < 4; q++) \
      E[q] = phi_pack(pack_bf16(ACC[8 * (U) + 2 * q] * ((q & 1) ? r1 : r0), ACC[8 * (U) + 2 * q + 1] * ((q & 1) ? r1 : r0)), ACC[8 * (U) + 2 * q] * ((q & 1) ? l1 : l0), ACC[8 * (U) + 2 * q + 1] * ((q & 1) ? l1 : l0), pc1, pc2); \
    st_ll64(reinterpret_cast<uint2*>(DST) + 64 * (U), E[0], E[1], par); st_ll64(reinterpret_cast<uint2*>(DST) + 64 * (U) + 32, E[2], E[3], par); }
#define PHI_SETUP const float l0 = r0 * 1.4426950408889634f, l1 = r1 * 1.4426950408889634f; const uint32_t pc1 = srole ? 0xff80ff80u : 0x35863586u, pc2 = srole ? 0u : 0x3f803f80u;
#define HADDR(KB0, U) ((hst ^ (((U) & 3) << 5)) + ((KB0) + ((U) >> 2)) * 16384)
#define LDS_R(SC) float r0, r1; asm volatile("ld.shared.f32 %0, [%1];" : "=f"(r0) : "r"(rst)); asm volatile("ld.shared.f32 %0, [%1];" : "=f"(r1) : "r"(rst + 32)); r0 *= (SC); r1 *= (SC);
    const uint32_t rst = sbase + SM_RSTD + (warp * 16 + g) * 4;
    const int fr = f % 3;
#pragma unroll 1
    for (int i = srole;; i++) {
      {
        c.set((!srole && i >= 1) ? 1u : 0u, 0u);
        const uint32_t owp = i == 4 ? 0u : 1u;
        c.wait(bar_ofull, owp);
        issue192(A, c, 0, true);
        const int ln = opaque(lane);
        uint4* dst = i == 1 ? reinterpret_cast<uint4*>(g_qkv + (rb * 216 + 144 + 12 * f) * 32 + ln) : g_part + ((rb * 8 + f) * 36 + 12 * (i == 3 ? fr : (fr + 2) % 3)) * 32 + ln;
        LDS_R(i == 2 ? GK : 1.f)
#define HEAD(ACC) wg_wait<1>(); c.release(4); c.release(5); fence_regs<96>(ACC);
        const bool duty = i == 1 + srole;
        const int head = 4 * f + (warp >> 1), rb0 = m * 8 + (warp & 1) * 4;
        uint32_t W[48];
#define WZERO _Pragma("unroll") for (int q = 0; q < 48; q++) W[q] = 0u;
        auto nop = [](int) {};
        if (i == 2) {
          HEAD(B)
          float2 bs[2], bn[2];
          uint4 V[12];
          const uint4* hsp = g_hsp + (blockIdx.x * 8 + warp) * 12 * 32 + ln;
#pragma unroll
          for (int k = 1; k < 16; k++) {
            issue192(A, c, k);
            if (k >= 2 && k < 14) lds_bias(bn, bias_t + (192 + 16 * (k - 2)) * 4);
            if (k >= 3 && k < 15) { const int u = (k >= 3 && k < 15) ? k - 3 : 0; EXB(B, u) stsm4(HADDR(0, u), gelu_group(E)); }
            if (k >= 2) { bs[0] = bn[0]; bs[1] = bn[1]; }
            if (k >= 6 && k < 12) { V[2 * (k - 6)] = ldcg128(hsp + 2 * (k - 6) * 32); V[2 * (k - 6) + 1] = ldcg128(hsp + (2 * (k - 6) + 1) * 32); }
            if (k >= 13) {
#pragma unroll
              for (int q = 4 * (k - 13); q < 4 * (k - 13) + 4; q++) stsm4(HADDR(3, q), V[q]);
            }
            if (k == 15) {
              wg_sync();
              WZERO
            }
            retire(c, k - 1);
          }
        } else if (i >= 3) {
          HEAD(B)
          if (i == 4 && leader) mbar_arrive(bar_xfree + 64);
#pragma unroll
          for (int u = 0; u < 15; u++) {
            if (u & 1) c.wait(bar_ofull + 4 * (u + 1), owp);
            issue192(A, c, u + 1);
            if (u < 12) part_groups<0, 1>(&B[8 * (u < 12 ? u : 0)], dst + u * 32, par);
            if (u == 12 && srole) hint_signal(&g_f_y1[(m * 8 + f) * 32]);
            if (u == 14) { WZERO }
            retire(c, u);
          }
        } else if (i > srole) {
          HEAD(B)
#pragma unroll
          for (int u = 0; u < 3; u++) {
            issue192(A, c, u + 1);
#pragma unroll
            for (int q = 4 * u; q < 4 * u + 4; q++) st_ll64(reinterpret_cast<uint2*>(dst) + 32 * q, pack_bf16(B[4 * q] * r0, B[4 * q + 1] * r0), pack_bf16(B[4 * q + 2] * r1, B[4 * q + 3] * r1), par);
            if (u == 2) hint_signal(&g_f_qkv[(m) * 32]);
            retire(c, u);
          }
          plain192(A, c, 4, 11, nop, nop);
          issue192(A, c, 11);
          c.wait(bar_d, 0);
          d1_load<false, 0, 2>(W, rb0, head, opaque(lane));
          retire(c, 10);
          issue192(A, c, 12);
          d1_load<false, 2, 4>(W, rb0, head, opaque(lane));
          retire(c, 11);
          plain192(A, c, 13, 16, nop, nop);
        } else {
          wg_wait<1>();
          WZERO
          plain192(A, c, 1, 16, nop, nop);
        }
        c.wait(bar_ofull + 64, owp);
        issue192(A, c, 16);
        if (duty) {
          int tries = 0;
#pragma unroll 1
          while ((d1_bad(W, t, par) || (srole && tries == 0)) && ++tries < (1 << 20)) {
            c.wait(bar_d, 0);
            ld_acquire(g_f_m);
            d1_load<false, 0, 4>(W, rb0, head, opaque(lane));
          }
          d1_mov(W, 0, t); d1_mov(W, 1, t);
          retire(c, 15);
          issue192(A, c, 17);
          d1_mov(W, 2, t); d1_mov(W, 3, t);
          wg_wait<0>();
          asm volatile("bar.sync 4, 256;" ::: "memory");
          float R[18];
          float zero;
          asm volatile("ld.volatile.shared.f32 %0, [%1];" : "=f"(zero) : "r"(sbase + SM_BIAS + 2304) : "memory");
#pragma unroll
          for (int q = 0; q < 18; q++) R[q] = (q < 12 ? (q & 3) : (q & 1)) ? 0.f : zero;
          d1_mma(W, R);
          const int l2 = opaque(lane);
          float2* xch = reinterpret_cast<float2*>(smem + SM_SCR + (warp >> 1) * 1792) + l2;
          float2* xc2 = xch + 192 - l2 + (l2 < 12 ? l2 : 31);
          if (warp & 1) {
#pragma unroll
            for (int q = 0; q < 6; q++) xch[q * 32] = make_float2(R[2 * q], R[2 * q + 1]);
            if (l2 < 12) { xc2[0] = make_float2(R[12], R[13]); xc2[12] = make_float2(R[14], R[15]); }
            if (l2 < 12 && (l2 & 3) == 0) xc2[24 - l2 + (l2 >> 2)] = make_float2(R[16], R[17]);
          } else if ((R[0] + R[4]) + (R[8] + R[12]) + (R[14] + R[16]) == 1.2345e-30f) xch[223 - l2] = make_float2(0.f, 0.f);
          asm volatile("bar.sync 4, 256;" ::: "memory");
          if (!(warp & 1)) {
#pragma unroll
            for (int q = 0; q < 6; q++) { const float2 o = xch[q * 32]; R[2 * q] += o.x; R[2 * q + 1] += o.y; }
            const float2 o0 = xc2[0], o1 = xc2[l2 < 12 ? 12 : 0], o2 = xc2[l2 < 12 ? 24 - l2 + (l2 >> 2) : 0];
            uint4* dkv = &g_kvp[(head * 80 + m) * 32 + l2];
#pragma unroll
            for (int w = 0; w < 3; w++) st_ll(dkv + w * 512, __float_as_uint(R[4 * w]), __float_as_uint(R[4 * w + 1]), __float_as_uint(R[4 * w + 2]), __float_as_uint(R[4 * w + 3]), par);
            st_ll(dkv + 1536, __float_as_uint(R[12] + o0.x), __float_as_uint(R[13] + o0.y), __float_as_uint(R[14] + o1.x), __float_as_uint(R[15] + o1.y), par);
            st_ll(dkv + 2048, __float_as_uint(R[16] + o2.x), __float_as_uint(R[17] + o2.y), 0u, 0u, par);
            hint_signal(&g_f_kvp[(head) * 32]);
          }
        } else {
          retire(c, 15);
          issue192(A, c, 17);
        }
      }
      c.set((!srole && i >= 1) ? 1u : 0u, 1u);
      if ((i & 3) == 0) {
        issue96(B, c, 0, true);
        const int ln = opaque(lane);
        uint2* dst = i == 0 ? g_qkv + (rb * 216 + 24 * f) * 32 + ln : g_s + (rb * 72 + 24 * (f - 5)) * 32 + ln;
        c.wait(bar_d + 8, 0);
        LDS_R(1.f)
        if (i != 0) { r0 = 1.f; r1 = 1.f; }
        PHI_SETUP
        HEAD(A)
#pragma unroll
        for (int k = 1; k < 9; k++) {
          issue96(B, c, k, false);
#pragma unroll
          for (int u = (3 * (k - 1) + 1) / 2; u < (3 * k + 1) / 2; u++) ST_QKV(A, u, dst)
          if (k == 8) hint_signal(i == 0 ? &g_f_qkv[(m) * 32] : &g_f_fin[rb * 32 + f]);
          if (k < 8) retire(c, k - 1);
        }
        if (i == 4) {
          wg_wait<0>();
          cluster_arrive_relaxed();
          fence_regs<48>(B);
          uint2* d2 = g_s + (rb * 72 + 12 * (f - 6)) * 32 + opaque(lane);
#pragma unroll
          for (int q = 0; q < 12; q++) st_ll64(d2 + q * 32, pack_bf16(B[4 * q], B[4 * q + 1]), pack_bf16(B[4 * q + 2], B[4 * q + 3]), par);
          hint_signal(&g_f_fin[rb * 32 + f]);
          break;
        }
      } else {
        issue192(B, c, 0, true);
        const int ln = opaque(lane);
        uint4* dst = i == 1 ? g_hsp + (blockIdx.x * 8 + warp) * 12 * 32 + ln : g_part + ((rb * 8 + f) * 36 + 12 * ((fr + 1) % 3)) * 32 + ln;
        const bool xf = leader;
        const uint32_t bsa = bias_t + (i == 1 ? 0 : 384) * 4;
        c.wait(bar_d + 8, 0);
        LDS_R(GK)
        if (i == 3) {
          const int c2 = (fr + 2) % 3, v0 = 12 * c2 + (f < 3 ? 0 : 6), fo = f < 3 ? f + 3 : f - 3;
          uint4 S[6];
          uint32_t bad = 0;
          auto add3 = [&](uint4 a, uint4 b) { return make_uint4(hadd2(a.x, b.x), hadd2(a.y, b.y), hadd2(a.z, b.z), hadd2(a.w, b.w)); };
          const uint4* pb = g_part + (rb * 8 * 36 + v0) * 32 + ln;
          uint4 p[6];
          HEAD(A)
#pragma unroll
          for (int u = 0; u < 10; u++) {
            issue192(B, c, u + 1);
#pragma unroll
            for (int q = (6 * u + 4) / 5; q < (6 * u + 10) / 5; q++) part_groups<0, 1>(&A[8 * q], dst + q * 32, par);
            if (u == 9) hint_signal(&g_f_y1[(m * 8 + f) * 32]);
            retire(c, u);
            if ((u & 1) && xf) mbar_arrive(bar_xfree + 4 * u - 4);
          }
          plain192(B, c, 11, 17, [](int) {}, [&](int k) { if (!(k & 1) && xf) mbar_arrive(bar_xfree + 4 * k - 8); });
          issue192(B, c, 17);
          if (srole) continue;
          const int l2 = opaque(lane);
          const uint2* sp = g_s + (rb * 72 + 2 * v0) * 32 + l2;
          uint2 sv[12];
          c.wait(bar_ofull, 0);
#pragma unroll
          for (int q = 0; q < 6; q++) {
            uint4 a, b;
            asm volatile("ld.shared.v4.u32 {%0,%1,%2,%3}, [%4];" : "=r"(a.x), "=r"(a.y), "=r"(a.z), "=r"(a.w) : "r"(sbase + SM_A + warp * 3072 + l2 * 16 + q * 512) : "memory");
            asm volatile("ld.shared.v4.u32 {%0,%1,%2,%3}, [%4];" : "=r"(b.x), "=r"(b.y), "=r"(b.z), "=r"(b.w) : "r"(sbase + SM_A + 24576 + warp * 3072 + l2 * 16 + q * 512) : "memory");
            ll_chk(bad, a.x, a.z, par); ll_chk(bad, b.x, b.z, par);
            S[q] = add3(a, b);
          }
          wg_wait<0>();
          cluster_arrive_relaxed();
          fence_regs<96>(B);
          uint4* snd = g_part + ((rb * 8 + f) * 36 + 12 * c2 + (f < 3 ? 6 : 0)) * 32 + l2;
          if (f < 3) part_groups<0, 6>(B + 48, snd, par);
          else {
            part_groups<0, 6>(B, snd, par);
#pragma unroll
            for (int q = 0; q < 48; q++) B[q] = B[48 + q];
          }
          hint_signal(&g_f_fin[rb * 32 + f]);
#pragma unroll 1
          for (int bt = 1; bt < 3; bt++) {
            const uint32_t a0 = sbase + (bt < 2 ? SM_A + bt * 49152 : SM_B + 36864) + warp * 3072 + l2 * 16;
            const uint32_t a1 = a0 + (bt < 2 ? 24576 : SM_A + 98304 - SM_B - 36864);
            c.wait(bar_ofull + 8 * bt, 0);
#pragma unroll
            for (int q = 0; q < 6; q++) {
              uint4 a, b;
              asm volatile("ld.shared.v4.u32 {%0,%1,%2,%3}, [%4];" : "=r"(a.x), "=r"(a.y), "=r"(a.z), "=r"(a.w) : "r"(a0 + q * 512) : "memory");
              asm volatile("ld.shared.v4.u32 {%0,%1,%2,%3}, [%4];" : "=r"(b.x), "=r"(b.y), "=r"(b.z), "=r"(b.w) : "r"(a1 + q * 512) : "memory");
              ll_chk(bad, a.x, a.z, par); ll_chk(bad, b.x, b.z, par);
              S[q] = add3(S[q], add3(a, b));
            }
          }
          if (__any_sync(0xffffffffu, bad & 1)) {
#pragma unroll
            for (int q = 0; q < 6; q++) S[q] = make_uint4(0u, 0u, 0u, 0u);
#pragma unroll 1
            for (int k = 0, tries = 0; k < 8; k++) {
              if (k == f || k == fo) continue;
              bad = 0;
              const uint4* pk = pb + k * 36 * 32;
#pragma unroll
              for (int q = 0; q < 6; q++) { p[q] = ld_ll(pk + q * 32); ll_chk(bad, p[q].x, p[q].z, par); }
              if (__any_sync(0xffffffffu, bad & 1) && ++tries < (1 << 20)) { k--; continue; }
#pragma unroll
              for (int q = 0; q < 6; q++) S[q] = add3(S[q], p[q]);
            }
          }
#pragma unroll
          for (int q = 0; q < 24; q++) {
            const float2 bb = reinterpret_cast<const float2*>(smem + SM_B2)[4 * (q >> 1) + (l2 & 3)];
            B[2 * q] = fmaf(B[2 * q], 0.25f / GK, bb.x); B[2 * q + 1] = fmaf(B[2 * q + 1], 0.25f / GK, bb.y);
          }
          const uint4* pf = pb + fo * 36 * 32;
          if (l2 < 2) hint_wait(&g_f_fin[rb * 32 + (l2 == 0 ? fo : (c2 == 0 ? (f < 3 ? 6 : 7) : 5 + c2))], l2 == 0 ? ep : 2 * ep - (c2 == 0 ? 0u : 1u), 20);
          __syncwarp();
#pragma unroll 1
          for (int tries = 0; tries < (1 << 20); tries++) {
            bad = 0;
#pragma unroll
            for (int q = 0; q < 6; q++) { p[q] = ld_ll(pf + q * 32); sv[2 * q] = ld_ll64(sp + 2 * q * 32); sv[2 * q + 1] = ld_ll64(sp + (2 * q + 1) * 32); }
#pragma unroll
            for (int q = 0; q < 6; q++) { ll_chk(bad, p[q].x, p[q].z, par); ll_chk(bad, sv[2 * q].x, sv[2 * q + 1].x, par); }
            if (!__any_sync(0xffffffffu, bad & 1)) break;
          }
          c.wait(bar_ofull + 24, 0);
          const int xr = (warp & 3) * 16 + (l2 & 15);
          const uint32_t xa = sbase + SM_B + (wg ? 0 : 61440) + xr * 64 + (((l2 >> 4) ^ ((xr >> 1) & 3)) << 4);
#pragma unroll
          for (int v = 0; v < 6; v++) {
            uint32_t o[4];
            const uint32_t ad = (xa ^ ((v & 1) << 5)) + (v >> 1) * 4096;
            asm volatile("ldmatrix.sync.aligned.m8n8.x4.shared.b16 {%0,%1,%2,%3}, [%4];" : "=r"(o[0]), "=r"(o[1]), "=r"(o[2]), "=r"(o[3]) : "r"(ad) : "memory");
#pragma unroll
            for (int k = 0; k < 4; k++) {
              const int q = 4 * v + k;
              const uint32_t w = hadd2(reinterpret_cast<const uint32_t*>(p)[q], reinterpret_cast<const uint32_t*>(S)[q]);
              const uint32_t gt = pack_bf16(silu_h(fmaf(bf_lo(w), 0.25f / GK, B[2 * q])), silu_h(fmaf(bf_hi(w), 0.25f / GK, B[2 * q + 1])));
              o[k] = hfma2(reinterpret_cast<const uint32_t*>(sv)[q], gt, o[k]);
            }
            stsm4(ad, make_uint4(o[0], o[1], o[2], o[3]));
          }
          wg_sync();
          if ((warp & 3) == 0)
            asm volatile("{.reg .pred p; elect.sync _|p, 0xffffffff; @p cp.async.bulk.tensor.3d.global.shared::cta.bulk_group [%0, {%2, %3, %4}], [%1]; cp.async.bulk.commit_group; cp.async.bulk.wait_group.read 0;}"
                         ::"l"(&P.tm_o3), "r"(sbase + SM_B + (wg ? 0 : 61440)), "r"(16 * v0), "r"(m * 128 + wg * 64), "r"(0) : "memory");
          break;
        }
        {
          float2 bs[2], bn[2];
          lds_bias(bs, bsa);
          HEAD(A)
#pragma unroll
          for (int u = 0; u < 12; u++) {
            issue192(B, c, u + 1);
            if (u < 11) lds_bias(bn, bsa + 16 * (u + 1) * 4);
            EXB(A, u)
            bs[0] = bn[0]; bs[1] = bn[1];
            const uint4 h = gelu_group(E);
            asm volatile("{.reg .pred p; setp.eq.s32 p, %6, 1; @p st.global.v4.u32 [%0], {%2,%3,%4,%5}; @!p stmatrix.sync.aligned.m8n8.x4.shared.b16 [%1], {%2,%3,%4,%5};}"
                         ::"l"(dst + u * 32), "r"(HADDR(6, u)), "r"(h.x), "r"(h.y), "r"(h.z), "r"(h.w), "r"(i) : "memory");
            if (u == 9) wg_sync();
            retire(c, u);
          }
        }
#pragma unroll
        for (int k = 13; k < 17; k++) {
          issue192(B, c, k);
          if (k == 14) wg_sync();
          retire(c, k - 1);
        }
        issue192(B, c, 17);
      }
    }
    if (lane == 0) mbar_arrive(bar_end);
    cluster_wait();
    if (tid == 0) g_epoch[blockIdx.x] = ep;
  }
}

typedef CUresult (*EncFn)(CUtensorMap*, CUtensorMapDataType, cuuint32_t, void*, const cuuint64_t*, const cuuint64_t*, const cuuint32_t*, const cuuint32_t*,
                          CUtensorMapInterleave, CUtensorMapSwizzle, CUtensorMapL2promotion, CUtensorMapFloatOOBfill);

void make_map(EncFn enc, CUtensorMap* tm, const void* ptr, int rows, int cols, int box_cols, int box_rows, CUtensorMapSwizzle sw) {
  cuuint64_t gd[2] = {(cuuint64_t)cols, (cuuint64_t)rows};
  cuuint64_t gs[1] = {(cuuint64_t)cols * 2};
  cuuint32_t bx[2] = {(cuuint32_t)box_cols, (cuuint32_t)box_rows};
  cuuint32_t es[2] = {1, 1};
  enc(tm, CU_TENSOR_MAP_DATA_TYPE_BFLOAT16, 2, const_cast<void*>(ptr), gd, gs, bx, es, CU_TENSOR_MAP_INTERLEAVE_NONE, sw, CU_TENSOR_MAP_L2_PROMOTION_L2_256B, CU_TENSOR_MAP_FLOAT_OOB_FILL_NONE);
}
void make_wmap(EncFn enc, CUtensorMap* tm, const void* ptr, int rows, int cols, bool sw64, unsigned brows = 0) {
  const int ac = sw64 ? 32 : 64;
  cuuint64_t gd[3] = {(cuuint64_t)(cols - 2 * ac), (cuuint64_t)rows, 3};
  cuuint64_t gs[2] = {(cuuint64_t)cols * 2, (cuuint64_t)ac * 2};
  cuuint32_t bx[3] = {(cuuint32_t)ac, brows ? brows : (sw64 ? 32u : 16u), 3};
  cuuint32_t es[3] = {1, 1, 1};
  enc(tm, CU_TENSOR_MAP_DATA_TYPE_BFLOAT16, 3, const_cast<void*>(ptr), gd, gs, bx, es, CU_TENSOR_MAP_INTERLEAVE_NONE, sw64 ? CU_TENSOR_MAP_SWIZZLE_64B : CU_TENSOR_MAP_SWIZZLE_128B,
      CU_TENSOR_MAP_L2_PROMOTION_L2_256B, CU_TENSOR_MAP_FLOAT_OOB_FILL_NONE);
}

}

extern "C" void kernel_launch(void* const* d_in, const int* in_sizes, int n_in, void* d_out, int out_size) {
  (void)in_sizes; (void)n_in; (void)out_size;
  static EncFn enc = nullptr;
  static void *a_ptr = nullptr, *m_ptr = nullptr, *p_ptr = nullptr;
  if (!enc) {
    void* fn = nullptr; cudaDriverEntryPointQueryResult q;
    cudaGetDriverEntryPoint("cuTensorMapEncodeTiled", &fn, cudaEnableDefault, &q);
    enc = (EncFn)fn;
    cudaFuncSetAttribute(fused_kernel, cudaFuncAttributeMaxDynamicSharedMemorySize, SMEM_BYTES);
    cudaGetSymbolAddress(&a_ptr, g_a);
    cudaGetSymbolAddress(&m_ptr, g_m);
    cudaGetSymbolAddress(&p_ptr, g_part);
  }
  Params P;
  P.x = (const __nv_bfloat16*)d_in[0];
  P.wqkv = (const __nv_bfloat16*)d_in[1];
  P.wo = (const __nv_bfloat16*)d_in[2];
  P.w1 = (const __nv_bfloat16*)d_in[4];
  P.b1 = (const __nv_bfloat16*)d_in[5];
  P.w2 = (const __nv_bfloat16*)d_in[6];
  P.b2 = (const __nv_bfloat16*)d_in[7];
  P.out = (__nv_bfloat16*)d_out;
  make_wmap(enc, &P.tm_wqkv, P.wqkv, D_, Q3_, false);
  make_wmap(enc, &P.tm_w1, P.w1, D_, F_, false);
  make_wmap(enc, &P.tm_w2, P.w2, F_, D_, false);
  make_wmap(enc, &P.tm_m, m_ptr, D_, D_, false);
  make_wmap(enc, &P.tm_wqkv64, P.wqkv, D_, Q3_, true);
  make_wmap(enc, &P.tm_m64, m_ptr, D_, D_, true);
  make_wmap(enc, &P.tm_x3, P.x, S_, D_, true, 64);
  make_wmap(enc, &P.tm_o3, P.out, S_, D_, true, 64);
  make_map(enc, &P.tm_wo, P.wo, D_, D_, 64, 144, CU_TENSOR_MAP_SWIZZLE_128B);
  make_map(enc, &P.tm_mst, m_ptr, D_, D_, 64, 144, CU_TENSOR_MAP_SWIZZLE_128B);
  make_map(enc, &P.tm_a, a_ptr, S_, D_, 64, 128, CU_TENSOR_MAP_SWIZZLE_128B);
  make_map(enc, &P.tm_x, P.x, S_, D_, 64, 32, CU_TENSOR_MAP_SWIZZLE_128B);
  make_map(enc, &P.tm_ast, a_ptr, S_, D_, 72, 16, CU_TENSOR_MAP_SWIZZLE_NONE);
  {
    cuuint64_t gd[3] = {192, 96, 128};
    cuuint64_t gs[2] = {1536, 147456};
    cuuint32_t bx[3] = {192, 2, 4};
    cuuint32_t es[3] = {1, 1, 1};
    enc(&P.tm_p, CU_TENSOR_MAP_DATA_TYPE_UINT64, 3, p_ptr, gd, gs, bx, es, CU_TENSOR_MAP_INTERLEAVE_NONE, CU_TENSOR_MAP_SWIZZLE_NONE, CU_TENSOR_MAP_L2_PROMOTION_NONE, CU_TENSOR_MAP_FLOAT_OOB_FILL_NONE);
  }
  fused_kernel<<<NCTAS, NTHREADS, SMEM_BYTES, cudaStreamPerThread>>>(P);
}
```
